```python
import torch

def _softmax(x, axis=-1):
    return torch.softmax(x, dim=axis)
def _gelu(x):
    return torch.nn.functional.gelu(x, approximate="tanh")
def _silu(x):
    return torch.nn.functional.silu(x)
def _sigmoid(x):
    return torch.sigmoid(x)
def _layernorm(x, axis=-1, eps=1e-5):
    m = x.mean(dim=axis, keepdim=True)
    v = x.var(dim=axis, keepdim=True, unbiased=False)
    return (x - m) / torch.sqrt(v + eps)
def _scatter_add(tgt, idx, src, axis=0):
    return tgt.clone().index_add_(axis, idx, src)
def _segment_sum(src, seg, n):
    out = torch.zeros((n,) + src.shape[1:], dtype=src.dtype)
    return out.index_add_(0, seg, src)
def _pad(x, pw):
    flat = tuple(v for pair in reversed(pw) for v in pair)
    return torch.nn.functional.pad(x, flat)

kernel_name = 'concat_heads__sliding_local_dilated__spectral_fnet__prompt'

def setup_inputs():

    _w = (lambda a: (lambda t: t.to(torch.bfloat16) if t.is_floating_point() else t)(torch.as_tensor(a)))
    def _A_setup():
        B, S, D = 1, 2048, 448
        return {
            "x": _w((lambda *s: torch.randn(*s, dtype=torch.bfloat16) * 0.2)(B, S, D)),
            "wqkv": _w((lambda *s: torch.randn(*s, dtype=torch.bfloat16) * 0.8)(D, 3 * D)),
            "wo": _w((lambda *s: torch.randn(*s, dtype=torch.bfloat16) * 0.2)(D, D)),
        }
    _A_in = _A_setup()

    def _B_setup():
        B, S, D = 1, 2048, 448
        ns = torch.arange(S)[:, None] * torch.arange(S)[None, :]
        nd = torch.arange(D)[:, None] * torch.arange(D)[None, :]
        Ws_re = torch.cos(-2.0 * torch.pi * ns / S).to(float)
        Ws_im = torch.sin(-2.0 * torch.pi * ns / S).to(float)
        Wd_re = torch.cos(-2.0 * torch.pi * nd / D).to(float)
        Wd_im = torch.sin(-2.0 * torch.pi * nd / D).to(float)
        return {
            "x": _w((lambda *s: torch.randn(*s, dtype=torch.bfloat16) * 0.05)(B, S, D)),
            "dft_seq_re": _w(Ws_re),
            "dft_seq_im": _w(Ws_im),
            "dft_hid_re": _w(Wd_re),
            "dft_hid_im": _w(Wd_im),
        }
    _B_in = _B_setup()

    return {
        "A_x": _A_in["x"],
        "A_wqkv": _A_in["wqkv"],
        "A_wo": _A_in["wo"],
        "B_x": _B_in["x"],
        "B_dft_seq_re": _B_in["dft_seq_re"],
        "B_dft_seq_im": _B_in["dft_seq_im"],
        "B_dft_hid_re": _B_in["dft_hid_re"],
        "B_dft_hid_im": _B_in["dft_hid_im"],
    }

def reference(A_x, A_wqkv, A_wo, B_x, B_dft_seq_re, B_dft_seq_im, B_dft_hid_re, B_dft_hid_im):
    def _A_ref(x, wqkv, wo):
        B, S, D = x.shape
        H = 16; Dh = D // H
        W, dil = 8, 2
        qkv = (lambda x, *d: x.permute(*d))((x @ wqkv).reshape(B, S, 3, H, Dh), 2, 0, 3, 1, 4)
        q, k, v = qkv[0], qkv[1], qkv[2]
        scale = Dh ** -0.5
        pos = torch.arange(S)
        off = torch.arange(W) * dil
        idx = pos[:, None] - off[None, :]
        mask = idx >= 0
        idx_c = torch.where(mask, idx, 0).reshape(-1)
        kg = k[:, :, idx_c, :].reshape(B, H, S, W, Dh)
        vg = v[:, :, idx_c, :].reshape(B, H, S, W, Dh)
        logits = torch.einsum("bhsd,bhswd->bhsw", q, kg) * scale
        logits = torch.where(mask[None, None, :, :], logits, -1e9)
        attn = _softmax(logits, axis=-1)
        o = torch.einsum("bhsw,bhswd->bhsd", attn, vg)
        return (lambda x, *d: x.permute(*d))(o, 0, 2, 1, 3).reshape(B, S, D) @ wo

    def _B_ref(x, dft_seq_re, dft_seq_im, dft_hid_re, dft_hid_im):
        a = torch.einsum("bsd,ed->bse", x, dft_hid_re)
        b = torch.einsum("bsd,ed->bse", x, dft_hid_im)
        y = torch.einsum("ts,bse->bte", dft_seq_re, a) - torch.einsum("ts,bse->bte", dft_seq_im, b)
        return y

    a = _A_ref(A_x, A_wqkv, A_wo)
    b = _B_ref(B_x, B_dft_seq_re, B_dft_seq_im, B_dft_hid_re, B_dft_hid_im)
    return torch.concatenate([a, b], axis=-1)
```

```cpp
#include <cuda_runtime.h>
#include <cuda_bf16.h>
#include <cuda.h>
#include <stdint.h>

namespace {

constexpr int SEQ = 2048, DM = 448, NOUT = 896;
constexpr int NCTA = 128;
constexpr int SLOT_A = 16384, SLOT_B = 28672, SLOT_BYTES = SLOT_A + SLOT_B, NSLOT = 4;
constexpr int AB_BYTES = SLOT_A + 112 * 128;
constexpr int STG_OFF = NSLOT * SLOT_BYTES;
constexpr int STG_BYTES = 7 * 7168;
constexpr int KV_PITCH = 240;
constexpr int KV_OFF = 2 * 7168, KV_PAR = 72 * KV_PITCH;
#define OUT_A(j) (((j) < 2 ? 44 + 8 * (j) : (j) < 4 ? 116 + 8 * (j) : (j) == 5 ? 124 : 4 * (j) - 16) * 1024)
#define OUT_B(j) (((j) < 6 ? 176 + 8 * (j) : 60) * 1024)
#define OUT_O(p, j) (((p) ? ((j) < 3 ? 148 + 8 * (j) : (j) < 6 ? 8 * (j) - 8 : 68) : 68 + 8 * (j)) * 1024)
constexpr int BAR_OFF = STG_OFF + STG_BYTES;
constexpr int TR_OFF = BAR_OFF + 512;
constexpr int SMEM_BYTES = TR_OFF + 1024;
constexpr int SPIN_LIMIT = 1 << 24;
#define TUNE_LIST(X) \
    X(START_GAP1, 400, 50, 0, 900)   \
    X(START_GAP, 280, 30, 0, 500)   \
    X(WARM_N, 3, 1, 0, 6)   \
    X(WARM_GAP, 150, 50, 50, 500)   \
    X(ZERO_GAP, 100, 50, 0, 300)   \
    X(ZERO_AT, 900, 200, 0, 2400)   \
    X(ABS_AT1, 500, 100, 0, 1000)   \
    X(ABS_AT, 1500, 150, 300, 3000)   \
    X(ABS_GAP, 60, 40, 0, 400)   \
    X(ABS_GAP2, 230, 40, 0, 400)   \
    X(ABS_GAP3, 100, 40, 0, 400)   \
    X(POLL_AT, 3100, 100, 2000, 4000)   \
    X(POLL_AT1, 3600, 150, 2000, 5000)   \
    X(POLL_AT2, 6300, 200, 4000, 8000)   \
    X(POLL_AT3, 9200, 200, 6000, 11000)   \
    X(OPOLL_AT, 15400, 200, 13000, 17500)   \
    X(POLL_NS, 50, 100, 0, 800)   \
    X(OPOLL_NS, 100, 60, 0, 600)   \
    X(BIG_GAP, 250, 100, 0, 1000)   \
    X(W_GAP, 180, 100, 0, 900)   \
    X(HALO_WAIT, 350, 100, 0, 1500)   \
    X(O_GAP, 130, 60, 10, 600)   \
    X(PF_N, 0, 1, 0, 3)   \
    X(PF_E, 6, 1, 4, 13)   \
    X(PF_L, 14, 1, 4, 17)   \
    X(WO_AT, 7, 1, 5, 10)   \
    X(WB_AT, 10, 1, 10, 13)   \
    X(L_XAT, 13, 1, 10, 13)   \
    X(RED_GAP, 140, 30, 0, 300)   \
    X(RED_AT1, 0, 100, 0, 1000)   \
    X(RED_GAP1, 160, 30, 0, 300)   \

#define X(n, d, s, lo, hi) constexpr int n = d;
TUNE_LIST(X)
#undef X
#define TP(n) n
#define L_UP 1
#define ABL 0
#define BIG_ST 1
#define FLIP 1
#define URG(mt) ((((mt) >> 2) & 1) ^ FLIP)
#define AB_ST 7
#define AB_ST2 8
#define GAP_FLIP 1
#define L_PRE 1
#define E_FILL 2
#define KB_EARLY 14
#define O_N 2
#define QK_AT 10
#define WAIT_KIND 1
#define KV_FIRST 1
#define Q_ARR 11
#define E_SPLIT 7
#define RED_A 4
#define RED_FAST 6
#define L_ARR 11
#define START_N 2
#define REG_CONS 200
#define REG_AUX 104

struct __align__(64) TMaps { CUtensorMap xB, wdre, wdim, wre, wim, abP4, abP3, abH, ab32, ab80, wreH, wimH, wo64, xA3, wqkv3, outA, outB; };

__device__ __nv_bfloat16 g_abT[896 * SEQ];
__device__ uint4 g_o[SEQ * DM / 8];
__device__ uint4 g_halo[16 * 8 * 2 * 160];
__device__ unsigned g_flag_ab[40 * 32];
__device__ unsigned g_flag_o[16 * 32];
__device__ unsigned g_epoch[NCTA * 8];

__device__ __forceinline__ uint32_t smem_u32(const void* p) { return (uint32_t)__cvta_generic_to_shared(p); }
__device__ __forceinline__ uint32_t clk32() { uint32_t c; asm volatile("mov.u32 %0, %%clock;" : "=r"(c) :: "memory"); return c; }
__device__ __forceinline__ void give_up() { asm volatile("st.global.u32 [%0], 0;" :: "l"(0ull) : "memory"); }
__device__ __forceinline__ void mbar_init(uint32_t bar, uint32_t count) { asm volatile("mbarrier.init.shared::cta.b64 [%0], %1;" :: "r"(bar), "r"(count) : "memory"); }
__device__ __forceinline__ void mbar_expect_tx(uint32_t bar, uint32_t bytes) { asm volatile("mbarrier.arrive.expect_tx.shared::cta.b64 _, [%0], %1;" :: "r"(bar), "r"(bytes) : "memory"); }
__device__ __forceinline__ void mbar_arrive(uint32_t bar) { asm volatile("mbarrier.arrive.shared::cta.b64 _, [%0];" :: "r"(bar) : "memory"); }
__device__ __forceinline__ void mbar_arrive_remote(uint32_t bar, uint32_t cta) {
    asm volatile("{\n.reg .b32 ra;\nmapa.shared::cluster.u32 ra, %0, %1;\nmbarrier.arrive.shared::cluster.b64 _, [ra];\n}" :: "r"(bar), "r"(cta) : "memory");
}
__device__ __forceinline__ bool mbar_try_wait(uint32_t bar, uint32_t parity) {
    uint32_t ok;
    asm volatile("{\n.reg .pred p;\nmbarrier.try_wait.parity.shared::cta.b64 p, [%1], %2;\nselp.u32 %0, 1, 0, p;\n}" : "=r"(ok) : "r"(bar), "r"(parity) : "memory");
    return ok;
}
__device__ __forceinline__ bool mbar_test_wait(uint32_t bar, uint32_t parity) {
    uint32_t ok;
    asm volatile("{\n.reg .pred p;\nmbarrier.test_wait.parity.shared::cta.b64 p, [%1], %2;\nselp.u32 %0, 1, 0, p;\n}" : "=r"(ok) : "r"(bar), "r"(parity) : "memory");
    return ok;
}
#define WAIT_OP "pmevent 0;\nmbarrier.try_wait.parity.shared::cta.b64 p, [%0], %1;\n"
__device__ __forceinline__ void mbar_wait(uint32_t bar, uint32_t parity) {
    asm volatile("{\n.reg .pred p;\nWAIT:\n" WAIT_OP "@!p bra WAIT;\n}" :: "r"(bar), "r"(parity) : "memory");
}
__device__ __forceinline__ void mbar_wait_p(uint32_t bar, uint32_t parity) {
    asm volatile("{\n.reg .pred p;\nWAIT:\nmbarrier.try_wait.parity.shared::cta.b64 p, [%0], %1;\n@!p bra WAIT;\n}" :: "r"(bar), "r"(parity) : "memory");
}
__device__ __forceinline__ void mbar_wait_limit(uint32_t bar, uint32_t parity) {
    int it = 0;
    while (!mbar_try_wait(bar, parity)) { if (++it > SPIN_LIMIT) give_up(); }
}
__device__ __forceinline__ void tma_load(uint32_t dst, const CUtensorMap* tm, uint32_t bar, int c0, int c1) {
    asm volatile("cp.async.bulk.tensor.2d.shared::cluster.global.mbarrier::complete_tx::bytes [%0], [%1, {%3, %4}], [%2];"
        :: "r"(dst), "l"(tm), "r"(bar), "r"(c0), "r"(c1) : "memory");
}
__device__ __forceinline__ void tma_load_mc(uint32_t dst, const CUtensorMap* tm, uint32_t bar, int c0, int c1) {
    asm volatile("cp.async.bulk.tensor.2d.shared::cluster.global.mbarrier::complete_tx::bytes.multicast::cluster [%0], [%1, {%3, %4}], [%2], %5;"
        :: "r"(dst), "l"(tm), "r"(bar), "r"(c0), "r"(c1), "h"((uint16_t)3) : "memory");
}
__device__ __forceinline__ void tma_load3(uint32_t dst, const CUtensorMap* tm, uint32_t bar, int c0, int c1) {
    asm volatile("cp.async.bulk.tensor.3d.shared::cluster.global.mbarrier::complete_tx::bytes [%0], [%1, {%3, %4, %5}], [%2];"
        :: "r"(dst), "l"(tm), "r"(bar), "r"(c0), "r"(c1), "r"(0) : "memory");
}
__device__ __forceinline__ void tma_load3_mc(uint32_t dst, const CUtensorMap* tm, uint32_t bar, int c0, int c1, int c2) {
    asm volatile("cp.async.bulk.tensor.3d.shared::cluster.global.mbarrier::complete_tx::bytes.multicast::cluster [%0], [%1, {%3, %4, %6}], [%2], %5;"
        :: "r"(dst), "l"(tm), "r"(bar), "r"(c0), "r"(c1), "h"((uint16_t)3), "r"(c2) : "memory");
}
__device__ __forceinline__ void tma_prefetch(const CUtensorMap* tm, int c0, int c1) {
    asm volatile("cp.async.bulk.prefetch.tensor.2d.L2.global [%0, {%1, %2}];" :: "l"(tm), "r"(c0), "r"(c1) : "memory");
}
__device__ __forceinline__ void tma_prefetch3(const CUtensorMap* tm, int c0, int c1) {
    asm volatile("cp.async.bulk.prefetch.tensor.3d.L2.global [%0, {%1, %2, %3}];" :: "l"(tm), "r"(c0), "r"(c1), "r"(0) : "memory");
}
__device__ __forceinline__ void tma_store(const CUtensorMap* tm, uint32_t src, int c0, int c1) {
    asm volatile("cp.async.bulk.tensor.2d.global.shared::cta.bulk_group [%0, {%2, %3}], [%1];" :: "l"(tm), "r"(src), "r"(c0), "r"(c1) : "memory");
}
__device__ __forceinline__ void tma_store3(const CUtensorMap* tm, uint32_t src, int c1, int c2) {
    asm volatile("cp.async.bulk.tensor.3d.global.shared::cta.bulk_group [%0, {%2, %3, %4}], [%1];" :: "l"(tm), "r"(src), "r"(0), "r"(c1), "r"(c2) : "memory");
}
__device__ __forceinline__ void bulk_load(uint32_t dst, const void* src, uint32_t bytes, uint32_t bar) {
    asm volatile("cp.async.bulk.shared::cluster.global.mbarrier::complete_tx::bytes [%0], [%1], %2, [%3];" :: "r"(dst), "l"(src), "r"(bytes), "r"(bar) : "memory");
}
__device__ __forceinline__ void bulk_store(void* dst, uint32_t src, uint32_t bytes) {
    asm volatile("cp.async.bulk.global.shared::cta.bulk_group [%0], [%1], %2;" :: "l"(dst), "r"(src), "r"(bytes) : "memory");
}
__device__ __forceinline__ void tma_load5_mc(uint32_t dst, const CUtensorMap* tm, uint32_t bar, int c0, int c4) {
    asm volatile("cp.async.bulk.tensor.5d.shared::cluster.global.mbarrier::complete_tx::bytes.multicast::cluster [%0], [%1, {%3, %6, %6, %6, %4}], [%2], %5;"
        :: "r"(dst), "l"(tm), "r"(bar), "r"(c0), "r"(c4), "h"((uint16_t)3), "r"(0) : "memory");
}
__device__ __forceinline__ void red_add_bf16x8(__nv_bfloat16* p, uint32_t w0, uint32_t w1, uint32_t w2, uint32_t w3) {
    asm volatile("red.relaxed.gpu.global.add.noftz.v4.bf16x2 [%0], {%1, %2, %3, %4};" :: "l"(p), "r"(w0), "r"(w1), "r"(w2), "r"(w3) : "memory");
}
__device__ __forceinline__ void prefetch_tmap(const CUtensorMap* tm) { asm volatile("prefetch.tensormap [%0];" :: "l"(tm) : "memory"); }
__device__ __forceinline__ void cluster_arrive() { asm volatile("barrier.cluster.arrive.relaxed.aligned;" ::: "memory"); }
__device__ __forceinline__ void cluster_wait() { asm volatile("barrier.cluster.wait.aligned;" ::: "memory"); }
__device__ __forceinline__ void wgmma_fence() { asm volatile("wgmma.fence.sync.aligned;" ::: "memory"); }
__device__ __forceinline__ void wgmma_commit() { asm volatile("wgmma.commit_group.sync.aligned;" ::: "memory"); }
template<int N> __device__ __forceinline__ void wgmma_wait() { asm volatile("wgmma.wait_group.sync.aligned %0;" :: "n"(N) : "memory"); }
__device__ __forceinline__ void fence_async_smem() { asm volatile("fence.proxy.async.shared::cta;" ::: "memory"); }
__device__ __forceinline__ void fence_async_global() { asm volatile("fence.proxy.async.global;" ::: "memory"); }
__device__ __forceinline__ uint32_t desc_k(uint32_t addr) { return ((addr & 0x3FFFF) >> 4) | (1u << 16); }
__device__ __forceinline__ uint32_t desc_mn(uint32_t addr) { return ((addr & 0x3FFFF) >> 4) | ((8192u >> 4) << 16); }
template<int R> __device__ __forceinline__ void reg_set() {
    if (R > 168) asm volatile("setmaxnreg.inc.sync.aligned.u32 %0;" :: "n"(R));
    if (R < 168) asm volatile("setmaxnreg.dec.sync.aligned.u32 %0;" :: "n"(R));
}
__device__ __forceinline__ unsigned ld_acquire(const unsigned* p) { unsigned v; asm volatile("ld.acquire.gpu.global.u32 %0, [%1];" : "=r"(v) : "l"(p) : "memory"); return v; }
__device__ __forceinline__ unsigned ld_relaxed(const unsigned* p) { unsigned v; asm volatile("ld.relaxed.gpu.global.u32 %0, [%1];" : "=r"(v) : "l"(p) : "memory"); return v; }
__device__ __forceinline__ void st_release(unsigned* p, unsigned v) { asm volatile("fence.proxy.async.global;\nst.release.gpu.global.u32 [%0], %1;" :: "l"(p), "r"(v) : "memory"); }
__device__ __forceinline__ void red_release(unsigned* p, unsigned v) { asm volatile("fence.proxy.async.global;\nred.release.gpu.global.add.u32 [%0], %1;" :: "l"(p), "r"(v) : "memory"); }
__device__ __forceinline__ bool elect_one() {
    uint32_t pred;
    asm volatile("{\n.reg .pred p;\nelect.sync _|p, 0xffffffff;\nselp.u32 %0, 1, 0, p;\n}" : "=r"(pred));
    return pred;
}
__device__ __forceinline__ int pick3(int cta, int a, int b, int c) {
    int v;
    asm("{\n.reg .pred p, q;\nsetp.lt.s32 p, %1, 8;\nsetp.lt.s32 q, %1, 72;\nselp.b32 %0, %3, %4, q;\nselp.b32 %0, %2, %0, p;\n}" : "=&r"(v) : "r"(cta), "r"(a), "r"(b), "r"(c));
    return v;
}
template<typename T> __device__ __forceinline__ T pin(T v) {
    if constexpr (sizeof(T) == 8) asm volatile("" : "+l"(v) :: "memory"); else asm volatile("" : "+r"(v) :: "memory");
    return v;
}
__device__ __forceinline__ void bulk_commit() { asm volatile("cp.async.bulk.commit_group;" ::: "memory"); }
__device__ __forceinline__ void bulk_wait_all() { asm volatile("cp.async.bulk.wait_group 0;" ::: "memory"); }
__device__ __forceinline__ uint32_t pack_bf16(float lo, float hi) { uint32_t r; asm("cvt.rn.bf16x2.f32 %0, %1, %2;" : "=r"(r) : "f"(hi), "f"(lo)); return r; }
__device__ __forceinline__ float bf_lo(uint32_t w) { return __uint_as_float(w << 16); }
__device__ __forceinline__ float bf_hi(uint32_t w) { return __uint_as_float(w & 0xffff0000u); }
__device__ __forceinline__ void stsm_x4(uint32_t addr, uint32_t r0, uint32_t r1, uint32_t r2, uint32_t r3) {
    asm volatile("stmatrix.sync.aligned.m8n8.x4.shared.b16 [%0], {%1, %2, %3, %4};" :: "r"(addr), "r"(r0), "r"(r1), "r"(r2), "r"(r3) : "memory");
}
__device__ __forceinline__ void stsm_x2(uint32_t addr, uint32_t r0, uint32_t r1) {
    asm volatile("stmatrix.sync.aligned.m8n8.x2.shared.b16 [%0], {%1, %2};" :: "r"(addr), "r"(r0), "r"(r1) : "memory");
}
__device__ __forceinline__ void stsm_x4_t(uint32_t addr, uint32_t r0, uint32_t r1, uint32_t r2, uint32_t r3) {
    asm volatile("stmatrix.sync.aligned.m8n8.x4.trans.shared.b16 [%0], {%1, %2, %3, %4};" :: "r"(addr), "r"(r0), "r"(r1), "r"(r2), "r"(r3) : "memory");
}
__device__ __forceinline__ void stsm_x2_t(uint32_t addr, uint32_t r0, uint32_t r1) {
    asm volatile("stmatrix.sync.aligned.m8n8.x2.trans.shared.b16 [%0], {%1, %2};" :: "r"(addr), "r"(r0), "r"(r1) : "memory");
}
__device__ __forceinline__ uint32_t movm_t(uint32_t x) { uint32_t r; asm volatile("movmatrix.sync.aligned.m8n8.trans.b16 %0, %1;" : "=r"(r) : "r"(x)); return r; }
__device__ __forceinline__ void ldsm_x4(uint32_t addr, uint32_t& r0, uint32_t& r1, uint32_t& r2, uint32_t& r3) {
    asm volatile("ldmatrix.sync.aligned.m8n8.x4.shared.b16 {%0, %1, %2, %3}, [%4];" : "=r"(r0), "=r"(r1), "=r"(r2), "=r"(r3) : "r"(addr) : "memory");
}
__device__ __forceinline__ void ldsm_x4_t(uint32_t addr, uint32_t& r0, uint32_t& r1, uint32_t& r2, uint32_t& r3) {
    asm volatile("ldmatrix.sync.aligned.m8n8.x4.trans.shared.b16 {%0, %1, %2, %3}, [%4];" : "=r"(r0), "=r"(r1), "=r"(r2), "=r"(r3) : "r"(addr) : "memory");
}
__device__ __forceinline__ void mma16816(float (&d)[4], uint32_t a0, uint32_t a1, uint32_t a2, uint32_t a3, uint32_t b0, uint32_t b1) {
    asm("mma.sync.aligned.m16n8k16.row.col.f32.bf16.bf16.f32 {%0, %1, %2, %3}, {%4, %5, %6, %7}, {%8, %9}, {%0, %1, %2, %3};"
        : "+f"(d[0]), "+f"(d[1]), "+f"(d[2]), "+f"(d[3]) : "r"(a0), "r"(a1), "r"(a2), "r"(a3), "r"(b0), "r"(b1));
}
__device__ __forceinline__ void mma1688(float (&d)[4], uint32_t a0, uint32_t a1, uint32_t b0) {
    asm("mma.sync.aligned.m16n8k8.row.col.f32.bf16.bf16.f32 {%0, %1, %2, %3}, {%4, %5}, {%6}, {%0, %1, %2, %3};"
        : "+f"(d[0]), "+f"(d[1]), "+f"(d[2]), "+f"(d[3]) : "r"(a0), "r"(a1), "r"(b0));
}
__device__ __forceinline__ uint32_t max_bf16x2(uint32_t a, uint32_t b) { uint32_t r; asm("max.bf16x2 %0, %1, %2;" : "=r"(r) : "r"(a), "r"(b)); return r; }
__device__ __forceinline__ float bf16_round(float x) { return __bfloat162float(__float2bfloat16_rn(x)); }
__device__ __forceinline__ uint32_t lds32(uint32_t addr) { uint32_t v; asm volatile("ld.shared.u32 %0, [%1];" : "=r"(v) : "r"(addr)); return v; }
__device__ __forceinline__ float ex2_approx(float x) { float y; asm("ex2.approx.ftz.f32 %0, %1;" : "=f"(y) : "f"(x)); return y; }
__device__ __forceinline__ float rcp_approx(float x) { float y; asm("rcp.approx.ftz.f32 %0, %1;" : "=f"(y) : "f"(x)); return y; }
__device__ __forceinline__ void st_b128_relaxed(uint4* p, uint32_t w0, uint32_t w1, uint32_t w2, uint32_t w3) {
    asm volatile("{\n.reg .b128 t;\n.reg .b64 lo, hi;\nmov.b64 lo, {%1, %2};\nmov.b64 hi, {%3, %4};\nmov.b128 t, {lo, hi};\nst.relaxed.gpu.global.b128 [%0], t;\n}"
        :: "l"(p), "r"(w0), "r"(w1), "r"(w2), "r"(w3) : "memory");
}
__device__ __forceinline__ uint4 ld_b128_relaxed(const uint4* p) {
    uint4 v;
    asm volatile("{\n.reg .b128 t;\n.reg .b64 lo, hi;\nld.relaxed.gpu.global.b128 t, [%4];\nmov.b128 {lo, hi}, t;\nmov.b64 {%0, %1}, lo;\nmov.b64 {%2, %3}, hi;\n}"
        : "=r"(v.x), "=r"(v.y), "=r"(v.z), "=r"(v.w) : "l"(p) : "memory");
    return v;
}

template<int SA, int TB, int HA = 0x40000040, int M>
__device__ __forceinline__ void wgmma_n8(float (&d)[M], uint32_t da, uint32_t db, int scale_d) {
    asm volatile("{\n.reg .pred p;\n.reg .b32 hi, ha;\n.reg .b64 da, db;\nmov.b32 hi, 0x40000040;\nmov.b32 ha, %9;\nmov.b64 da, {%4, ha};\nmov.b64 db, {%5, hi};\nsetp.ne.b32 p, %6, 0;\n"
        "wgmma.mma_async.sync.aligned.m64n8k16.f32.bf16.bf16 "
        "{%0, %1, %2, %3}, "
        "da, db, p, %8, 1, 0, %7;\n}\n"
        : "+f"(d[0]), "+f"(d[1]), "+f"(d[2]), "+f"(d[3])
        : "r"(da), "r"(db), "r"(scale_d), "n"(TB), "n"(SA), "n"(HA));
}
template<int SA, int TB, int HA = 0x40000040, int M>
__device__ __forceinline__ void wgmma_n96(float (&d)[M], uint32_t da, uint32_t db, int scale_d) {
    asm volatile("{\n.reg .pred p;\n.reg .b32 hi, ha;\n.reg .b64 da, db;\nmov.b32 hi, 0x40000040;\nmov.b32 ha, %53;\nmov.b64 da, {%48, ha};\nmov.b64 db, {%49, hi};\nsetp.ne.b32 p, %50, 0;\n"
        "wgmma.mma_async.sync.aligned.m64n96k16.f32.bf16.bf16 "
        "{%0, %1, %2, %3, %4, %5, %6, %7, %8, %9, %10, %11, %12, %13, %14, %15, "
        "%16, %17, %18, %19, %20, %21, %22, %23, %24, %25, %26, %27, %28, %29, %30, %31, "
        "%32, %33, %34, %35, %36, %37, %38, %39, %40, %41, %42, %43, %44, %45, %46, %47}, "
        "da, db, p, %52, 1, 0, %51;\n}\n"
        : "+f"(d[0]), "+f"(d[1]), "+f"(d[2]), "+f"(d[3]), "+f"(d[4]), "+f"(d[5]), "+f"(d[6]), "+f"(d[7]),
          "+f"(d[8]), "+f"(d[9]), "+f"(d[10]), "+f"(d[11]), "+f"(d[12]), "+f"(d[13]), "+f"(d[14]), "+f"(d[15]),
          "+f"(d[16]), "+f"(d[17]), "+f"(d[18]), "+f"(d[19]), "+f"(d[20]), "+f"(d[21]), "+f"(d[22]), "+f"(d[23]),
          "+f"(d[24]), "+f"(d[25]), "+f"(d[26]), "+f"(d[27]), "+f"(d[28]), "+f"(d[29]), "+f"(d[30]), "+f"(d[31]),
          "+f"(d[32]), "+f"(d[33]), "+f"(d[34]), "+f"(d[35]), "+f"(d[36]), "+f"(d[37]), "+f"(d[38]), "+f"(d[39]),
          "+f"(d[40]), "+f"(d[41]), "+f"(d[42]), "+f"(d[43]), "+f"(d[44]), "+f"(d[45]), "+f"(d[46]), "+f"(d[47])
        : "r"(da), "r"(db), "r"(scale_d), "n"(TB), "n"(SA), "n"(HA));
}
template<int SA, int TB, int HA = 0x40000040, int M>
__device__ __forceinline__ void wgmma_n112(float (&d)[M], uint32_t da, uint32_t db, int scale_d) {
    asm volatile("{\n.reg .pred p;\n.reg .b32 hi, ha;\n.reg .b64 da, db;\nmov.b32 hi, 0x40000040;\nmov.b32 ha, %61;\nmov.b64 da, {%56, ha};\nmov.b64 db, {%57, hi};\nsetp.ne.b32 p, %58, 0;\n"
        "wgmma.mma_async.sync.aligned.m64n112k16.f32.bf16.bf16 "
        "{%0, %1, %2, %3, %4, %5, %6, %7, %8, %9, %10, %11, %12, %13, %14, %15, "
        "%16, %17, %18, %19, %20, %21, %22, %23, %24, %25, %26, %27, %28, %29, %30, %31, "
        "%32, %33, %34, %35, %36, %37, %38, %39, %40, %41, %42, %43, %44, %45, %46, %47, "
        "%48, %49, %50, %51, %52, %53, %54, %55}, "
        "da, db, p, %60, 1, 0, %59;\n}\n"
        : "+f"(d[0]), "+f"(d[1]), "+f"(d[2]), "+f"(d[3]), "+f"(d[4]), "+f"(d[5]), "+f"(d[6]), "+f"(d[7]),
          "+f"(d[8]), "+f"(d[9]), "+f"(d[10]), "+f"(d[11]), "+f"(d[12]), "+f"(d[13]), "+f"(d[14]), "+f"(d[15]),
          "+f"(d[16]), "+f"(d[17]), "+f"(d[18]), "+f"(d[19]), "+f"(d[20]), "+f"(d[21]), "+f"(d[22]), "+f"(d[23]),
          "+f"(d[24]), "+f"(d[25]), "+f"(d[26]), "+f"(d[27]), "+f"(d[28]), "+f"(d[29]), "+f"(d[30]), "+f"(d[31]),
          "+f"(d[32]), "+f"(d[33]), "+f"(d[34]), "+f"(d[35]), "+f"(d[36]), "+f"(d[37]), "+f"(d[38]), "+f"(d[39]),
          "+f"(d[40]), "+f"(d[41]), "+f"(d[42]), "+f"(d[43]), "+f"(d[44]), "+f"(d[45]), "+f"(d[46]), "+f"(d[47]),
          "+f"(d[48]), "+f"(d[49]), "+f"(d[50]), "+f"(d[51]), "+f"(d[52]), "+f"(d[53]), "+f"(d[54]), "+f"(d[55])
        : "r"(da), "r"(db), "r"(scale_d), "n"(TB), "n"(SA), "n"(HA));
}
template<int SA, int TB, int HA = 0x40000040, int M>
__device__ __forceinline__ void wgmma_n128(float (&d)[M], uint32_t da, uint32_t db, int scale_d) {
    asm volatile("{\n.reg .pred p;\n.reg .b32 hi, ha;\n.reg .b64 da, db;\nmov.b32 hi, 0x40000040;\nmov.b32 ha, %69;\nmov.b64 da, {%64, ha};\nmov.b64 db, {%65, hi};\nsetp.ne.b32 p, %66, 0;\n"
        "wgmma.mma_async.sync.aligned.m64n128k16.f32.bf16.bf16 "
        "{%0, %1, %2, %3, %4, %5, %6, %7, %8, %9, %10, %11, %12, %13, %14, %15, "
        "%16, %17, %18, %19, %20, %21, %22, %23, %24, %25, %26, %27, %28, %29, %30, %31, "
        "%32, %33, %34, %35, %36, %37, %38, %39, %40, %41, %42, %43, %44, %45, %46, %47, "
        "%48, %49, %50, %51, %52, %53, %54, %55, %56, %57, %58, %59, %60, %61, %62, %63}, "
        "da, db, p, %68, 1, 0, %67;\n}\n"
        : "+f"(d[0]), "+f"(d[1]), "+f"(d[2]), "+f"(d[3]), "+f"(d[4]), "+f"(d[5]), "+f"(d[6]), "+f"(d[7]),
          "+f"(d[8]), "+f"(d[9]), "+f"(d[10]), "+f"(d[11]), "+f"(d[12]), "+f"(d[13]), "+f"(d[14]), "+f"(d[15]),
          "+f"(d[16]), "+f"(d[17]), "+f"(d[18]), "+f"(d[19]), "+f"(d[20]), "+f"(d[21]), "+f"(d[22]), "+f"(d[23]),
          "+f"(d[24]), "+f"(d[25]), "+f"(d[26]), "+f"(d[27]), "+f"(d[28]), "+f"(d[29]), "+f"(d[30]), "+f"(d[31]),
          "+f"(d[32]), "+f"(d[33]), "+f"(d[34]), "+f"(d[35]), "+f"(d[36]), "+f"(d[37]), "+f"(d[38]), "+f"(d[39]),
          "+f"(d[40]), "+f"(d[41]), "+f"(d[42]), "+f"(d[43]), "+f"(d[44]), "+f"(d[45]), "+f"(d[46]), "+f"(d[47]),
          "+f"(d[48]), "+f"(d[49]), "+f"(d[50]), "+f"(d[51]), "+f"(d[52]), "+f"(d[53]), "+f"(d[54]), "+f"(d[55]),
          "+f"(d[56]), "+f"(d[57]), "+f"(d[58]), "+f"(d[59]), "+f"(d[60]), "+f"(d[61]), "+f"(d[62]), "+f"(d[63])
        : "r"(da), "r"(db), "r"(scale_d), "n"(TB), "n"(SA), "n"(HA));
}
template<int SA, int TB, int HA = 0x40000040, int M>
__device__ __forceinline__ void wgmma_n224(float (&d)[M], uint32_t da, uint32_t db, int scale_d) {
    asm volatile("{\n.reg .pred p;\n.reg .b32 hi, ha;\n.reg .b64 da, db;\nmov.b32 hi, 0x40000040;\nmov.b32 ha, %117;\nmov.b64 da, {%112, ha};\nmov.b64 db, {%113, hi};\nsetp.ne.b32 p, %114, 0;\n"
        "wgmma.mma_async.sync.aligned.m64n224k16.f32.bf16.bf16 "
        "{%0, %1, %2, %3, %4, %5, %6, %7, %8, %9, %10, %11, %12, %13, %14, %15, "
        "%16, %17, %18, %19, %20, %21, %22, %23, %24, %25, %26, %27, %28, %29, %30, %31, "
        "%32, %33, %34, %35, %36, %37, %38, %39, %40, %41, %42, %43, %44, %45, %46, %47, "
        "%48, %49, %50, %51, %52, %53, %54, %55, %56, %57, %58, %59, %60, %61, %62, %63, "
        "%64, %65, %66, %67, %68, %69, %70, %71, %72, %73, %74, %75, %76, %77, %78, %79, "
        "%80, %81, %82, %83, %84, %85, %86, %87, %88, %89, %90, %91, %92, %93, %94, %95, "
        "%96, %97, %98, %99, %100, %101, %102, %103, %104, %105, %106, %107, %108, %109, %110, %111}, "
        "da, db, p, %116, 1, 0, %115;\n}\n"
        : "+f"(d[0]), "+f"(d[1]), "+f"(d[2]), "+f"(d[3]), "+f"(d[4]), "+f"(d[5]), "+f"(d[6]), "+f"(d[7]),
          "+f"(d[8]), "+f"(d[9]), "+f"(d[10]), "+f"(d[11]), "+f"(d[12]), "+f"(d[13]), "+f"(d[14]), "+f"(d[15]),
          "+f"(d[16]), "+f"(d[17]), "+f"(d[18]), "+f"(d[19]), "+f"(d[20]), "+f"(d[21]), "+f"(d[22]), "+f"(d[23]),
          "+f"(d[24]), "+f"(d[25]), "+f"(d[26]), "+f"(d[27]), "+f"(d[28]), "+f"(d[29]), "+f"(d[30]), "+f"(d[31]),
          "+f"(d[32]), "+f"(d[33]), "+f"(d[34]), "+f"(d[35]), "+f"(d[36]), "+f"(d[37]), "+f"(d[38]), "+f"(d[39]),
          "+f"(d[40]), "+f"(d[41]), "+f"(d[42]), "+f"(d[43]), "+f"(d[44]), "+f"(d[45]), "+f"(d[46]), "+f"(d[47]),
          "+f"(d[48]), "+f"(d[49]), "+f"(d[50]), "+f"(d[51]), "+f"(d[52]), "+f"(d[53]), "+f"(d[54]), "+f"(d[55]),
          "+f"(d[56]), "+f"(d[57]), "+f"(d[58]), "+f"(d[59]), "+f"(d[60]), "+f"(d[61]), "+f"(d[62]), "+f"(d[63]),
          "+f"(d[64]), "+f"(d[65]), "+f"(d[66]), "+f"(d[67]), "+f"(d[68]), "+f"(d[69]), "+f"(d[70]), "+f"(d[71]),
          "+f"(d[72]), "+f"(d[73]), "+f"(d[74]), "+f"(d[75]), "+f"(d[76]), "+f"(d[77]), "+f"(d[78]), "+f"(d[79]),
          "+f"(d[80]), "+f"(d[81]), "+f"(d[82]), "+f"(d[83]), "+f"(d[84]), "+f"(d[85]), "+f"(d[86]), "+f"(d[87]),
          "+f"(d[88]), "+f"(d[89]), "+f"(d[90]), "+f"(d[91]), "+f"(d[92]), "+f"(d[93]), "+f"(d[94]), "+f"(d[95]),
          "+f"(d[96]), "+f"(d[97]), "+f"(d[98]), "+f"(d[99]), "+f"(d[100]), "+f"(d[101]), "+f"(d[102]), "+f"(d[103]),
          "+f"(d[104]), "+f"(d[105]), "+f"(d[106]), "+f"(d[107]), "+f"(d[108]), "+f"(d[109]), "+f"(d[110]), "+f"(d[111])
        : "r"(da), "r"(db), "r"(scale_d), "n"(TB), "n"(SA), "n"(HA));
}
template<int TB, int SA = 1>
__device__ __forceinline__ void wgmma_rs_n32(float (&d)[16], const uint32_t (&a)[4], uint32_t db, int scale_d) {
    asm volatile("{\n.reg .pred p;\n.reg .b32 hi;\n.reg .b64 db;\nmov.b32 hi, 0x40000040;\nmov.b64 db, {%20, hi};\nsetp.ne.b32 p, %21, 0;\n"
        "wgmma.mma_async.sync.aligned.m64n32k16.f32.bf16.bf16 "
        "{%0, %1, %2, %3, %4, %5, %6, %7, %8, %9, %10, %11, %12, %13, %14, %15}, "
        "{%16, %17, %18, %19}, db, p, %23, 1, %22;\n}\n"
        : "+f"(d[0]), "+f"(d[1]), "+f"(d[2]), "+f"(d[3]), "+f"(d[4]), "+f"(d[5]), "+f"(d[6]), "+f"(d[7]),
          "+f"(d[8]), "+f"(d[9]), "+f"(d[10]), "+f"(d[11]), "+f"(d[12]), "+f"(d[13]), "+f"(d[14]), "+f"(d[15])
        : "r"(a[0]), "r"(a[1]), "r"(a[2]), "r"(a[3]), "r"(db), "r"(scale_d), "n"(TB), "n"(SA));
}
template<int TB, int SA = 1>
__device__ __forceinline__ void wgmma_rs_n56(float (&d)[28], const uint32_t (&a)[4], uint32_t db, int scale_d) {
    asm volatile("{\n.reg .pred p;\n.reg .b32 hi;\n.reg .b64 db;\nmov.b32 hi, 0x40000040;\nmov.b64 db, {%32, hi};\nsetp.ne.b32 p, %33, 0;\n"
        "wgmma.mma_async.sync.aligned.m64n56k16.f32.bf16.bf16 "
        "{%0, %1, %2, %3, %4, %5, %6, %7, %8, %9, %10, %11, %12, %13, %14, %15, "
        "%16, %17, %18, %19, %20, %21, %22, %23, %24, %25, %26, %27}, "
        "{%28, %29, %30, %31}, db, p, %35, 1, %34;\n}\n"
        : "+f"(d[0]), "+f"(d[1]), "+f"(d[2]), "+f"(d[3]), "+f"(d[4]), "+f"(d[5]), "+f"(d[6]), "+f"(d[7]),
          "+f"(d[8]), "+f"(d[9]), "+f"(d[10]), "+f"(d[11]), "+f"(d[12]), "+f"(d[13]), "+f"(d[14]), "+f"(d[15]),
          "+f"(d[16]), "+f"(d[17]), "+f"(d[18]), "+f"(d[19]), "+f"(d[20]), "+f"(d[21]), "+f"(d[22]), "+f"(d[23]),
          "+f"(d[24]), "+f"(d[25]), "+f"(d[26]), "+f"(d[27])
        : "r"(a[0]), "r"(a[1]), "r"(a[2]), "r"(a[3]), "r"(db), "r"(scale_d), "n"(TB), "n"(SA));
}
template<int TB, int SA = 1>
__device__ __forceinline__ void wgmma_rs_n64(float (&d)[32], const uint32_t (&a)[4], uint32_t db, int scale_d) {
    asm volatile("{\n.reg .pred p;\n.reg .b32 hi;\n.reg .b64 db;\nmov.b32 hi, 0x40000040;\nmov.b64 db, {%36, hi};\nsetp.ne.b32 p, %37, 0;\n"
        "wgmma.mma_async.sync.aligned.m64n64k16.f32.bf16.bf16 "
        "{%0, %1, %2, %3, %4, %5, %6, %7, %8, %9, %10, %11, %12, %13, %14, %15, "
        "%16, %17, %18, %19, %20, %21, %22, %23, %24, %25, %26, %27, %28, %29, %30, %31}, "
        "{%32, %33, %34, %35}, db, p, %39, 1, %38;\n}\n"
        : "+f"(d[0]), "+f"(d[1]), "+f"(d[2]), "+f"(d[3]), "+f"(d[4]), "+f"(d[5]), "+f"(d[6]), "+f"(d[7]),
          "+f"(d[8]), "+f"(d[9]), "+f"(d[10]), "+f"(d[11]), "+f"(d[12]), "+f"(d[13]), "+f"(d[14]), "+f"(d[15]),
          "+f"(d[16]), "+f"(d[17]), "+f"(d[18]), "+f"(d[19]), "+f"(d[20]), "+f"(d[21]), "+f"(d[22]), "+f"(d[23]),
          "+f"(d[24]), "+f"(d[25]), "+f"(d[26]), "+f"(d[27]), "+f"(d[28]), "+f"(d[29]), "+f"(d[30]), "+f"(d[31])
        : "r"(a[0]), "r"(a[1]), "r"(a[2]), "r"(a[3]), "r"(db), "r"(scale_d), "n"(TB), "n"(SA));
}
template<int TB, int SA = 1>
__device__ __forceinline__ void wgmma_rs_n112(float (&d)[56], const uint32_t (&a)[4], uint32_t db, int scale_d) {
    asm volatile("{\n.reg .pred p;\n.reg .b32 hi;\n.reg .b64 db;\nmov.b32 hi, 0x40000040;\nmov.b64 db, {%60, hi};\nsetp.ne.b32 p, %61, 0;\n"
        "wgmma.mma_async.sync.aligned.m64n112k16.f32.bf16.bf16 "
        "{%0, %1, %2, %3, %4, %5, %6, %7, %8, %9, %10, %11, %12, %13, %14, %15, "
        "%16, %17, %18, %19, %20, %21, %22, %23, %24, %25, %26, %27, %28, %29, %30, %31, "
        "%32, %33, %34, %35, %36, %37, %38, %39, %40, %41, %42, %43, %44, %45, %46, %47, "
        "%48, %49, %50, %51, %52, %53, %54, %55}, "
        "{%56, %57, %58, %59}, db, p, %63, 1, %62;\n}\n"
        : "+f"(d[0]), "+f"(d[1]), "+f"(d[2]), "+f"(d[3]), "+f"(d[4]), "+f"(d[5]), "+f"(d[6]), "+f"(d[7]),
          "+f"(d[8]), "+f"(d[9]), "+f"(d[10]), "+f"(d[11]), "+f"(d[12]), "+f"(d[13]), "+f"(d[14]), "+f"(d[15]),
          "+f"(d[16]), "+f"(d[17]), "+f"(d[18]), "+f"(d[19]), "+f"(d[20]), "+f"(d[21]), "+f"(d[22]), "+f"(d[23]),
          "+f"(d[24]), "+f"(d[25]), "+f"(d[26]), "+f"(d[27]), "+f"(d[28]), "+f"(d[29]), "+f"(d[30]), "+f"(d[31]),
          "+f"(d[32]), "+f"(d[33]), "+f"(d[34]), "+f"(d[35]), "+f"(d[36]), "+f"(d[37]), "+f"(d[38]), "+f"(d[39]),
          "+f"(d[40]), "+f"(d[41]), "+f"(d[42]), "+f"(d[43]), "+f"(d[44]), "+f"(d[45]), "+f"(d[46]), "+f"(d[47]),
          "+f"(d[48]), "+f"(d[49]), "+f"(d[50]), "+f"(d[51]), "+f"(d[52]), "+f"(d[53]), "+f"(d[54]), "+f"(d[55])
        : "r"(a[0]), "r"(a[1]), "r"(a[2]), "r"(a[3]), "r"(db), "r"(scale_d), "n"(TB), "n"(SA));
}
template<int TB, int SA = 1>
__device__ __forceinline__ void wgmma_rs_n224(float (&d)[112], const uint32_t (&a)[4], uint32_t db, int scale_d) {
    asm volatile("{\n.reg .pred p;\n.reg .b32 hi;\n.reg .b64 db;\nmov.b32 hi, 0x40000040;\nmov.b64 db, {%116, hi};\nsetp.ne.b32 p, %117, 0;\n"
        "wgmma.mma_async.sync.aligned.m64n224k16.f32.bf16.bf16 "
        "{%0, %1, %2, %3, %4, %5, %6, %7, %8, %9, %10, %11, %12, %13, %14, %15, "
        "%16, %17, %18, %19, %20, %21, %22, %23, %24, %25, %26, %27, %28, %29, %30, %31, "
        "%32, %33, %34, %35, %36, %37, %38, %39, %40, %41, %42, %43, %44, %45, %46, %47, "
        "%48, %49, %50, %51, %52, %53, %54, %55, %56, %57, %58, %59, %60, %61, %62, %63, "
        "%64, %65, %66, %67, %68, %69, %70, %71, %72, %73, %74, %75, %76, %77, %78, %79, "
        "%80, %81, %82, %83, %84, %85, %86, %87, %88, %89, %90, %91, %92, %93, %94, %95, "
        "%96, %97, %98, %99, %100, %101, %102, %103, %104, %105, %106, %107, %108, %109, %110, %111}, "
        "{%112, %113, %114, %115}, db, p, %119, 1, %118;\n}\n"
        : "+f"(d[0]), "+f"(d[1]), "+f"(d[2]), "+f"(d[3]), "+f"(d[4]), "+f"(d[5]), "+f"(d[6]), "+f"(d[7]),
          "+f"(d[8]), "+f"(d[9]), "+f"(d[10]), "+f"(d[11]), "+f"(d[12]), "+f"(d[13]), "+f"(d[14]), "+f"(d[15]),
          "+f"(d[16]), "+f"(d[17]), "+f"(d[18]), "+f"(d[19]), "+f"(d[20]), "+f"(d[21]), "+f"(d[22]), "+f"(d[23]),
          "+f"(d[24]), "+f"(d[25]), "+f"(d[26]), "+f"(d[27]), "+f"(d[28]), "+f"(d[29]), "+f"(d[30]), "+f"(d[31]),
          "+f"(d[32]), "+f"(d[33]), "+f"(d[34]), "+f"(d[35]), "+f"(d[36]), "+f"(d[37]), "+f"(d[38]), "+f"(d[39]),
          "+f"(d[40]), "+f"(d[41]), "+f"(d[42]), "+f"(d[43]), "+f"(d[44]), "+f"(d[45]), "+f"(d[46]), "+f"(d[47]),
          "+f"(d[48]), "+f"(d[49]), "+f"(d[50]), "+f"(d[51]), "+f"(d[52]), "+f"(d[53]), "+f"(d[54]), "+f"(d[55]),
          "+f"(d[56]), "+f"(d[57]), "+f"(d[58]), "+f"(d[59]), "+f"(d[60]), "+f"(d[61]), "+f"(d[62]), "+f"(d[63]),
          "+f"(d[64]), "+f"(d[65]), "+f"(d[66]), "+f"(d[67]), "+f"(d[68]), "+f"(d[69]), "+f"(d[70]), "+f"(d[71]),
          "+f"(d[72]), "+f"(d[73]), "+f"(d[74]), "+f"(d[75]), "+f"(d[76]), "+f"(d[77]), "+f"(d[78]), "+f"(d[79]),
          "+f"(d[80]), "+f"(d[81]), "+f"(d[82]), "+f"(d[83]), "+f"(d[84]), "+f"(d[85]), "+f"(d[86]), "+f"(d[87]),
          "+f"(d[88]), "+f"(d[89]), "+f"(d[90]), "+f"(d[91]), "+f"(d[92]), "+f"(d[93]), "+f"(d[94]), "+f"(d[95]),
          "+f"(d[96]), "+f"(d[97]), "+f"(d[98]), "+f"(d[99]), "+f"(d[100]), "+f"(d[101]), "+f"(d[102]), "+f"(d[103]),
          "+f"(d[104]), "+f"(d[105]), "+f"(d[106]), "+f"(d[107]), "+f"(d[108]), "+f"(d[109]), "+f"(d[110]), "+f"(d[111])
        : "r"(a[0]), "r"(a[1]), "r"(a[2]), "r"(a[3]), "r"(db), "r"(scale_d), "n"(TB), "n"(SA));
}

#define TR(idx) do {} while (0)
#define TRL(idx) do {} while (0)
#define TRX(idx) do {} while (0)
#define TRG(idx) do {} while (0)
#define TR_END() do {} while (0)

template<int V> struct Int { static constexpr int value = V; };
constexpr float ATT_SCALE = 0.18898223650461361f;
constexpr float LOG2E = 1.4426950408889634f;
constexpr uint32_t MASKED = 0xce6ece6eu;

__global__ void __cluster_dims__(2, 1, 1) __launch_bounds__(384, 1)
fused_kernel(__nv_bfloat16* __restrict__ out,
    const __grid_constant__ TMaps tm) {
    extern __shared__ __align__(1024) uint8_t smem_raw[];
    const uint32_t sb = smem_u32(smem_raw);
    const uint32_t bars = sb + BAR_OFF;
    const uint32_t bar_full = bars, bar_empty = bars + 32, bar_abf = bars + 64  , bar_ab6 = bars + 120, bar_ab = bars + 128  , bar_free = bars + 296  , bar_halo = bars + 152;
    const uint32_t bar_o = bars + 160, bar_qkv = bars + 176  , bar_sf = bars + 200, bar_se = bar_sf + 32  ;
    const uint32_t bar_fl = bars + 256  , bar_go = bars + 240  , bar_end = bars + 192, bar_af = bars + 312;
    const uint32_t stg = sb + STG_OFF;
    const int cta = blockIdx.x, r = cta & 1, cl = cta >> 1, tq = (cl * 37 - 36 * 37) >> 8;
    const int mt = pick3(cta, r, (cta - 8) & 15, cta - 70 - 14 * tq);
    const int sub = pick3(cta, 4 + cl, (cta - 8) >> 4, 4 + tq);
    const CUtensorMap* tmWd = sub < 4 ? &tm.wdre : &tm.wdim;
    uint32_t t_first = 0;
    if (threadIdx.x < 32 + (((uint32_t)(uintptr_t)tmWd | sb | (mt << 6)) & 32) && elect_one()) {
        prefetch_tmap(tmWd); prefetch_tmap(&tm.xB);
        #pragma unroll
        for (int kb = 0; kb < START_N; kb++) {
            mbar_init(bar_abf + 8 * kb, 1);
            mbar_expect_tx(bar_abf + 8 * kb, AB_BYTES);
            tma_load(sb + kb * AB_BYTES + SLOT_A, tmWd, bar_abf + 8 * kb, kb * 64, (sub & 3) * 112);
            tma_load(sb + kb * AB_BYTES, &tm.xB, bar_abf + 8 * kb, kb * 64, mt * 128);
        }
        t_first = clk32();
    }
    const int tid = threadIdx.x, warp = __shfl_sync(0xffffffffu, tid >> 5, 0), lane = tid & 31;
    const bool late = sub < 4;
    const int nh = sub & 1, part = (sub >> 1) & 1;
    const int nj = late ? 32 - KB_EARLY : KB_EARLY;
    static_assert(KB_EARLY == 14, "order of the k-blocks");
    const uint32_t t0 = clk32();
    auto clear_out = [&]() {
        while ((int)(clk32() - t0) < TP(ZERO_AT)) { }
        uint4* zp = reinterpret_cast<uint4*>(out + (size_t)(mt * 128 + sub * 16 + (warp - 2) * 8) * NOUT + DM) + lane;
        #pragma unroll 1
        for (int j = 0; j < (ABL & 8 ? 0 : 8); j++) {
            while ((int)(clk32() - t0) < TP(ZERO_AT) + j * TP(ZERO_GAP)) { }
            zp[j * (NOUT / 8)] = make_uint4(0, 0, 0, 0);
            if (lane < 24) zp[j * (NOUT / 8) + 32] = make_uint4(0, 0, 0, 0);
        }
    };
    if (warp == 0) {
        if (elect_one()) {
            #pragma unroll
            for (int s = START_N; s < 7; s++) mbar_init(bar_abf + 8 * s, 1);
            #pragma unroll
            for (int s = 0; s < NSLOT; s++) { mbar_init(bar_full + 8 * s, 1); mbar_init(bar_empty + 8 * s, 4); }
            asm volatile("fence.mbarrier_init.release.cluster;" ::: "memory");
        }
        __syncwarp();
        cluster_arrive();
        if (elect_one()) {
            #pragma unroll 1
            for (int kb = START_N; kb < 7; kb++) {
                while ((int)(clk32() - t_first) < TP(START_GAP1) + (kb - START_N) * TP(START_GAP)) { }
                const uint32_t a = sb + kb * AB_BYTES, fb = bar_abf + 8 * kb;
                mbar_expect_tx(fb, AB_BYTES);
                tma_load(a, &tm.xB, fb, kb * 64, mt * 128);
                tma_load(a + SLOT_A, tmWd, fb, kb * 64, (sub & 3) * 112);
            }
            TR(2);
            prefetch_tmap(&tm.xA3); prefetch_tmap(&tm.wqkv3);
        }
        __syncwarp();
    } else if (warp < 4) {
        cluster_arrive();
        if (warp >= 2) clear_out();
    }
    if (warp < 4) {
      reg_set<REG_AUX>();
      const CUtensorMap* tmB = r ? &tm.abP3 : &tm.abP4;
      const uint32_t boff = SLOT_A + r * 16384;
      const int bgrp = part * 14 + nh * 7 + r * 4;
      if (warp == 0) {
        cluster_wait();
        if (elect_one()) {
        uint32_t slot = sb, fb = bar_full, par = 0;
        auto advance = [&]() { if (fb == bar_full + 24) { fb = bar_full; slot = sb; par ^= 1; } else { fb += 8; slot += SLOT_BYTES; } };
        const CUtensorMap* tmW = part ? &tm.wim : &tm.wre;
        const CUtensorMap* tmH = part ? &tm.wimH : &tm.wreH;
        const int qc = sub * 56 - (sub & 1) * 8;
        auto next_kc = [&](int kc, int wi) { return wi == 3 ? (late ? 14 * 64 : 2 * 64) : wi == nj / 2 - 1 ? (late ? 15 * 64 : 64) : kc + (FLIP && wi == 1 ? -768 : wi < nj / 2 ? 256 : 128); };
        #pragma unroll 1
        for (int it = 0; it < 7; it++) {
            mbar_wait_p(fb + 32, par);
            mbar_expect_tx(fb, SLOT_A + 3 * 8192);
            tma_load3(slot, &tm.xA3, fb, it * 64, mt * 64);
            tma_load3_mc(slot + SLOT_A + r * 12288, &tm.wqkv3, fb, qc, it * 64 + r * 32, 0);
            TRL(64 + it);
            if (r && it == 2) {
                const int c = (7 - sub) * 8 + (mt >> 1), c7 = (c * 37) >> 8;
                tma_prefetch3(&tm.xA3, (3 + (sub >> 1)) * 64, (mt - (sub & 1)) * 64);
                if (c7 < 8) tma_prefetch3(&tm.wqkv3, (c - 7 * c7) * 64, 192 + c7 * 32);
            }
            if (it == 1) { prefetch_tmap(tmW); prefetch_tmap(tmB); prefetch_tmap(tmH); }
            advance();
        }
        int kc = (late ? 1024 : 0) + 512 * FLIP;
        #pragma unroll 1
        for (int wi = 0; wi < nj - late; wi++) {
            mbar_wait_p(fb + 32, par);
            if (TP(W_GAP) && wi > 0 && wi < 4) { const uint32_t t1 = clk32() + TP(W_GAP); while ((int)(clk32() - t1) < 0) { } }
            mbar_expect_tx(fb, SLOT_BYTES);
            tma_load(slot, tmW, fb, kc, mt * 128);
            TR(224 + 7 + wi);
            if (wi >= 4) {
                if (wi == 4 || wi == nj / 2) mbar_wait(bar_fl + (wi == 4 ? 16 : 24), 0);
                tma_load5_mc(slot + boff, tmB, fb, kc, bgrp);
                TR(64 + 7 + wi);
            } else mbar_arrive(bar_go + 8 * wi);
            advance();
            kc = next_kc(kc, wi);
            if (wi == (late ? TP(PF_L) : TP(PF_E))) tma_prefetch(tmH, (late ? 29 : 13) * 64, mt * 128 + nh * 64);
            if (late) {
                if (wi == TP(L_XAT) - 1) {
                    mbar_wait(bar_se, 0);
                    mbar_expect_tx(bar_sf, SLOT_BYTES);
                    tma_load5_mc(stg + boff, tmB, bar_sf, 31 * 64, bgrp);
                }
                if (wi == TP(L_XAT)) tma_load(stg, tmW, bar_sf, 31 * 64, mt * 128);
            } else if (wi == TP(WB_AT)) {
                mbar_wait(bar_se, 0);
                #pragma unroll
                for (int j = 0; j < 6; j += 2) tma_load_mc(sb + OUT_B(j) + r * 8192, &tm.wo64, bar_abf, 256 + 48 * (sub & 3), (j + r) * 64);
            } else if (wi == TP(WO_AT) - 1) {
                const int c = mt * 4 + (sub & 3), c7 = (c * 37) >> 8;
                if (c < 49) tma_prefetch(&tm.wo64, (c - 7 * c7) * 64, c7 * 64); else prefetch_tmap(&tm.wo64);
            }
        }
        if (!late) {
            const uint4* const po = g_o + mt * 7168;
            const int ca = 64 * (sub & 3), cb = 256 + 48 * (sub & 3);
            auto load_w = [&](int d0, int c0, int j0, int d1, int c1, int j1, int g) { tma_load_mc(sb + (r ? d1 : d0), &tm.wo64, bar_abf + 8 * g, r ? c1 : c0, (r ? j1 : j0) * 64); };
            auto load_o = [&](int p, int j, int n, int g) { bulk_load(sb + OUT_O(p, j), po + p * 3584 + j * 512, n * 8192, bar_abf + 8 * g); };
            #pragma unroll
            for (int g = 0; g < 6; g++) mbar_expect_tx(bar_abf + 8 * g, (g == 0 ? 11 : g == 1 ? 4 : g == 2 ? 6 : g < 5 ? 3 : 1) * 8192);
            mbar_wait_p(bar_empty + 8, 1);
            load_w(OUT_A(0), ca, 0, OUT_A(1), ca, 1, 0);
            if (r == 0) load_w(OUT_B(6), cb, 6, 0, 0, 0, 0);
            TR(64 + 7 + KB_EARLY);
            mbar_wait_p(bar_fl + 32, 0);
            TR(3);
            load_o(0, 0, 2, 0);
            mbar_wait_p(bar_af, 0);
            load_w(OUT_A(2), ca, 2, OUT_A(3), ca, 3, 1); load_o(0, 2, 2, 1); load_w(OUT_A(4), ca, 4, OUT_A(6), ca, 6, 2);
            TR(64 + 7 + KB_EARLY + 1);
            mbar_wait_p(bar_empty + 16, 1);
            if (r) load_w(0, 0, 0, OUT_A(5), ca, 5, 2);
            load_o(0, 4, 3, 2);
            TR(64 + 7 + KB_EARLY + 2);
            mbar_wait_p(bar_empty + 24, 1);
            load_o(1, 0, 3, 3);
            TR(64 + 7 + KB_EARLY + 3);
            mbar_wait_p(bar_empty, 0);
            load_o(1, 3, 3, 4);
            TR(64 + 7 + KB_EARLY + 4);
            mbar_wait_p(bar_ab6, 0);
            load_o(1, 6, 1, 5);
            TR(64 + 7 + KB_EARLY + 5);
        }
        mbar_arrive(bar_end);
        }
      } else {
        const unsigned epoch = ld_relaxed(&g_epoch[cta * 8]) + 1;
        cluster_wait();
        auto forward = [&](const unsigned* fl, unsigned target, auto first, uint32_t bar, uint32_t again) {
            for (int spin = 0; !__all_sync(0xffffffffu, (int)(ld_acquire(fl) - target) >= 0);) {
                if ((int)(clk32() - again) < 0) { while ((int)(clk32() - again) < 0) { } } else __nanosleep(target != epoch ? TP(OPOLL_NS) : TP(POLL_NS));
                if (++spin > SPIN_LIMIT) give_up();
            }
            if (elect_one()) {
                fence_async_global();
                if constexpr (!decltype(first)::value) mbar_arrive(bar);
                else {
                    #pragma unroll
                    for (int i = 0; i < 2; i++) {
                        const int wi = 2 * (warp - 2) + i, sl = (wi + 3) & 3;
                        mbar_wait_limit(bar_go + 8 * wi, 0);
                        tma_load5_mc(sb + sl * SLOT_BYTES + boff, tmB, bar_full + 8 * sl, (late ? 1024 : 0) + 256 * (wi ^ 2 * FLIP), bgrp);
                        TR(64 + 7 + wi);
                        if (i == 0) { const uint32_t t1 = clk32() + TP(BIG_GAP); while ((int)(clk32() - t1) < 0) { } }
                    }
                }
            }
            __syncwarp();
        };
        const int frow = part * 4 + nh * 2 + (lane & 1), st0 = late ? 8 : 0;
        const int ft = late ? min(7 + (lane >> 1), 15) : min(lane >> 1, 6);
        const unsigned* const fl2 = &g_flag_ab[(32 + frow) * 32 + (late ? min(7 + (lane & 14), 15) : min(1 + (lane & 14), 5))];
        const unsigned* const fl3 = &g_flag_ab[(16 + 8 * (ft & 1) + frow) * 32 + ft];
        if (warp == 1) {
            if (elect_one()) {
                prefetch_tmap(&tm.abH); if (BIG_ST) { prefetch_tmap(&tm.ab80); prefetch_tmap(&tm.ab32); }
                const int e0 = pin(sub * 112 - (sub & 2) * 16), e1 = pin((sub & 3) == 2 ? 224 : 0);
                #pragma unroll 1
                for (int hf = 0; hf < 2; hf++) {
                    const int gap = pin(hf ? (r ? TP(ABS_GAP3) : TP(ABS_GAP2)) : (r ? TP(ABS_GAP) : 0)), sc = pin(mt * 128 + hf * 64);
                    const uint32_t src = pin(hf ? stg : sb + 7 * AB_BYTES);
                    unsigned* const fl = pin(&g_flag_ab[((hf ? 2 + r : r ? 4 : URG(mt)) * 8 + sub) * 32 + mt]);
                    mbar_wait(bar_ab + 8 * hf, 0);
                    fence_async_smem();
                    uint32_t t1 = clk32() + (hf ? 0 : r ? TP(ABS_AT) : URG(mt) * TP(ABS_AT1));
                    if (BIG_ST && (hf | r) == 0) {
                        if (URG(mt)) { while ((int)(clk32() - t1) < 0) { } }
                        TR(4);
                        tma_store(&tm.ab80, src + 4096, sc, e0 + 32);
                        tma_store(&tm.ab32, src, sc, e0 + e1);
                    } else
                    #pragma unroll
                    for (int i = 0; i < 7; i++) {
                        if (i == 0 || gap) { while ((int)(clk32() - t1) < 0) { } }
                        t1 += gap;
                        if (i == 0 && hf == 0) TR(4);
                        if (hf > r && i % 3 == 0 && i / 3 < TP(PF_N)) tma_prefetch(part ? &tm.wim : &tm.wre, (late ? 1024 : 0) + ((i / 3) ^ 2 * FLIP) * 256, (mt + nh) * 128);
                        tma_store(&tm.abH, src + i * 2048, sc, e0 + i * 16 + (i < 2 ? e1 : 0));
                    }
                    bulk_commit();
                    bulk_wait_all();
                    if (hf) TR(5);
                    mbar_arrive(bar_free + 8 * hf);
                    st_release(fl, epoch);
                    TR(hf ? 6 : 38);
                }
                uint4* const po = pin(g_o + mt * 7168 + sub * 448);
                mbar_wait(bar_o, 0);
                fence_async_smem();
                TR(9);
                {
                    uint32_t t2 = clk32();
                    #pragma unroll 1
                    for (int i = 0; i < 2 * O_N; i++) {
                        while ((int)(clk32() - t2) < 0) { }
                        t2 += TP(O_GAP);
                        bulk_store(po + (i >= O_N ? 3584 - 448 : 0) + i * (448 / O_N), stg + i * (7168 / O_N), 7168 / O_N);
                    }
                }
                bulk_commit();
                TR(62);
                bulk_wait_all();
                TR(111);
                mbar_arrive(bar_se); mbar_arrive_remote(bar_se, r ^ 1);
                red_release(&g_flag_o[mt * 32], 1);
                TR(17); TRG(102);
                if (!late) {
                    prefetch_tmap(&tm.outA); prefetch_tmap(&tm.outB);
                    #pragma unroll
                    for (int c = 0; c < 2; c++) {
                        mbar_wait(bar_qkv + 8 * c, 1);
                        fence_async_smem();
                        tma_store3(c ? &tm.outB : &tm.outA, sb + OUT_O(0, 1) + c * 8192, mt * 64, sub & 3);
                    }
                    bulk_commit();
                    asm volatile("cp.async.bulk.wait_group.read 0;" ::: "memory");
                    TR(19);
                }
            }
            __syncwarp();
        } else {
            asm volatile("st.shared.u32 [%0], %1;" :: "r"(bars + 168), "r"(epoch) : "memory");
            __syncwarp();
            if (lane == 0) mbar_arrive(bar_ab + 8);
            mbar_wait_limit(bar_ab, 0);
            const uint32_t ta = clk32();
            if (tid == 96) TRG(98);
            const bool rest = warp == 3 && __all_sync(0xffffffffu, (int)(ld_acquire(lane >= 22 ? fl2 : fl3) - epoch) >= 0);
            forward(&g_flag_ab[((warp - 2) * 8 + frow) * 32 + st0 + 4 * ((warp - 2) ^ FLIP) + (lane & 2)], epoch, Int<1>(), 0, ta + (warp == 2 ? TP(POLL_AT) : TP(POLL_AT1)));
            if (warp == 2) {
                const uint4* const hp = pin(g_halo + (max(mt - 1, 0) * 8 + sub) * 320 + lane);
                const uint32_t ha = pin(stg + KV_OFF + (lane & 7) * KV_PITCH + (lane >> 3) * 16);
                mbar_wait(mt > 0 ? bar_go + 24 : bar_qkv, 0);
                uint4 v[10];
                if (mt > 0) {
                    const uint32_t tq = clk32();
                    while ((int)(clk32() - tq) < TP(HALO_WAIT)) { }
                    #pragma unroll 1
                    for (;;) {
                        uint32_t bad = 0;
                        #pragma unroll
                        for (int j = 0; j < 10; j++) v[j] = ld_b128_relaxed(hp + j * 32);
                        #pragma unroll
                        for (int j = 0; j < 10; j++) bad |= v[j].w ^ epoch;
                        if (__all_sync(0xffffffffu, bad == 0) || (ABL & 1)) break;
                        __nanosleep(200);
                    }
                } else {
                    const uint32_t r0 = stg + KV_OFF + 8 * KV_PITCH + 112 + (lane & 3) * 4;
                    v[0].x = v[0].y = v[0].z = v[1].x = v[1].y = v[1].z = v[2].x = 0;
                    v[2].y = lds32(r0); v[2].z = lds32(r0 + 16); v[3].x = lds32(r0 + 32); v[3].y = lds32(r0 + 48); v[3].z = lds32(r0 + 64); v[4].x = lds32(r0 + 80); v[4].y = lds32(r0 + 96);
                    #pragma unroll
                    for (int j = 0; j < 5; j++) v[5 + j] = v[j];
                }
                mbar_wait(bar_free, 0);
                #pragma unroll
                for (int p = 0; p < 2; p++) {
                    const uint4* u = v + 5 * p;
                    stsm_x4(ha + p * KV_PAR, u[0].x, u[0].y, u[0].z, u[1].x);
                    stsm_x4(ha + p * KV_PAR + 64, u[1].y, u[1].z, u[2].x, u[2].y);
                    stsm_x4(ha + p * KV_PAR + 128, u[2].z, u[3].x, u[3].y, u[3].z);
                    stsm_x2(ha + p * KV_PAR + 192, u[4].x, u[4].y);
                }
                __syncwarp();
                if (lane == 0) { mbar_arrive(bar_halo); TR(10); TRG(100); }
            } else {
                #pragma unroll 1
                for (int j = 2; j < (late ? 4 : 5); j++) {
                    const unsigned* const fl = j == 2 ? fl2 : j == 4 ? &g_flag_o[mt * 32] : lane < 24 ? fl3 : &g_flag_ab[(16 + 8 * r + (lane & 7)) * 32 + mt];
                    const uint32_t at = ta + (j == 2 ? TP(POLL_AT2) : j == 3 ? TP(POLL_AT3) : TP(OPOLL_AT));
                    if (!rest) { while ((int)(clk32() - at) < 0) { } }
                    forward(fl, j == 4 ? epoch * 8 : epoch, Int<0>(), bar_fl + 8 * j, at);
                    if (lane == 0) TR(j == 3 ? 39 : j == 4 ? 13 : 35 + j);
                }
                mbar_wait_limit(bar_end, 0);
            }
            __syncwarp();
        }
      }
      TR_END();
    } else {
        if (tid == 128) {
            mbar_init(bar_ab6, 1); mbar_init(bar_ab, 4); mbar_init(bar_ab + 8, 6); mbar_init(bar_free, 1); mbar_init(bar_free + 8, 1); mbar_init(bar_qkv, 4); mbar_init(bar_qkv + 8, 4); mbar_init(bar_o, 8);
            mbar_init(bar_halo, 1); mbar_init(bar_end, 3);
            #pragma unroll
            for (int j = 0; j < 7; j++) mbar_init(bar_go + 8 * j, 1);
            mbar_init(bar_sf, 1); mbar_init(bar_se, 2); mbar_init(bar_af, 4);
            asm volatile("fence.mbarrier_init.release.cluster;" ::: "memory");
        }
        __syncwarp();
        cluster_arrive();
        if (warp >= 8) {
            float d[4];
            #pragma unroll 1
            for (int i = 0; i < TP(WARM_N); i++) {
                const uint32_t t1 = clk32();
                wgmma_fence();
                wgmma_n8<1, 0>(d, desc_k(sb + 7 * AB_BYTES), desc_k(sb + 7 * AB_BYTES), 0);
                wgmma_commit();
                wgmma_wait<0>();
                while ((int)(clk32() - t1) < TP(WARM_GAP)) { }
                __syncwarp();
            }
        }
        cluster_wait();
        const int wg = warp >> 3, w = warp & 3, cw = warp - 4;

        const bool sig_local = (tid & 127) == 0;
        const int i8 = lane & 7, m = lane >> 3;
        const bool sig = (tid & 95) == 0;
        uint32_t rel;
        asm("mapa.shared::cluster.u32 %0, %1, %2;" : "=r"(rel) : "r"(bar_empty), "r"(r ^ (w & 1)));
        auto done = [&](int it) { (void)it; if ((tid & 127) == 64) TRL(160 + it); };
        auto release = [&](int s) { if (sig) asm volatile("mbarrier.arrive.shared::cluster.b64 _, [%0];" :: "r"(rel + 8 * s) : "memory"); };
        const uint32_t dA = desc_k(sb + wg * 8192), dB = desc_k(sb + SLOT_A), dBt = desc_mn(sb + SLOT_A);
        const uint32_t a_frag = sb + wg * 8192 + (w * 16 + (lane & 15)) * 128 + (((lane >> 4) ^ i8) << 4);
        auto wait_full = [&](int it) { mbar_wait(bar_full + 8 * (it & 3), (it >> 2) & 1); if (sig_local) TR(128 + wg * 64 + it); };
        uint32_t kq[4][4], vq[14], qb[2][8];
        {
            float aq[28], ak[28], av[28];
            const uint32_t mh0 = pin((lane & 3) < 2 ? 0xffffffffu : 0u);
            uint32_t af[2][4][4];
            auto load_af = [&](int it) {
                wait_full(it);
                #pragma unroll
                for (int k = 0; k < 4; k++) ldsm_x4((a_frag ^ (k << 5)) + (it & 3) * SLOT_BYTES, af[it & 1][k][0], af[it & 1][k][1], af[it & 1][k][2], af[it & 1][k][3]);
            };
            uint32_t abw[28], base;
            auto stage_ab = [&](int j0, int j1) {
                #pragma unroll
                for (int j = j0; j < j1; j++) {
                    if (j < 7) stsm_x4_t(base + j * 2048, abw[4 * j], abw[4 * j + 1], abw[4 * j + 2], abw[4 * j + 3]);
                    else { __syncwarp(); if (lane == 0) mbar_arrive(bar_ab + 8 * wg); }
                }
            };
            {
                float bacc[56];
                base = pin((wg ? stg : sb + 7 * AB_BYTES) + (((2 * w + (m & 1)) ^ i8) << 4) + ((m >> 1) * 8 + i8) * 128);
                auto ab_loop = [&](auto sign) {
                auto ab_issue = [&](int kb) {
                    mbar_wait_p(bar_abf + 8 * kb, 0);
                    if (kb == 0 && wg == 1) asm volatile("bar.sync 3, 256;" ::: "memory");
                    if (sig_local) TR(112 + wg * 8 + kb);
                    wgmma_fence();
                    #pragma unroll
                    for (int k = 0; k < 4; k++) wgmma_n112<decltype(sign)::value, 0>(bacc, dA + kb * (AB_BYTES >> 4) + 2 * k, dB + kb * (AB_BYTES >> 4) + 2 * k, (kb | k) != 0);
                    wgmma_commit();
                    if (kb == 0 && wg == 0) asm volatile("bar.arrive 3, 256;" ::: "memory");
                };
                #pragma unroll
                for (int kb = 0; kb < 5; kb++) {
                    ab_issue(kb);
                    if (kb > 0) wgmma_wait<1>();
                    if (kb == 2 || kb == 3) release(kb - 2);
                }
                if (wg == 0) {
                    ab_issue(5);
                    ab_issue(6);
                    asm volatile("bar.arrive 4, 256;" ::: "memory");
                    wgmma_wait<2>();
                    release(2);
                } else {
                    uint32_t xf[8][4];
                    #pragma unroll
                    for (int j = 0; j < 8; j++) {
                        if ((j & 3) == 0) mbar_wait(bar_abf + 8 * (5 + (j >> 2)), 0);
                        ldsm_x4((a_frag ^ ((j & 3) << 5)) + (5 + (j >> 2)) * AB_BYTES, xf[j][0], xf[j][1], xf[j][2], xf[j][3]);
                    }
                    wgmma_wait<0>();
                    release(2);
                    asm volatile("bar.sync 4, 256;" ::: "memory");
                    wgmma_fence();
                    #pragma unroll
                    for (int j = 0; j < 8; j++) {
                        wgmma_rs_n112<0, decltype(sign)::value>(bacc, xf[j], dB + (5 + (j >> 2)) * (AB_BYTES >> 4) + 2 * (j & 3), 1);
                        if ((j & 3) == 3) wgmma_commit();
                    }
                }
                };
                if (sub >> 2) ab_loop(Int<-1>()); else ab_loop(Int<1>());
                wgmma_wait<1>();
                release(3);
                reg_set<REG_CONS>();
                if (wg == 1) load_af(0);
                wgmma_wait<0>();
                if (sig_local) TRX(21 + wg);
                if (AB_ST) { if (wg == 0) asm volatile("bar.arrive 3, 256;" ::: "memory"); else asm volatile("bar.sync 3, 256;" ::: "memory"); }
                #pragma unroll
                for (int j = 0; j < 28; j++) abw[j] = pack_bf16(bacc[2 * j], bacc[2 * j + 1]);
                stage_ab(0, AB_ST);
                if (wg == 0 || AB_ST == 7) stage_ab(AB_ST, 8);
            }
            const uint32_t dQ = dBt + (sub & 1);
            #pragma unroll
            for (int it = 0; it < 7; it++) {
                const uint32_t o = (it & 3) * (SLOT_BYTES >> 4);
                if (it > 0 || wg == 0) load_af(it);
                if (AB_ST < 7 && wg == 1) { if (it == 1) stage_ab(AB_ST, AB_ST2); if (it == 2) stage_ab(AB_ST2, 8); }
                wgmma_wait<0>();
                if (it > 0) { release((it - 1) & 3); done(it - 1); }
                if (it == 0 && sig_local) TRL(60 + wg);
                if (wg == 0) { if (it > 0) asm volatile("bar.sync 6, 256;" ::: "memory"); } else asm volatile("bar.sync 8, 256;" ::: "memory");
                wgmma_fence();
                #pragma unroll
                for (int j = 0; j < 12; j++) {
                    const int k = it < 6 || !KV_FIRST ? j / 3 : j < 8 ? j >> 1 : j - 8, x = it < 6 || !KV_FIRST ? j % 3 : j < 8 ? j & 1 : 2;
                    const uint32_t d = dQ + o + (k >> 1) * 768 + (k & 1) * 128;
                    if (j == Q_ARR) { if (wg == 0) asm volatile("bar.arrive 8, 256;" ::: "memory"); else asm volatile("bar.arrive 6, 256;" ::: "memory"); }
                    if (x == 0) wgmma_rs_n56<1>(ak, af[it & 1][k], d + 256, (it | k) != 0);
                    if (x == 1) wgmma_rs_n56<1>(av, af[it & 1][k], d + 512, (it | k) != 0);
                    if (x == 2) wgmma_rs_n56<1>(aq, af[it & 1][k], d, (it | k) != 0);
                    if (KV_FIRST && it == 6 && j == 7) wgmma_commit();
                }
                wgmma_commit();
            }
            uint4* const hp = pin(g_halo + (mt * 8 + sub) * 320 + wg * 160 + lane);
            mbar_wait(bar_ab + 8, 0);
            const uint32_t epoch = lds32(bars + 168);
            wgmma_wait<KV_FIRST>();
            #pragma unroll
            for (int j = 0; j < 16; j++) kq[j >> 2][j & 3] = pin(pack_bf16(ak[2 * (j - 2 * (j > 7))], ak[1 + 2 * (j - 2 * (j > 7))]));
            #pragma unroll
            for (int j = 0; j < 14; j++) vq[j] = pin(pack_bf16(av[2 * j], av[2 * j + 1]));
            if (w == 3 && !(ABL & 1)) {
                st_b128_relaxed(hp, kq[0][1], kq[0][3], kq[1][1], epoch);
                st_b128_relaxed(hp + 32, kq[1][3], kq[2][3], kq[3][1], epoch);
                st_b128_relaxed(hp + 64, kq[3][3], vq[1], vq[3], epoch);
                st_b128_relaxed(hp + 96, vq[5], vq[7], vq[9], epoch);
                st_b128_relaxed(hp + 128, vq[11], vq[13], 0u, epoch);
                if (lane == 0) TR(8);
            }
            wgmma_wait<0>();
            release(6 & 3);
            if (sig_local) TRX(23 + wg);
            #pragma unroll
            for (int j = 0; j < 14; j++) qb[j & 1][(j >> 1) + (j > 7)] = pin(pack_bf16(aq[2 * j], aq[2 * j + 1]));
            #pragma unroll
            for (int j = 0; j < 2; j++) { qb[j][4] = qb[j][3] & ~mh0; qb[j][3] &= mh0; }
        }
        float acc[112];
        const int it1 = 7 + nj;
        auto big_issue = [&](int slot, bool first) {
            wgmma_fence();
            #pragma unroll
            for (int k = 0; k < 4; k++) wgmma_n224<1, 0>(acc, dA + slot * (SLOT_BYTES >> 4) + 2 * k, dB + slot * (SLOT_BYTES >> 4) + 2 * k, !first || k != 0);
            wgmma_commit();
        };
        if (wg == 1) {
            asm volatile("bar.sync 7, 256;" ::: "memory");
            big_issue(3, true);
        } else {
            wait_full(7);
            asm volatile("bar.sync 6, 256;" ::: "memory");
            big_issue(3, true);
            asm volatile("bar.arrive 7, 256;" ::: "memory");
            if (sig_local) TR(20);
        }
        {
            auto plain = [&](int it) {
                wait_full(it); wgmma_wait<0>(); release((it - 1) & 3); done(it - 1); big_issue(it & 3, false);
                mbar_wait(bar_free, 0);
            };
            auto before_mma = [&](int it, int last) {
                if (wg == last) {
                    mbar_wait_limit(bar_full + 8 * (it & 3), (it >> 2) & 1);
                    if (sig_local) TR(128 + last * 64 + it);
                    asm volatile("bar.sync 2, 256;" ::: "memory");
                    wgmma_wait<0>();
                    release((it - 1) & 3);
                    done(it - 1);
                } else {
                    if (GAP_FLIP) { wgmma_wait<0>(); release((it - 1) & 3); }
                    asm volatile("bar.arrive 2, 256;" ::: "memory");
                }
            };
            auto after_mma = [&](int it, int last) {
                if (wg == (last ^ 1)) {
                    if (!GAP_FLIP) { wgmma_wait<0>(); release((it - 1) & 3); }
                    asm volatile("bar.sync 7, 256;" ::: "memory");
                    big_issue(it & 3, false);
                } else {
                    big_issue(it & 3, false);
                    asm volatile("bar.arrive 7, 256;" ::: "memory");
                }
            };
            const uint32_t kvw = stg + KV_OFF + wg * KV_PAR + (w * 16 + i8) * KV_PITCH;
            const uint32_t a_k = kvw + (m & 1) * 8 * KV_PITCH + (m >> 1) * 16, a_v = kvw + (m >> 1) * 8 * KV_PITCH + 112 + (m & 1) * 16;
            mbar_wait(bar_free, 0);
            #pragma unroll
            for (int u = 0; u < 3; u++) stsm_x4(a_k + 8 * KV_PITCH + 112 + u * 32, vq[4 * u], vq[4 * u + 1], vq[4 * u + 2], vq[4 * u + 3]);
            stsm_x2(a_k + 8 * KV_PITCH + 112 + 96, vq[12], vq[13]);
            plain(8);
            #pragma unroll
            for (int u = 0; u < 4; u++) stsm_x4(a_k + 8 * KV_PITCH + (2 * u - (u > 1)) * 16, kq[u][0], kq[u][1], kq[u][2], kq[u][3]);
            __syncwarp();
            if (lane == 0) mbar_arrive(bar_qkv + 8 * wg);
            if (sig_local) TR(25 + wg);
            uint32_t kp[4][4], vt[8][4], pb[4][2];
            auto load_v = [&](int n) {
                #pragma unroll
                for (int u = 0; u < 4; u++) ldsm_x4_t(a_v + n * 8 * KV_PITCH + (2 * u - (u > 1)) * 16, vt[2 * u + n][0], vt[2 * u + n][1], vt[2 * u + n][2], vt[2 * u + n][3]);
            };
            load_v(1);
            plain(9);
            if (QK_AT > 10) plain(10);
            mbar_wait(w == 0 && !(ABL & 2) ? bar_halo : bar_qkv + 8 * wg, 0);
            #pragma unroll
            for (int u = 0; u < 4; u++) ldsm_x4(a_k + (2 * u - (u > 1)) * 16, kp[u][0], kp[u][1], kp[u][2], kp[u][3]);
            if (sig_local) TR(54 + wg);
            before_mma(QK_AT, GAP_FLIP);
            float s[4][4];
            #pragma unroll
            for (int i = 0; i < 16; i++) s[i >> 2][i & 3] = 0.f;
            #pragma unroll
            for (int i = 0; i < (ABL & 4 ? 0 : 8); i++) {
                const int n = i & 1, h = (i >> 1) & 1, ks = 2 * h + (i >> 2);
                if (n) mma16816(s[i & 3], kq[ks][0], kq[ks][1], kq[ks][2], kq[ks][3], qb[1][2 * ks], qb[1][2 * ks + 1]);
                else mma16816(s[i & 3], kp[ks][0], kp[ks][1], kp[ks][2], kp[ks][3], qb[0][2 * ks], qb[0][2 * ks + 1]);
            }
            #pragma unroll
            for (int i = 0; i < 16; i++) asm volatile("" : "+f"(s[i >> 2][i & 3]) :: "memory");
            after_mma(QK_AT, GAP_FLIP);
            if (sig_local) TR(48 + wg);
            const int g = lane >> 2, t2 = 2 * (lane & 3);
            const uint32_t mlo = (t2 > g ? 0xffffu : 0u) | (t2 + 1 > g ? 0xffff0000u : 0u), before = (mt | w) == 0 ? mlo : 0u;
            uint32_t y[4], mx[2];
            #pragma unroll
            for (int i = 0; i < 4; i++) {
                const uint32_t x = pack_bf16(g > t2 ? s[i][0] : s[i][2], g > t2 + 1 ? s[i][1] : s[i][3]);
                y[i] = movm_t(pack_bf16(bf_lo(x) * ATT_SCALE, bf_hi(x) * ATT_SCALE));
                if (!(i & 1)) y[i] = (y[i] & ~before) | (MASKED & before);
            }
            #pragma unroll
            for (int h = 0; h < 2; h++) {
                mx[h] = max_bf16x2(__byte_perm(y[2 * h], y[2 * h + 1], 0x5410), __byte_perm(y[2 * h], y[2 * h + 1], 0x7632));
                mx[h] = pin(max_bf16x2(mx[h], __shfl_xor_sync(0xffffffffu, mx[h], 1)));
            }
            load_v(0);
            if (sig_local) TR(50 + wg);
            plain(QK_AT + 1);
            #pragma unroll
            for (int h = 0; h < 2; h++) mx[h] = max_bf16x2(mx[h], __shfl_xor_sync(0xffffffffu, mx[h], 2));
            #pragma unroll
            for (int i = 0; i < 4; i++) {
                const float mi = i & 1 ? bf_hi(mx[i >> 1]) : bf_lo(mx[i >> 1]);
                const float e0 = ex2_approx((bf_lo(y[i]) - mi) * LOG2E), e1 = ex2_approx((bf_hi(y[i]) - mi) * LOG2E);
                float sum = e0 + e1;
                sum += __shfl_xor_sync(0xffffffffu, sum, 1);
                sum += __shfl_xor_sync(0xffffffffu, sum, 2);
                const float inv = rcp_approx(sum);
                const uint32_t p = pack_bf16(e0 * inv, e1 * inv);
                pb[i][0] = pin(p & mlo); pb[i][1] = pin(p & ~mlo);
            }
            if (sig_local) TR(52 + wg);
            before_mma(QK_AT + 2, 0);
            float ao[8][4];
            #pragma unroll
            for (int i = 0; i < 8; i++) {
                ao[i][0] = ao[i][1] = ao[i][2] = ao[i][3] = 0.f;
                if (!(ABL & 4)) mma16816(ao[i], vt[i][0], vt[i][1], vt[i][2], vt[i][3], pb[(i >> 2) * 2 + (i & 1)][0], pb[(i >> 2) * 2 + (i & 1)][1]);
            }
            #pragma unroll
            for (int i = 0; i < 32; i++) asm volatile("" : "+f"(ao[i >> 2][i & 3]) :: "memory");
            after_mma(QK_AT + 2, 0);
            if (sig_local) TRX(11 + wg);
            if (g >= 4) { ao[2][2] = ao[4][0]; ao[2][3] = ao[4][1]; ao[3][2] = ao[5][0]; ao[3][3] = ao[5][1]; }
            mbar_wait(bar_free + 8, 0);
            const uint32_t orow = stg + wg * 7168 + (m >> 1) * 1024 + (w * 16 + (lane & 15)) * 16;
            stsm_x4_t(orow, pack_bf16(ao[0][0], ao[0][1]), pack_bf16(ao[1][0], ao[1][1]), pack_bf16(ao[0][2], ao[0][3]), pack_bf16(ao[1][2], ao[1][3]));
            stsm_x4_t(orow + 2048, pack_bf16(ao[2][0], ao[2][1]), pack_bf16(ao[3][0], ao[3][1]), pack_bf16(ao[2][2], ao[2][3]), pack_bf16(ao[3][2], ao[3][3]));
            stsm_x4_t(orow + 4096, pack_bf16(ao[4][2], ao[4][3]), pack_bf16(ao[5][2], ao[5][3]), pack_bf16(ao[6][0], ao[6][1]), pack_bf16(ao[7][0], ao[7][1]));
            stsm_x2_t(orow + 6144, pack_bf16(ao[6][2], ao[6][3]), pack_bf16(ao[7][2], ao[7][3]));
            __syncwarp();
            if (lane == 0) mbar_arrive(bar_o);
        }
        uint32_t af[12][4];
        #pragma unroll 1
        for (int it = QK_AT + 3; it < it1 - 3; it++) {
            wait_full(it);
            wgmma_wait<0>();
            if (it != 7 + 32 - KB_EARLY - 4) release((it - 1) & 3);
            done(it - 1);
            big_issue(it & 3, false);
            if (L_PRE && it == 7 + 32 - KB_EARLY - 5) {
                mbar_wait(bar_sf, 0);
                #pragma unroll
                for (int k = 0; k < 4; k++) ldsm_x4((a_frag ^ (k << 5)) + NSLOT * SLOT_BYTES, af[k][0], af[k][1], af[k][2], af[k][3]);
            }
        }
        mbar_wait(bar_fl + 24, 0);
        if (tid == 128) atomicAdd(&g_epoch[cta * 8], 1);
        __nv_bfloat16* const yp = pin(out + (size_t)(mt * 128 + cw * 16 + (lane >> 2)) * NOUT + DM + nh * 256 + (lane & 3) * 8);
        const int y6 = 192 - nh * 224;
        #define Y_WORD(A, i, jj) pack_bf16(A[16 * ((i) >> 1) + 4 * (jj) + 2 * ((i) & 1)], A[16 * ((i) >> 1) + 4 * (jj) + 2 * ((i) & 1) + 1])
        #define Y_ADDR(i) (yp + ((i) & 1) * 8 * NOUT + ((i) < 12 ? ((i) >> 1) * 32 : y6))
        const bool odd = lane & 4;
        __nv_bfloat16* const yq = pin(odd ? yp - NOUT + 32 : yp);
        #define Y_PAIR(A, i, B, j, rh, C, PAUSE) do { \
            uint32_t x_[4], y_[4]; \
            _Pragma("unroll") \
            for (int jj = 0; jj < 4; jj++) { \
                const uint32_t u_ = Y_WORD(A, 2 * (i) + (rh), jj), v_ = Y_WORD(B, 2 * (j) + (rh), jj), o_ = __shfl_xor_sync(0xffffffffu, odd ? u_ : v_, 4); \
                x_[jj] = odd ? o_ : u_; y_[jj] = odd ? v_ : o_; \
            } \
            red_add_bf16x8(yq + (rh) * 8 * NOUT + (C), x_[0], x_[1], x_[2], x_[3]); \
            PAUSE; \
            red_add_bf16x8(yq + ((rh) * 8 + 1) * NOUT + (C), y_[0], y_[1], y_[2], y_[3]); \
        } while (0)
        if (late) {
            constexpr int IT = 7 + 32 - KB_EARLY - 3;
            #define L_SLOT(j) ((j) == 0 ? NSLOT : (IT + (j) - 1) & 3)
            auto load_af = [&](int j) {
                if (j == 0) mbar_wait(bar_sf, 0); else wait_full(IT + j - 1);
                #pragma unroll
                for (int k = 0; k < 4; k++) ldsm_x4((a_frag ^ (k << 5)) + L_SLOT(j) * SLOT_BYTES, af[4 * j + k][0], af[4 * j + k][1], af[4 * j + k][2], af[4 * j + k][3]);
            };
            if (!L_PRE) load_af(0);
            load_af(1);
            if (L_UP) load_af(2);
            wgmma_wait<0>();
            done(IT - 1);
            if (!L_UP && wg == 1) load_af(2);
            auto issue = [&](auto& p, auto c0, int j0, int j1, bool first, bool last) {
                constexpr int W = sizeof(p) / 2, C0 = decltype(c0)::value;
                if (wg == 0) { if (!first) asm volatile("bar.sync 9, 256;" ::: "memory"); } else asm volatile("bar.sync 5, 256;" ::: "memory");
                wgmma_fence();
                #pragma unroll
                for (int j = j0; j < j1; j++) {
                    if (!L_UP && first && j == 8) { if (wg == 0) load_af(2); wgmma_fence(); }
                    if (j == j1 - 12 + L_ARR) { if (wg == 0) asm volatile("bar.arrive 5, 256;" ::: "memory"); else if (!last) asm volatile("bar.arrive 9, 256;" ::: "memory"); }
                    const uint32_t d = dB + L_SLOT(j >> 2) * (SLOT_BYTES >> 4) + C0 * 8 + 2 * (j & 3);
                    if constexpr (W == 64) wgmma_rs_n64<0>(p, af[j], d, 1); else wgmma_rs_n32<0>(p, af[j], d, 1);
                }
                wgmma_commit();
            };
            float p0[32], p1[32], p2[32], p3[16];
            #pragma unroll
            for (int i = 0; i < 16; i++) asm volatile("mov.b32 %0, %1;" : "=f"(p3[i]) : "f"(acc[96 + i]));
            #pragma unroll
            for (int i = 0; i < 32; i++) asm volatile("mov.b32 %0, %1;" : "=f"(p2[i]) : "f"(acc[64 + i]));
            #pragma unroll
            for (int i = 0; i < 32; i++) asm volatile("mov.b32 %0, %1;" : "=f"(p1[i]) : "f"(acc[32 + i]));
            #pragma unroll
            for (int i = 0; i < 32; i++) asm volatile("mov.b32 %0, %1;" : "=f"(p0[i]) : "f"(acc[i]));
            issue(p0, Int<0>(), 0, 12, true, false);
            wgmma_wait<0>();
            if (sig_local) TRL(14 + wg);
            Y_PAIR(p0, 0, p0, 1, 0, 0, ); Y_PAIR(p0, 0, p0, 1, 1, 0, );
            issue(p1, Int<64>(), 0, 12, false, false);
            wgmma_wait<0>();
            Y_PAIR(p1, 0, p1, 1, 0, 64, ); Y_PAIR(p1, 0, p1, 1, 1, 64, );
            issue(p2, Int<128>(), 0, 12, false, false);
            wgmma_wait<0>();
            Y_PAIR(p2, 0, p2, 1, 0, 128, );
            Y_PAIR(p2, 0, p2, 1, 1, 128, );
            issue(p3, Int<192>(), 0, 12, false, true);
            if (sig_local) mbar_arrive(bar_end);
            wgmma_wait<0>();
            if (sig_local) TRX(27 + wg);
            #pragma unroll
            for (int i = 0; i < 2; i++) red_add_bf16x8(Y_ADDR(12 + i), Y_WORD(p3, i, 0), Y_WORD(p3, i, 1), Y_WORD(p3, i, 2), Y_WORD(p3, i, 3));
            if (sig_local) TR(29 + wg);
        } else {
        constexpr int IT0 = 7 + KB_EARLY;
        auto load_af = [&](int j) {
            wait_full(IT0 - 3 + j);
            #pragma unroll
            for (int k = 0; k < 4; k++) ldsm_x4((a_frag ^ (k << 5)) + ((IT0 - 3 + j) & 3) * SLOT_BYTES, af[4 * j + k][0], af[4 * j + k][1], af[4 * j + k][2], af[4 * j + k][3]);
        };
        wait_full(IT0 - 3);
        wgmma_wait<0>();
        release((IT0 - 4) & 3);
        done(IT0 - 4);
        if (wg == 1) {
            load_af(0); load_af(1); load_af(2);
            asm volatile("bar.sync 5, 256;" ::: "memory");
            release((bar_af - bar_empty) / 8);
            #pragma unroll
            for (int it = IT0 - 3; it < IT0; it++) {
                if (it == IT0 - 1) { wgmma_wait<1>(); release((it - 2) & 3); }
                wgmma_fence();
                #pragma unroll
                for (int k = 0; k < 4; k++) wgmma_rs_n224<0>(acc, af[4 * (it - IT0 + 3) + k], dB + (it & 3) * (SLOT_BYTES >> 4) + 2 * k, 1);
                wgmma_commit();
            }
            asm volatile("bar.arrive 9, 256;" ::: "memory");
            wgmma_wait<1>();
            release((IT0 - 2) & 3);
            wgmma_wait<0>();
            release((IT0 - 1) & 3);
            if (sig_local) { mbar_arrive(bar_end); TRL(28); }
            const uint32_t t1 = clk32() + TP(RED_AT1);
            auto pause = [&](int i) { while ((int)(clk32() - t1) < i * TP(RED_GAP1)) { } };
            #pragma unroll
            for (int i = 0; i < 2; i++) { pause(i); red_add_bf16x8(Y_ADDR(12 + i), Y_WORD(acc, 12 + i, 0), Y_WORD(acc, 12 + i, 1), Y_WORD(acc, 12 + i, 2), Y_WORD(acc, 12 + i, 3)); }
            #pragma unroll
            for (int i = 0; i < 6; i++) { pause(2 + 2 * i); Y_PAIR(acc, i & 6, acc, (i & 6) + 1, i & 1, 32 * (i & 6), pause(3 + 2 * i)); }
            if (sig_local) TR(30);
        } else {
            float lo[64], hi[48];
            #pragma unroll
            for (int i = 0; i < 48; i++) asm volatile("mov.b32 %0, %1;" : "=f"(hi[i]) : "f"(acc[64 + i]));
            #pragma unroll
            for (int i = 0; i < 64; i++) asm volatile("mov.b32 %0, %1;" : "=f"(lo[i]) : "f"(acc[i]));
            #pragma unroll
            for (int it = IT0 - 3; it < IT0; it++) {
                if (it == IT0 - 1) {
                    #pragma unroll
                    for (int k = 0; k < E_FILL; k++) wgmma_n96<1, 0>(hi, dA + ((IT0 - 3 + (k >> 2)) & 3) * (SLOT_BYTES >> 4) + 2 * (k & 3), dB + ((IT0 - 3 + (k >> 2)) & 3) * (SLOT_BYTES >> 4) + 1024 + 2 * (k & 3), 1);
                }
                if (it > IT0 - 3) wait_full(it);
                wgmma_fence();
                #pragma unroll
                for (int k = 0; k < 4; k++) wgmma_n128<1, 0>(lo, dA + (it & 3) * (SLOT_BYTES >> 4) + 2 * k, dB + (it & 3) * (SLOT_BYTES >> 4) + 2 * k, 1);
            }
            wgmma_commit();
            #define E_RED(i) do { if ((i) < 8) red_add_bf16x8(Y_ADDR(i), Y_WORD(lo, (i) & 7, 0), Y_WORD(lo, (i) & 7, 1), Y_WORD(lo, (i) & 7, 2), Y_WORD(lo, (i) & 7, 3)); \
                                  else red_add_bf16x8(Y_ADDR(i), Y_WORD(hi, (i) & 7, 0), Y_WORD(hi, (i) & 7, 1), Y_WORD(hi, (i) & 7, 2), Y_WORD(hi, (i) & 7, 3)); } while (0)
            #pragma unroll
            for (int j = E_FILL; j < 12; j++) {
                const int it = IT0 - 3 + (j >> 2), k = j & 3;
                if (j == E_FILL + E_SPLIT) {
                    wgmma_commit();
                    wgmma_wait<1>();
                    if (sig_local) TR(14);
                    #pragma unroll
                    for (int i = 0; i < RED_A; i++) E_RED(i);
                    wgmma_fence();
                }
                wgmma_n96<1, 0>(hi, dA + (it & 3) * (SLOT_BYTES >> 4) + 2 * k, dB + (it & 3) * (SLOT_BYTES >> 4) + 1024 + 2 * k, 1);
            }
            wgmma_commit();
            asm volatile("bar.arrive 5, 256;" ::: "memory");
            #pragma unroll
            for (int i = RED_A; i < RED_FAST; i++) E_RED(i);
            wgmma_wait<0>();
            release((bar_af - bar_empty) / 8); release((IT0 - 3) & 3); release((IT0 - 2) & 3); release((IT0 - 1) & 3);
            if (sig_local) TRL(27);
            const uint32_t t1 = clk32();
            #pragma unroll
            for (int i = RED_FAST; i < 14; i++) {
                while ((int)(clk32() - t1) < (i - RED_FAST) * TP(RED_GAP)) { }
                E_RED(i);
            }
            #undef E_RED
            if (sig_local) TR(29);
            float o0[56], o1[56];
            auto out_issue = [&](float (&oa)[56], int p, int j) {
                wgmma_fence();
                #pragma unroll
                for (int k = 0; k < 4; k++) wgmma_n112<1, 1, 8>(oa, dB + (63 << 16) + ((OUT_O(p, j) - SLOT_A) >> 4) + 128 * k, dB + ((((OUT_B(j) - OUT_A(j)) >> 4) - 1) << 16) + ((OUT_A(j) - SLOT_A) >> 4) + 128 * k, (j | k) != 0);
                wgmma_commit();
            };
            const uint32_t wa = pin(sb + w * 2048 + ((m & 1) * 8 + i8) * 128 + (((m >> 1) ^ i8) << 4)), ra = pin(sb + w * 2048 + m * 128 + ((i8 ^ m) << 4));
            auto stage = [&](float (&oa)[56], int buf, int u) {
                stsm_x4((wa ^ ((u & 3) << 5)) + buf + (u >> 2) * 8192, pack_bf16(oa[8 * u], oa[8 * u + 1]), pack_bf16(oa[8 * u + 2], oa[8 * u + 3]),
                        pack_bf16(oa[8 * u + 4], oa[8 * u + 5]), pack_bf16(oa[8 * u + 6], oa[8 * u + 7]));
            };
            __nv_bfloat16* const op = pin(out + (size_t)(mt * 128 + 1 + w * 32 + 2 * m) * NOUT + (sub & 3) * 64 + i8 * 8);
            const int c1 = 256 - (sub & 3) * 16;
            asm volatile("bar.sync 9, 256;" ::: "memory");
            #pragma unroll
            for (int j = 0; j < 7; j++) {
                if (j == 0 || j == 2 || j == 4) { mbar_wait(bar_abf + 4 * j, 1); if (sig_local) TR(128 + IT0 + j); }
                out_issue(o0, 0, j);
                if (j == 2) { wgmma_wait<2>(); if (sig_local) mbar_arrive(bar_ab6); }
            }
            #pragma unroll
            for (int j = 0; j < 7; j++) {
                if (j % 3 == 0) { mbar_wait(bar_abf + 24 + 8 * (j / 3), 1); if (sig_local) TR(192 + IT0 + j); }
                out_issue(o1, 1, j);
                if (j == 1) { wgmma_wait<2>(); if (sig_local) TR(31); }
                if (j >= 1 && j < 5) {
                    stage(o0, OUT_O(0, 1), 2 * j - 2);
                    if (j < 4) stage(o0, OUT_O(0, 1), 2 * j - 1);
                    if (j == 2 || j == 4) { __syncwarp(); if (lane == 0) mbar_arrive(bar_qkv + 4 * j - 8); }
                }
            }
            if (sig_local) mbar_arrive(bar_end);
            wgmma_wait<0>();
            if (sig_local) TRL(32);
            #pragma unroll
            for (int c = 0; c < 2; c++) {
                #pragma unroll
                for (int u = 4 * c; u < (c ? 7 : 4); u++) stage(o1, 0, u);
                __syncwarp();
                #pragma unroll
                for (int q = 0; q < 4; q++) {
                    uint4 v;
                    asm volatile("ld.shared.v4.u32 {%0, %1, %2, %3}, [%4];" : "=r"(v.x), "=r"(v.y), "=r"(v.z), "=r"(v.w) : "r"((ra ^ ((q & 1) << 6)) + c * 8192 + q * 512) : "memory");
                    if (c == 0 || i8 < 6) *reinterpret_cast<uint4*>(op + q * 8 * NOUT + (c ? c1 : 0)) = v;
                }
            }
        }
        }
        #undef Y_PAIR
        #undef Y_WORD
        #undef Y_ADDR
        if (sig_local) { TRX(33 + wg); if (wg == (late ? 1 : 0)) TRG(104); }
        TR_END();
    }
}

typedef CUresult (*EncodeFn)(CUtensorMap*, CUtensorMapDataType, cuuint32_t, void*, const cuuint64_t*, const cuuint64_t*,
                             const cuuint32_t*, const cuuint32_t*, CUtensorMapInterleave, CUtensorMapSwizzle,
                             CUtensorMapL2promotion, CUtensorMapFloatOOBfill);

void make_map(EncodeFn fn, CUtensorMap* tm, const void* ptr, uint64_t inner, uint64_t outer, uint32_t box_inner, uint32_t box_outer,
              CUtensorMapSwizzle sw = CU_TENSOR_MAP_SWIZZLE_128B, uint64_t clip = 0) {
    cuuint64_t gd[2] = {clip ? clip : inner, outer};
    cuuint64_t gs[1] = {inner * 2};
    cuuint32_t bd[2] = {box_inner, box_outer};
    cuuint32_t es[2] = {1, 1};
    fn(tm, CU_TENSOR_MAP_DATA_TYPE_BFLOAT16, 2, const_cast<void*>(ptr), gd, gs, bd, es, CU_TENSOR_MAP_INTERLEAVE_NONE,
       sw, CU_TENSOR_MAP_L2_PROMOTION_L2_128B, CU_TENSOR_MAP_FLOAT_OOB_FILL_NONE);
}
void make_map3(EncodeFn fn, CUtensorMap* tm, const void* ptr, uint64_t n0, uint64_t n1, uint64_t s1, uint64_t n2, uint64_t s2, uint32_t b1, uint32_t b2) {
    cuuint64_t gd[3] = {n0, n1, n2};
    cuuint64_t gs[2] = {s1 * 2, s2 * 2};
    cuuint32_t bd[3] = {64, b1, b2};
    cuuint32_t es[3] = {1, 1, 1};
    fn(tm, CU_TENSOR_MAP_DATA_TYPE_BFLOAT16, 3, const_cast<void*>(ptr), gd, gs, bd, es, CU_TENSOR_MAP_INTERLEAVE_NONE,
       CU_TENSOR_MAP_SWIZZLE_128B, CU_TENSOR_MAP_L2_PROMOTION_L2_128B, CU_TENSOR_MAP_FLOAT_OOB_FILL_NONE);
}
void make_map_perm(EncodeFn fn, CUtensorMap* tm, void* ptr, uint32_t n) {
    cuuint64_t gd[5] = {SEQ, 2, 4, 4, 28};
    cuuint64_t gs[4] = {SEQ * 2, 8 * SEQ * 2, 2 * SEQ * 2, 32 * SEQ * 2};
    cuuint32_t bd[5] = {64, 2, 4, 4, n};
    cuuint32_t es[5] = {1, 1, 1, 1, 1};
    fn(tm, CU_TENSOR_MAP_DATA_TYPE_BFLOAT16, 5, ptr, gd, gs, bd, es, CU_TENSOR_MAP_INTERLEAVE_NONE,
       CU_TENSOR_MAP_SWIZZLE_128B, CU_TENSOR_MAP_L2_PROMOTION_L2_128B, CU_TENSOR_MAP_FLOAT_OOB_FILL_NONE);
}

}

extern "C" void kernel_launch(void* const* d_in, const int* in_sizes, int n_in, void* d_out, int out_size) {
    (void)in_sizes; (void)n_in; (void)out_size;
    static EncodeFn fn = nullptr;
    static void* p_abT = nullptr;
    if (!fn) {
        void* p = nullptr; cudaDriverEntryPointQueryResult qr;
        cudaGetDriverEntryPoint("cuTensorMapEncodeTiled", &p, cudaEnableDefault, &qr);
        fn = (EncodeFn)p;
        cudaGetSymbolAddress(&p_abT, g_abT);
        cudaFuncSetAttribute(fused_kernel, cudaFuncAttributeMaxDynamicSharedMemorySize, SMEM_BYTES);
    }
    TMaps tm;
    make_map3(fn, &tm.xA3, d_in[0], DM, SEQ / 2, 2 * DM, 2, DM, 64, 2);
    make_map3(fn, &tm.wqkv3, d_in[1], DM, DM, 3 * DM, 3, DM, 32, 3);
    make_map(fn, &tm.wo64, d_in[2], DM, DM, 64, 64);
    make_map3(fn, &tm.outA, d_out, 64, SEQ / 2, 2 * NOUT, 4, 64, 64, 1);
    make_map3(fn, &tm.outB, (const __nv_bfloat16*)d_out + 256, 48, SEQ / 2, 2 * NOUT, 4, 48, 64, 1);
    make_map(fn, &tm.xB, d_in[3], DM, SEQ, 64, 128);
    make_map(fn, &tm.wre, d_in[4], SEQ, SEQ, 64, 128);
    make_map(fn, &tm.wim, d_in[5], SEQ, SEQ, 64, 128);
    make_map(fn, &tm.wreH, d_in[4], SEQ, SEQ, 64, 64);
    make_map(fn, &tm.wimH, d_in[5], SEQ, SEQ, 64, 64);
    make_map(fn, &tm.wdre, d_in[6], DM, DM, 64, 112);
    make_map(fn, &tm.wdim, d_in[7], DM, DM, 64, 112);
    make_map_perm(fn, &tm.abP4, p_abT, 4);
    make_map_perm(fn, &tm.abP3, p_abT, 3);
    make_map(fn, &tm.abH, p_abT, SEQ, 896, 64, 16);
    make_map(fn, &tm.ab32, p_abT, SEQ, 896, 64, 32);
    make_map(fn, &tm.ab80, p_abT, SEQ, 896, 64, 80);
    fused_kernel<<<NCTA, 384, SMEM_BYTES, cudaStreamPerThread>>>((__nv_bfloat16*)d_out,
        tm);
}
```

```cpp
#include <cuda_runtime.h>
#include <cuda_bf16.h>
#include <cuda.h>
#include <stdint.h>

namespace {

constexpr int SEQ = 2048, DM = 448, NOUT = 896;
constexpr int NCTA = 128;
constexpr int SLOT_A = 16384, SLOT_B = 28672, SLOT_BYTES = SLOT_A + SLOT_B, NSLOT = 4;
constexpr int AB_BYTES = SLOT_A + 112 * 128;
constexpr int STG_OFF = NSLOT * SLOT_BYTES;
constexpr int STG_BYTES = 7 * 7168;
constexpr int KV_PITCH = 240;
constexpr int KV_OFF = 2 * 7168, KV_PAR = 72 * KV_PITCH;
#define OUT_A(j) (((j) < 2 ? 44 + 8 * (j) : (j) < 4 ? 116 + 8 * (j) : (j) == 5 ? 124 : 4 * (j) - 16) * 1024)
#define OUT_B(j) (((j) < 6 ? 176 + 8 * (j) : 60) * 1024)
#define OUT_O(p, j) (((p) ? ((j) < 3 ? 148 + 8 * (j) : (j) < 6 ? 8 * (j) - 8 : 68) : 68 + 8 * (j)) * 1024)
constexpr int BAR_OFF = STG_OFF + STG_BYTES;
constexpr int TR_OFF = BAR_OFF + 512;
constexpr int SMEM_BYTES = TR_OFF + 1024;
constexpr int SPIN_LIMIT = 1 << 24;
#define TUNE_LIST(X) \
    X(START_GAP1, 400, 50, 0, 900)   \
    X(START_GAP, 280, 30, 0, 500)   \
    X(PF0_N, 0, 1, 0, 3)   \
    X(PF0_AT, 1800, 200, 0, 3000)   \
    X(WARM_N, 3, 1, 0, 6)   \
    X(WARM_GAP, 150, 50, 50, 500)   \
    X(ZERO_GAP, 100, 50, 0, 300)   \
    X(ZERO_AT, 900, 200, 0, 2400)   \
    X(ABS_AT1, 500, 100, 0, 1000)   \
    X(ABS_AT, 1500, 150, 300, 3000)   \
    X(ABS_GAP, 60, 40, 0, 400)   \
    X(ABS_GAP2, 230, 40, 0, 400)   \
    X(ABS_GAP3, 100, 40, 0, 400)   \
    X(POLL_AT, 3100, 100, 2000, 4000)   \
    X(POLL_AT1, 3600, 150, 2000, 5000)   \
    X(POLL_AT2, 6300, 200, 4000, 8000)   \
    X(POLL_AT3, 9200, 200, 6000, 11000)   \
    X(OPOLL_AT, 15100, 200, 13000, 17500)   \
    X(OPOLL2, 500, 100, -1000, 1500)   \
    X(POLL_NS, 50, 100, 0, 800)   \
    X(OPOLL_NS, 100, 60, 0, 600)   \
    X(BIG_GAP, 250, 100, 0, 1000)   \
    X(W_GAP, 180, 100, 0, 900)   \
    X(HALO_WAIT, 350, 100, 0, 1500)   \
    X(O_GAP, 130, 60, 10, 600)   \
    X(PF_N, 0, 1, 0, 3)   \
    X(PF_E, 6, 1, 4, 13)   \
    X(PF_L, 14, 1, 4, 17)   \
    X(WO_AT, 7, 1, 5, 10)   \
    X(WB_AT, 10, 1, 10, 13)   \
    X(L_XAT, 13, 1, 10, 13)   \
    X(RED_GAP, 185, 30, 0, 300)   \
    X(RED_AT1, 0, 100, 0, 1000)   \
    X(RED_GAP1, 80, 30, 0, 300)   \

#define X(n, d, s, lo, hi) constexpr int n = d;
TUNE_LIST(X)
#undef X
#define TP(n) n
#define L_UP 1
#define ABL 0
#define BIG_ST 1
#define FLIP 1
#define URG(mt) ((((mt) >> 2) & 1) ^ FLIP)
#define AB_ST 7
#define AB_ST2 8
#define GAP_FLIP 1
#define L_PRE 1
#define E_FILL 2
#define KB_EARLY 14
#define O_N 2
#define QK_AT 10
#define WAIT_KIND 1
#define KV_FIRST 1
#define Q_ARR 11
#define E_SPLIT 7
#define RED_A 4
#define RED_FAST 6
#define L_ARR 11
#define PF0_ALL 0
#define OPOLL2_ON 1
#define E_LATE 2
#define L_SPLIT 0
#define START_N 2
#define REG_CONS 200
#define REG_AUX 104

struct __align__(64) TMaps { CUtensorMap xB, wdre, wdim, wre, wim, abP4, abP3, abH, ab32, ab80, wreH, wimH, wo64, xA3, wqkv3, outA, outB; };

__device__ __nv_bfloat16 g_abT[896 * SEQ];
__device__ uint4 g_o[SEQ * DM / 8];
__device__ uint4 g_halo[16 * 8 * 2 * 160];
__device__ unsigned g_flag_ab[40 * 32];
__device__ unsigned g_flag_o[16 * 32];
__device__ unsigned g_epoch[NCTA * 8];

__device__ __forceinline__ uint32_t smem_u32(const void* p) { return (uint32_t)__cvta_generic_to_shared(p); }
__device__ __forceinline__ uint32_t clk32() { uint32_t c; asm volatile("mov.u32 %0, %%clock;" : "=r"(c) :: "memory"); return c; }
__device__ __forceinline__ void give_up() { asm volatile("st.global.u32 [%0], 0;" :: "l"(0ull) : "memory"); }
__device__ __forceinline__ void mbar_init(uint32_t bar, uint32_t count) { asm volatile("mbarrier.init.shared::cta.b64 [%0], %1;" :: "r"(bar), "r"(count) : "memory"); }
__device__ __forceinline__ void mbar_expect_tx(uint32_t bar, uint32_t bytes) { asm volatile("mbarrier.arrive.expect_tx.shared::cta.b64 _, [%0], %1;" :: "r"(bar), "r"(bytes) : "memory"); }
__device__ __forceinline__ void mbar_arrive(uint32_t bar) { asm volatile("mbarrier.arrive.shared::cta.b64 _, [%0];" :: "r"(bar) : "memory"); }
__device__ __forceinline__ void mbar_arrive_remote(uint32_t bar, uint32_t cta) {
    asm volatile("{\n.reg .b32 ra;\nmapa.shared::cluster.u32 ra, %0, %1;\nmbarrier.arrive.shared::cluster.b64 _, [ra];\n}" :: "r"(bar), "r"(cta) : "memory");
}
__device__ __forceinline__ bool mbar_try_wait(uint32_t bar, uint32_t parity) {
    uint32_t ok;
    asm volatile("{\n.reg .pred p;\nmbarrier.try_wait.parity.shared::cta.b64 p, [%1], %2;\nselp.u32 %0, 1, 0, p;\n}" : "=r"(ok) : "r"(bar), "r"(parity) : "memory");
    return ok;
}
__device__ __forceinline__ bool mbar_test_wait(uint32_t bar, uint32_t parity) {
    uint32_t ok;
    asm volatile("{\n.reg .pred p;\nmbarrier.test_wait.parity.shared::cta.b64 p, [%1], %2;\nselp.u32 %0, 1, 0, p;\n}" : "=r"(ok) : "r"(bar), "r"(parity) : "memory");
    return ok;
}
#define WAIT_OP "pmevent 0;\nmbarrier.try_wait.parity.shared::cta.b64 p, [%0], %1;\n"
__device__ __forceinline__ void mbar_wait(uint32_t bar, uint32_t parity) {
    asm volatile("{\n.reg .pred p;\nWAIT:\n" WAIT_OP "@!p bra WAIT;\n}" :: "r"(bar), "r"(parity) : "memory");
}
__device__ __forceinline__ void mbar_wait_p(uint32_t bar, uint32_t parity) {
    asm volatile("{\n.reg .pred p;\nWAIT:\nmbarrier.try_wait.parity.shared::cta.b64 p, [%0], %1;\n@!p bra WAIT;\n}" :: "r"(bar), "r"(parity) : "memory");
}
__device__ __forceinline__ void mbar_wait_limit(uint32_t bar, uint32_t parity) {
    int it = 0;
    while (!mbar_try_wait(bar, parity)) { if (++it > SPIN_LIMIT) give_up(); }
}
__device__ __forceinline__ void tma_load(uint32_t dst, const CUtensorMap* tm, uint32_t bar, int c0, int c1) {
    asm volatile("cp.async.bulk.tensor.2d.shared::cluster.global.mbarrier::complete_tx::bytes [%0], [%1, {%3, %4}], [%2];"
        :: "r"(dst), "l"(tm), "r"(bar), "r"(c0), "r"(c1) : "memory");
}
__device__ __forceinline__ void tma_load_mc(uint32_t dst, const CUtensorMap* tm, uint32_t bar, int c0, int c1) {
    asm volatile("cp.async.bulk.tensor.2d.shared::cluster.global.mbarrier::complete_tx::bytes.multicast::cluster [%0], [%1, {%3, %4}], [%2], %5;"
        :: "r"(dst), "l"(tm), "r"(bar), "r"(c0), "r"(c1), "h"((uint16_t)3) : "memory");
}
__device__ __forceinline__ void tma_load3(uint32_t dst, const CUtensorMap* tm, uint32_t bar, int c0, int c1) {
    asm volatile("cp.async.bulk.tensor.3d.shared::cluster.global.mbarrier::complete_tx::bytes [%0], [%1, {%3, %4, %5}], [%2];"
        :: "r"(dst), "l"(tm), "r"(bar), "r"(c0), "r"(c1), "r"(0) : "memory");
}
__device__ __forceinline__ void tma_load3_mc(uint32_t dst, const CUtensorMap* tm, uint32_t bar, int c0, int c1, int c2) {
    asm volatile("cp.async.bulk.tensor.3d.shared::cluster.global.mbarrier::complete_tx::bytes.multicast::cluster [%0], [%1, {%3, %4, %6}], [%2], %5;"
        :: "r"(dst), "l"(tm), "r"(bar), "r"(c0), "r"(c1), "h"((uint16_t)3), "r"(c2) : "memory");
}
__device__ __forceinline__ void tma_prefetch(const CUtensorMap* tm, int c0, int c1) {
    asm volatile("cp.async.bulk.prefetch.tensor.2d.L2.global [%0, {%1, %2}];" :: "l"(tm), "r"(c0), "r"(c1) : "memory");
}
__device__ __forceinline__ void tma_prefetch3(const CUtensorMap* tm, int c0, int c1) {
    asm volatile("cp.async.bulk.prefetch.tensor.3d.L2.global [%0, {%1, %2, %3}];" :: "l"(tm), "r"(c0), "r"(c1), "r"(0) : "memory");
}
__device__ __forceinline__ void tma_store(const CUtensorMap* tm, uint32_t src, int c0, int c1) {
    asm volatile("cp.async.bulk.tensor.2d.global.shared::cta.bulk_group [%0, {%2, %3}], [%1];" :: "l"(tm), "r"(src), "r"(c0), "r"(c1) : "memory");
}
__device__ __forceinline__ void tma_store3(const CUtensorMap* tm, uint32_t src, int c1, int c2) {
    asm volatile("cp.async.bulk.tensor.3d.global.shared::cta.bulk_group [%0, {%2, %3, %4}], [%1];" :: "l"(tm), "r"(src), "r"(0), "r"(c1), "r"(c2) : "memory");
}
__device__ __forceinline__ void bulk_load(uint32_t dst, const void* src, uint32_t bytes, uint32_t bar) {
    asm volatile("cp.async.bulk.shared::cluster.global.mbarrier::complete_tx::bytes [%0], [%1], %2, [%3];" :: "r"(dst), "l"(src), "r"(bytes), "r"(bar) : "memory");
}
__device__ __forceinline__ void bulk_store(void* dst, uint32_t src, uint32_t bytes) {
    asm volatile("cp.async.bulk.global.shared::cta.bulk_group [%0], [%1], %2;" :: "l"(dst), "r"(src), "r"(bytes) : "memory");
}
__device__ __forceinline__ void tma_load5_mc(uint32_t dst, const CUtensorMap* tm, uint32_t bar, int c0, int c4) {
    asm volatile("cp.async.bulk.tensor.5d.shared::cluster.global.mbarrier::complete_tx::bytes.multicast::cluster [%0], [%1, {%3, %6, %6, %6, %4}], [%2], %5;"
        :: "r"(dst), "l"(tm), "r"(bar), "r"(c0), "r"(c4), "h"((uint16_t)3), "r"(0) : "memory");
}
__device__ __forceinline__ void red_add_bf16x8(__nv_bfloat16* p, uint32_t w0, uint32_t w1, uint32_t w2, uint32_t w3) {
    asm volatile("red.relaxed.gpu.global.add.noftz.v4.bf16x2 [%0], {%1, %2, %3, %4};" :: "l"(p), "r"(w0), "r"(w1), "r"(w2), "r"(w3) : "memory");
}
__device__ __forceinline__ void prefetch_tmap(const CUtensorMap* tm) { asm volatile("prefetch.tensormap [%0];" :: "l"(tm) : "memory"); }
__device__ __forceinline__ void cluster_arrive() { asm volatile("barrier.cluster.arrive.relaxed.aligned;" ::: "memory"); }
__device__ __forceinline__ void cluster_wait() { asm volatile("barrier.cluster.wait.aligned;" ::: "memory"); }
__device__ __forceinline__ void wgmma_fence() { asm volatile("wgmma.fence.sync.aligned;" ::: "memory"); }
__device__ __forceinline__ void wgmma_commit() { asm volatile("wgmma.commit_group.sync.aligned;" ::: "memory"); }
template<int N> __device__ __forceinline__ void wgmma_wait() { asm volatile("wgmma.wait_group.sync.aligned %0;" :: "n"(N) : "memory"); }
__device__ __forceinline__ void fence_async_smem() { asm volatile("fence.proxy.async.shared::cta;" ::: "memory"); }
__device__ __forceinline__ void fence_async_global() { asm volatile("fence.proxy.async.global;" ::: "memory"); }
__device__ __forceinline__ uint32_t desc_k(uint32_t addr) { return ((addr & 0x3FFFF) >> 4) | (1u << 16); }
__device__ __forceinline__ uint32_t desc_mn(uint32_t addr) { return ((addr & 0x3FFFF) >> 4) | ((8192u >> 4) << 16); }
template<int R> __device__ __forceinline__ void reg_set() {
    if (R > 168) asm volatile("setmaxnreg.inc.sync.aligned.u32 %0;" :: "n"(R));
    if (R < 168) asm volatile("setmaxnreg.dec.sync.aligned.u32 %0;" :: "n"(R));
}
__device__ __forceinline__ unsigned ld_acquire(const unsigned* p) { unsigned v; asm volatile("ld.acquire.gpu.global.u32 %0, [%1];" : "=r"(v) : "l"(p) : "memory"); return v; }
__device__ __forceinline__ unsigned ld_relaxed(const unsigned* p) { unsigned v; asm volatile("ld.relaxed.gpu.global.u32 %0, [%1];" : "=r"(v) : "l"(p) : "memory"); return v; }
__device__ __forceinline__ void st_release(unsigned* p, unsigned v) { asm volatile("fence.proxy.async.global;\nst.release.gpu.global.u32 [%0], %1;" :: "l"(p), "r"(v) : "memory"); }
__device__ __forceinline__ void red_release(unsigned* p, unsigned v) { asm volatile("fence.proxy.async.global;\nred.release.gpu.global.add.u32 [%0], %1;" :: "l"(p), "r"(v) : "memory"); }
__device__ __forceinline__ bool elect_one() {
    uint32_t pred;
    asm volatile("{\n.reg .pred p;\nelect.sync _|p, 0xffffffff;\nselp.u32 %0, 1, 0, p;\n}" : "=r"(pred));
    return pred;
}
__device__ __forceinline__ int pick3(int cta, int a, int b, int c) {
    int v;
    asm("{\n.reg .pred p, q;\nsetp.lt.s32 p, %1, 8;\nsetp.lt.s32 q, %1, 72;\nselp.b32 %0, %3, %4, q;\nselp.b32 %0, %2, %0, p;\n}" : "=&r"(v) : "r"(cta), "r"(a), "r"(b), "r"(c));
    return v;
}
template<typename T> __device__ __forceinline__ T pin(T v) {
    if constexpr (sizeof(T) == 8) asm volatile("" : "+l"(v) :: "memory"); else asm volatile("" : "+r"(v) :: "memory");
    return v;
}
__device__ __forceinline__ void bulk_commit() { asm volatile("cp.async.bulk.commit_group;" ::: "memory"); }
__device__ __forceinline__ void bulk_wait_all() { asm volatile("cp.async.bulk.wait_group 0;" ::: "memory"); }
__device__ __forceinline__ uint32_t pack_bf16(float lo, float hi) { uint32_t r; asm("cvt.rn.bf16x2.f32 %0, %1, %2;" : "=r"(r) : "f"(hi), "f"(lo)); return r; }
__device__ __forceinline__ float bf_lo(uint32_t w) { return __uint_as_float(w << 16); }
__device__ __forceinline__ float bf_hi(uint32_t w) { return __uint_as_float(w & 0xffff0000u); }
__device__ __forceinline__ void stsm_x4(uint32_t addr, uint32_t r0, uint32_t r1, uint32_t r2, uint32_t r3) {
    asm volatile("stmatrix.sync.aligned.m8n8.x4.shared.b16 [%0], {%1, %2, %3, %4};" :: "r"(addr), "r"(r0), "r"(r1), "r"(r2), "r"(r3) : "memory");
}
__device__ __forceinline__ void stsm_x2(uint32_t addr, uint32_t r0, uint32_t r1) {
    asm volatile("stmatrix.sync.aligned.m8n8.x2.shared.b16 [%0], {%1, %2};" :: "r"(addr), "r"(r0), "r"(r1) : "memory");
}
__device__ __forceinline__ void stsm_x4_t(uint32_t addr, uint32_t r0, uint32_t r1, uint32_t r2, uint32_t r3) {
    asm volatile("stmatrix.sync.aligned.m8n8.x4.trans.shared.b16 [%0], {%1, %2, %3, %4};" :: "r"(addr), "r"(r0), "r"(r1), "r"(r2), "r"(r3) : "memory");
}
__device__ __forceinline__ void stsm_x2_t(uint32_t addr, uint32_t r0, uint32_t r1) {
    asm volatile("stmatrix.sync.aligned.m8n8.x2.trans.shared.b16 [%0], {%1, %2};" :: "r"(addr), "r"(r0), "r"(r1) : "memory");
}
__device__ __forceinline__ uint32_t movm_t(uint32_t x) { uint32_t r; asm volatile("movmatrix.sync.aligned.m8n8.trans.b16 %0, %1;" : "=r"(r) : "r"(x)); return r; }
__device__ __forceinline__ void ldsm_x4(uint32_t addr, uint32_t& r0, uint32_t& r1, uint32_t& r2, uint32_t& r3) {
    asm volatile("ldmatrix.sync.aligned.m8n8.x4.shared.b16 {%0, %1, %2, %3}, [%4];" : "=r"(r0), "=r"(r1), "=r"(r2), "=r"(r3) : "r"(addr) : "memory");
}
__device__ __forceinline__ void ldsm_x4_t(uint32_t addr, uint32_t& r0, uint32_t& r1, uint32_t& r2, uint32_t& r3) {
    asm volatile("ldmatrix.sync.aligned.m8n8.x4.trans.shared.b16 {%0, %1, %2, %3}, [%4];" : "=r"(r0), "=r"(r1), "=r"(r2), "=r"(r3) : "r"(addr) : "memory");
}
__device__ __forceinline__ void mma16816(float (&d)[4], uint32_t a0, uint32_t a1, uint32_t a2, uint32_t a3, uint32_t b0, uint32_t b1) {
    asm("mma.sync.aligned.m16n8k16.row.col.f32.bf16.bf16.f32 {%0, %1, %2, %3}, {%4, %5, %6, %7}, {%8, %9}, {%0, %1, %2, %3};"
        : "+f"(d[0]), "+f"(d[1]), "+f"(d[2]), "+f"(d[3]) : "r"(a0), "r"(a1), "r"(a2), "r"(a3), "r"(b0), "r"(b1));
}
__device__ __forceinline__ void mma1688(float (&d)[4], uint32_t a0, uint32_t a1, uint32_t b0) {
    asm("mma.sync.aligned.m16n8k8.row.col.f32.bf16.bf16.f32 {%0, %1, %2, %3}, {%4, %5}, {%6}, {%0, %1, %2, %3};"
        : "+f"(d[0]), "+f"(d[1]), "+f"(d[2]), "+f"(d[3]) : "r"(a0), "r"(a1), "r"(b0));
}
__device__ __forceinline__ uint32_t max_bf16x2(uint32_t a, uint32_t b) { uint32_t r; asm("max.bf16x2 %0, %1, %2;" : "=r"(r) : "r"(a), "r"(b)); return r; }
__device__ __forceinline__ float bf16_round(float x) { return __bfloat162float(__float2bfloat16_rn(x)); }
__device__ __forceinline__ uint32_t lds32(uint32_t addr) { uint32_t v; asm volatile("ld.shared.u32 %0, [%1];" : "=r"(v) : "r"(addr)); return v; }
__device__ __forceinline__ float ex2_approx(float x) { float y; asm("ex2.approx.ftz.f32 %0, %1;" : "=f"(y) : "f"(x)); return y; }
__device__ __forceinline__ float rcp_approx(float x) { float y; asm("rcp.approx.ftz.f32 %0, %1;" : "=f"(y) : "f"(x)); return y; }
__device__ __forceinline__ void st_b128_relaxed(uint4* p, uint32_t w0, uint32_t w1, uint32_t w2, uint32_t w3) {
    asm volatile("{\n.reg .b128 t;\n.reg .b64 lo, hi;\nmov.b64 lo, {%1, %2};\nmov.b64 hi, {%3, %4};\nmov.b128 t, {lo, hi};\nst.relaxed.gpu.global.b128 [%0], t;\n}"
        :: "l"(p), "r"(w0), "r"(w1), "r"(w2), "r"(w3) : "memory");
}
__device__ __forceinline__ uint4 ld_b128_relaxed(const uint4* p) {
    uint4 v;
    asm volatile("{\n.reg .b128 t;\n.reg .b64 lo, hi;\nld.relaxed.gpu.global.b128 t, [%4];\nmov.b128 {lo, hi}, t;\nmov.b64 {%0, %1}, lo;\nmov.b64 {%2, %3}, hi;\n}"
        : "=r"(v.x), "=r"(v.y), "=r"(v.z), "=r"(v.w) : "l"(p) : "memory");
    return v;
}

template<int SA, int TB, int HA = 0x40000040, int M>
__device__ __forceinline__ void wgmma_n8(float (&d)[M], uint32_t da, uint32_t db, int scale_d) {
    asm volatile("{\n.reg .pred p;\n.reg .b32 hi, ha;\n.reg .b64 da, db;\nmov.b32 hi, 0x40000040;\nmov.b32 ha, %9;\nmov.b64 da, {%4, ha};\nmov.b64 db, {%5, hi};\nsetp.ne.b32 p, %6, 0;\n"
        "wgmma.mma_async.sync.aligned.m64n8k16.f32.bf16.bf16 "
        "{%0, %1, %2, %3}, "
        "da, db, p, %8, 1, 0, %7;\n}\n"
        : "+f"(d[0]), "+f"(d[1]), "+f"(d[2]), "+f"(d[3])
        : "r"(da), "r"(db), "r"(scale_d), "n"(TB), "n"(SA), "n"(HA));
}
template<int SA, int TB, int HA = 0x40000040, int M>
__device__ __forceinline__ void wgmma_n96(float (&d)[M], uint32_t da, uint32_t db, int scale_d) {
    asm volatile("{\n.reg .pred p;\n.reg .b32 hi, ha;\n.reg .b64 da, db;\nmov.b32 hi, 0x40000040;\nmov.b32 ha, %53;\nmov.b64 da, {%48, ha};\nmov.b64 db, {%49, hi};\nsetp.ne.b32 p, %50, 0;\n"
        "wgmma.mma_async.sync.aligned.m64n96k16.f32.bf16.bf16 "
        "{%0, %1, %2, %3, %4, %5, %6, %7, %8, %9, %10, %11, %12, %13, %14, %15, "
        "%16, %17, %18, %19, %20, %21, %22, %23, %24, %25, %26, %27, %28, %29, %30, %31, "
        "%32, %33, %34, %35, %36, %37, %38, %39, %40, %41, %42, %43, %44, %45, %46, %47}, "
        "da, db, p, %52, 1, 0, %51;\n}\n"
        : "+f"(d[0]), "+f"(d[1]), "+f"(d[2]), "+f"(d[3]), "+f"(d[4]), "+f"(d[5]), "+f"(d[6]), "+f"(d[7]),
          "+f"(d[8]), "+f"(d[9]), "+f"(d[10]), "+f"(d[11]), "+f"(d[12]), "+f"(d[13]), "+f"(d[14]), "+f"(d[15]),
          "+f"(d[16]), "+f"(d[17]), "+f"(d[18]), "+f"(d[19]), "+f"(d[20]), "+f"(d[21]), "+f"(d[22]), "+f"(d[23]),
          "+f"(d[24]), "+f"(d[25]), "+f"(d[26]), "+f"(d[27]), "+f"(d[28]), "+f"(d[29]), "+f"(d[30]), "+f"(d[31]),
          "+f"(d[32]), "+f"(d[33]), "+f"(d[34]), "+f"(d[35]), "+f"(d[36]), "+f"(d[37]), "+f"(d[38]), "+f"(d[39]),
          "+f"(d[40]), "+f"(d[41]), "+f"(d[42]), "+f"(d[43]), "+f"(d[44]), "+f"(d[45]), "+f"(d[46]), "+f"(d[47])
        : "r"(da), "r"(db), "r"(scale_d), "n"(TB), "n"(SA), "n"(HA));
}
template<int SA, int TB, int HA = 0x40000040, int M>
__device__ __forceinline__ void wgmma_n112(float (&d)[M], uint32_t da, uint32_t db, int scale_d) {
    asm volatile("{\n.reg .pred p;\n.reg .b32 hi, ha;\n.reg .b64 da, db;\nmov.b32 hi, 0x40000040;\nmov.b32 ha, %61;\nmov.b64 da, {%56, ha};\nmov.b64 db, {%57, hi};\nsetp.ne.b32 p, %58, 0;\n"
        "wgmma.mma_async.sync.aligned.m64n112k16.f32.bf16.bf16 "
        "{%0, %1, %2, %3, %4, %5, %6, %7, %8, %9, %10, %11, %12, %13, %14, %15, "
        "%16, %17, %18, %19, %20, %21, %22, %23, %24, %25, %26, %27, %28, %29, %30, %31, "
        "%32, %33, %34, %35, %36, %37, %38, %39, %40, %41, %42, %43, %44, %45, %46, %47, "
        "%48, %49, %50, %51, %52, %53, %54, %55}, "
        "da, db, p, %60, 1, 0, %59;\n}\n"
        : "+f"(d[0]), "+f"(d[1]), "+f"(d[2]), "+f"(d[3]), "+f"(d[4]), "+f"(d[5]), "+f"(d[6]), "+f"(d[7]),
          "+f"(d[8]), "+f"(d[9]), "+f"(d[10]), "+f"(d[11]), "+f"(d[12]), "+f"(d[13]), "+f"(d[14]), "+f"(d[15]),
          "+f"(d[16]), "+f"(d[17]), "+f"(d[18]), "+f"(d[19]), "+f"(d[20]), "+f"(d[21]), "+f"(d[22]), "+f"(d[23]),
          "+f"(d[24]), "+f"(d[25]), "+f"(d[26]), "+f"(d[27]), "+f"(d[28]), "+f"(d[29]), "+f"(d[30]), "+f"(d[31]),
          "+f"(d[32]), "+f"(d[33]), "+f"(d[34]), "+f"(d[35]), "+f"(d[36]), "+f"(d[37]), "+f"(d[38]), "+f"(d[39]),
          "+f"(d[40]), "+f"(d[41]), "+f"(d[42]), "+f"(d[43]), "+f"(d[44]), "+f"(d[45]), "+f"(d[46]), "+f"(d[47]),
          "+f"(d[48]), "+f"(d[49]), "+f"(d[50]), "+f"(d[51]), "+f"(d[52]), "+f"(d[53]), "+f"(d[54]), "+f"(d[55])
        : "r"(da), "r"(db), "r"(scale_d), "n"(TB), "n"(SA), "n"(HA));
}
template<int SA, int TB, int HA = 0x40000040, int M>
__device__ __forceinline__ void wgmma_n128(float (&d)[M], uint32_t da, uint32_t db, int scale_d) {
    asm volatile("{\n.reg .pred p;\n.reg .b32 hi, ha;\n.reg .b64 da, db;\nmov.b32 hi, 0x40000040;\nmov.b32 ha, %69;\nmov.b64 da, {%64, ha};\nmov.b64 db, {%65, hi};\nsetp.ne.b32 p, %66, 0;\n"
        "wgmma.mma_async.sync.aligned.m64n128k16.f32.bf16.bf16 "
        "{%0, %1, %2, %3, %4, %5, %6, %7, %8, %9, %10, %11, %12, %13, %14, %15, "
        "%16, %17, %18, %19, %20, %21, %22, %23, %24, %25, %26, %27, %28, %29, %30, %31, "
        "%32, %33, %34, %35, %36, %37, %38, %39, %40, %41, %42, %43, %44, %45, %46, %47, "
        "%48, %49, %50, %51, %52, %53, %54, %55, %56, %57, %58, %59, %60, %61, %62, %63}, "
        "da, db, p, %68, 1, 0, %67;\n}\n"
        : "+f"(d[0]), "+f"(d[1]), "+f"(d[2]), "+f"(d[3]), "+f"(d[4]), "+f"(d[5]), "+f"(d[6]), "+f"(d[7]),
          "+f"(d[8]), "+f"(d[9]), "+f"(d[10]), "+f"(d[11]), "+f"(d[12]), "+f"(d[13]), "+f"(d[14]), "+f"(d[15]),
          "+f"(d[16]), "+f"(d[17]), "+f"(d[18]), "+f"(d[19]), "+f"(d[20]), "+f"(d[21]), "+f"(d[22]), "+f"(d[23]),
          "+f"(d[24]), "+f"(d[25]), "+f"(d[26]), "+f"(d[27]), "+f"(d[28]), "+f"(d[29]), "+f"(d[30]), "+f"(d[31]),
          "+f"(d[32]), "+f"(d[33]), "+f"(d[34]), "+f"(d[35]), "+f"(d[36]), "+f"(d[37]), "+f"(d[38]), "+f"(d[39]),
          "+f"(d[40]), "+f"(d[41]), "+f"(d[42]), "+f"(d[43]), "+f"(d[44]), "+f"(d[45]), "+f"(d[46]), "+f"(d[47]),
          "+f"(d[48]), "+f"(d[49]), "+f"(d[50]), "+f"(d[51]), "+f"(d[52]), "+f"(d[53]), "+f"(d[54]), "+f"(d[55]),
          "+f"(d[56]), "+f"(d[57]), "+f"(d[58]), "+f"(d[59]), "+f"(d[60]), "+f"(d[61]), "+f"(d[62]), "+f"(d[63])
        : "r"(da), "r"(db), "r"(scale_d), "n"(TB), "n"(SA), "n"(HA));
}
template<int SA, int TB, int HA = 0x40000040, int M>
__device__ __forceinline__ void wgmma_n224(float (&d)[M], uint32_t da, uint32_t db, int scale_d) {
    asm volatile("{\n.reg .pred p;\n.reg .b32 hi, ha;\n.reg .b64 da, db;\nmov.b32 hi, 0x40000040;\nmov.b32 ha, %117;\nmov.b64 da, {%112, ha};\nmov.b64 db, {%113, hi};\nsetp.ne.b32 p, %114, 0;\n"
        "wgmma.mma_async.sync.aligned.m64n224k16.f32.bf16.bf16 "
        "{%0, %1, %2, %3, %4, %5, %6, %7, %8, %9, %10, %11, %12, %13, %14, %15, "
        "%16, %17, %18, %19, %20, %21, %22, %23, %24, %25, %26, %27, %28, %29, %30, %31, "
        "%32, %33, %34, %35, %36, %37, %38, %39, %40, %41, %42, %43, %44, %45, %46, %47, "
        "%48, %49, %50, %51, %52, %53, %54, %55, %56, %57, %58, %59, %60, %61, %62, %63, "
        "%64, %65, %66, %67, %68, %69, %70, %71, %72, %73, %74, %75, %76, %77, %78, %79, "
        "%80, %81, %82, %83, %84, %85, %86, %87, %88, %89, %90, %91, %92, %93, %94, %95, "
        "%96, %97, %98, %99, %100, %101, %102, %103, %104, %105, %106, %107, %108, %109, %110, %111}, "
        "da, db, p, %116, 1, 0, %115;\n}\n"
        : "+f"(d[0]), "+f"(d[1]), "+f"(d[2]), "+f"(d[3]), "+f"(d[4]), "+f"(d[5]), "+f"(d[6]), "+f"(d[7]),
          "+f"(d[8]), "+f"(d[9]), "+f"(d[10]), "+f"(d[11]), "+f"(d[12]), "+f"(d[13]), "+f"(d[14]), "+f"(d[15]),
          "+f"(d[16]), "+f"(d[17]), "+f"(d[18]), "+f"(d[19]), "+f"(d[20]), "+f"(d[21]), "+f"(d[22]), "+f"(d[23]),
          "+f"(d[24]), "+f"(d[25]), "+f"(d[26]), "+f"(d[27]), "+f"(d[28]), "+f"(d[29]), "+f"(d[30]), "+f"(d[31]),
          "+f"(d[32]), "+f"(d[33]), "+f"(d[34]), "+f"(d[35]), "+f"(d[36]), "+f"(d[37]), "+f"(d[38]), "+f"(d[39]),
          "+f"(d[40]), "+f"(d[41]), "+f"(d[42]), "+f"(d[43]), "+f"(d[44]), "+f"(d[45]), "+f"(d[46]), "+f"(d[47]),
          "+f"(d[48]), "+f"(d[49]), "+f"(d[50]), "+f"(d[51]), "+f"(d[52]), "+f"(d[53]), "+f"(d[54]), "+f"(d[55]),
          "+f"(d[56]), "+f"(d[57]), "+f"(d[58]), "+f"(d[59]), "+f"(d[60]), "+f"(d[61]), "+f"(d[62]), "+f"(d[63]),
          "+f"(d[64]), "+f"(d[65]), "+f"(d[66]), "+f"(d[67]), "+f"(d[68]), "+f"(d[69]), "+f"(d[70]), "+f"(d[71]),
          "+f"(d[72]), "+f"(d[73]), "+f"(d[74]), "+f"(d[75]), "+f"(d[76]), "+f"(d[77]), "+f"(d[78]), "+f"(d[79]),
          "+f"(d[80]), "+f"(d[81]), "+f"(d[82]), "+f"(d[83]), "+f"(d[84]), "+f"(d[85]), "+f"(d[86]), "+f"(d[87]),
          "+f"(d[88]), "+f"(d[89]), "+f"(d[90]), "+f"(d[91]), "+f"(d[92]), "+f"(d[93]), "+f"(d[94]), "+f"(d[95]),
          "+f"(d[96]), "+f"(d[97]), "+f"(d[98]), "+f"(d[99]), "+f"(d[100]), "+f"(d[101]), "+f"(d[102]), "+f"(d[103]),
          "+f"(d[104]), "+f"(d[105]), "+f"(d[106]), "+f"(d[107]), "+f"(d[108]), "+f"(d[109]), "+f"(d[110]), "+f"(d[111])
        : "r"(da), "r"(db), "r"(scale_d), "n"(TB), "n"(SA), "n"(HA));
}
template<int TB, int SA = 1>
__device__ __forceinline__ void wgmma_rs_n32(float (&d)[16], const uint32_t (&a)[4], uint32_t db, int scale_d) {
    asm volatile("{\n.reg .pred p;\n.reg .b32 hi;\n.reg .b64 db;\nmov.b32 hi, 0x40000040;\nmov.b64 db, {%20, hi};\nsetp.ne.b32 p, %21, 0;\n"
        "wgmma.mma_async.sync.aligned.m64n32k16.f32.bf16.bf16 "
        "{%0, %1, %2, %3, %4, %5, %6, %7, %8, %9, %10, %11, %12, %13, %14, %15}, "
        "{%16, %17, %18, %19}, db, p, %23, 1, %22;\n}\n"
        : "+f"(d[0]), "+f"(d[1]), "+f"(d[2]), "+f"(d[3]), "+f"(d[4]), "+f"(d[5]), "+f"(d[6]), "+f"(d[7]),
          "+f"(d[8]), "+f"(d[9]), "+f"(d[10]), "+f"(d[11]), "+f"(d[12]), "+f"(d[13]), "+f"(d[14]), "+f"(d[15])
        : "r"(a[0]), "r"(a[1]), "r"(a[2]), "r"(a[3]), "r"(db), "r"(scale_d), "n"(TB), "n"(SA));
}
template<int TB, int SA = 1>
__device__ __forceinline__ void wgmma_rs_n56(float (&d)[28], const uint32_t (&a)[4], uint32_t db, int scale_d) {
    asm volatile("{\n.reg .pred p;\n.reg .b32 hi;\n.reg .b64 db;\nmov.b32 hi, 0x40000040;\nmov.b64 db, {%32, hi};\nsetp.ne.b32 p, %33, 0;\n"
        "wgmma.mma_async.sync.aligned.m64n56k16.f32.bf16.bf16 "
        "{%0, %1, %2, %3, %4, %5, %6, %7, %8, %9, %10, %11, %12, %13, %14, %15, "
        "%16, %17, %18, %19, %20, %21, %22, %23, %24, %25, %26, %27}, "
        "{%28, %29, %30, %31}, db, p, %35, 1, %34;\n}\n"
        : "+f"(d[0]), "+f"(d[1]), "+f"(d[2]), "+f"(d[3]), "+f"(d[4]), "+f"(d[5]), "+f"(d[6]), "+f"(d[7]),
          "+f"(d[8]), "+f"(d[9]), "+f"(d[10]), "+f"(d[11]), "+f"(d[12]), "+f"(d[13]), "+f"(d[14]), "+f"(d[15]),
          "+f"(d[16]), "+f"(d[17]), "+f"(d[18]), "+f"(d[19]), "+f"(d[20]), "+f"(d[21]), "+f"(d[22]), "+f"(d[23]),
          "+f"(d[24]), "+f"(d[25]), "+f"(d[26]), "+f"(d[27])
        : "r"(a[0]), "r"(a[1]), "r"(a[2]), "r"(a[3]), "r"(db), "r"(scale_d), "n"(TB), "n"(SA));
}
template<int TB, int SA = 1>
__device__ __forceinline__ void wgmma_rs_n64(float (&d)[32], const uint32_t (&a)[4], uint32_t db, int scale_d) {
    asm volatile("{\n.reg .pred p;\n.reg .b32 hi;\n.reg .b64 db;\nmov.b32 hi, 0x40000040;\nmov.b64 db, {%36, hi};\nsetp.ne.b32 p, %37, 0;\n"
        "wgmma.mma_async.sync.aligned.m64n64k16.f32.bf16.bf16 "
        "{%0, %1, %2, %3, %4, %5, %6, %7, %8, %9, %10, %11, %12, %13, %14, %15, "
        "%16, %17, %18, %19, %20, %21, %22, %23, %24, %25, %26, %27, %28, %29, %30, %31}, "
        "{%32, %33, %34, %35}, db, p, %39, 1, %38;\n}\n"
        : "+f"(d[0]), "+f"(d[1]), "+f"(d[2]), "+f"(d[3]), "+f"(d[4]), "+f"(d[5]), "+f"(d[6]), "+f"(d[7]),
          "+f"(d[8]), "+f"(d[9]), "+f"(d[10]), "+f"(d[11]), "+f"(d[12]), "+f"(d[13]), "+f"(d[14]), "+f"(d[15]),
          "+f"(d[16]), "+f"(d[17]), "+f"(d[18]), "+f"(d[19]), "+f"(d[20]), "+f"(d[21]), "+f"(d[22]), "+f"(d[23]),
          "+f"(d[24]), "+f"(d[25]), "+f"(d[26]), "+f"(d[27]), "+f"(d[28]), "+f"(d[29]), "+f"(d[30]), "+f"(d[31])
        : "r"(a[0]), "r"(a[1]), "r"(a[2]), "r"(a[3]), "r"(db), "r"(scale_d), "n"(TB), "n"(SA));
}
template<int TB, int SA = 1>
__device__ __forceinline__ void wgmma_rs_n112(float (&d)[56], const uint32_t (&a)[4], uint32_t db, int scale_d) {
    asm volatile("{\n.reg .pred p;\n.reg .b32 hi;\n.reg .b64 db;\nmov.b32 hi, 0x40000040;\nmov.b64 db, {%60, hi};\nsetp.ne.b32 p, %61, 0;\n"
        "wgmma.mma_async.sync.aligned.m64n112k16.f32.bf16.bf16 "
        "{%0, %1, %2, %3, %4, %5, %6, %7, %8, %9, %10, %11, %12, %13, %14, %15, "
        "%16, %17, %18, %19, %20, %21, %22, %23, %24, %25, %26, %27, %28, %29, %30, %31, "
        "%32, %33, %34, %35, %36, %37, %38, %39, %40, %41, %42, %43, %44, %45, %46, %47, "
        "%48, %49, %50, %51, %52, %53, %54, %55}, "
        "{%56, %57, %58, %59}, db, p, %63, 1, %62;\n}\n"
        : "+f"(d[0]), "+f"(d[1]), "+f"(d[2]), "+f"(d[3]), "+f"(d[4]), "+f"(d[5]), "+f"(d[6]), "+f"(d[7]),
          "+f"(d[8]), "+f"(d[9]), "+f"(d[10]), "+f"(d[11]), "+f"(d[12]), "+f"(d[13]), "+f"(d[14]), "+f"(d[15]),
          "+f"(d[16]), "+f"(d[17]), "+f"(d[18]), "+f"(d[19]), "+f"(d[20]), "+f"(d[21]), "+f"(d[22]), "+f"(d[23]),
          "+f"(d[24]), "+f"(d[25]), "+f"(d[26]), "+f"(d[27]), "+f"(d[28]), "+f"(d[29]), "+f"(d[30]), "+f"(d[31]),
          "+f"(d[32]), "+f"(d[33]), "+f"(d[34]), "+f"(d[35]), "+f"(d[36]), "+f"(d[37]), "+f"(d[38]), "+f"(d[39]),
          "+f"(d[40]), "+f"(d[41]), "+f"(d[42]), "+f"(d[43]), "+f"(d[44]), "+f"(d[45]), "+f"(d[46]), "+f"(d[47]),
          "+f"(d[48]), "+f"(d[49]), "+f"(d[50]), "+f"(d[51]), "+f"(d[52]), "+f"(d[53]), "+f"(d[54]), "+f"(d[55])
        : "r"(a[0]), "r"(a[1]), "r"(a[2]), "r"(a[3]), "r"(db), "r"(scale_d), "n"(TB), "n"(SA));
}
template<int TB, int SA = 1>
__device__ __forceinline__ void wgmma_rs_n224(float (&d)[112], const uint32_t (&a)[4], uint32_t db, int scale_d) {
    asm volatile("{\n.reg .pred p;\n.reg .b32 hi;\n.reg .b64 db;\nmov.b32 hi, 0x40000040;\nmov.b64 db, {%116, hi};\nsetp.ne.b32 p, %117, 0;\n"
        "wgmma.mma_async.sync.aligned.m64n224k16.f32.bf16.bf16 "
        "{%0, %1, %2, %3, %4, %5, %6, %7, %8, %9, %10, %11, %12, %13, %14, %15, "
        "%16, %17, %18, %19, %20, %21, %22, %23, %24, %25, %26, %27, %28, %29, %30, %31, "
        "%32, %33, %34, %35, %36, %37, %38, %39, %40, %41, %42, %43, %44, %45, %46, %47, "
        "%48, %49, %50, %51, %52, %53, %54, %55, %56, %57, %58, %59, %60, %61, %62, %63, "
        "%64, %65, %66, %67, %68, %69, %70, %71, %72, %73, %74, %75, %76, %77, %78, %79, "
        "%80, %81, %82, %83, %84, %85, %86, %87, %88, %89, %90, %91, %92, %93, %94, %95, "
        "%96, %97, %98, %99, %100, %101, %102, %103, %104, %105, %106, %107, %108, %109, %110, %111}, "
        "{%112, %113, %114, %115}, db, p, %119, 1, %118;\n}\n"
        : "+f"(d[0]), "+f"(d[1]), "+f"(d[2]), "+f"(d[3]), "+f"(d[4]), "+f"(d[5]), "+f"(d[6]), "+f"(d[7]),
          "+f"(d[8]), "+f"(d[9]), "+f"(d[10]), "+f"(d[11]), "+f"(d[12]), "+f"(d[13]), "+f"(d[14]), "+f"(d[15]),
          "+f"(d[16]), "+f"(d[17]), "+f"(d[18]), "+f"(d[19]), "+f"(d[20]), "+f"(d[21]), "+f"(d[22]), "+f"(d[23]),
          "+f"(d[24]), "+f"(d[25]), "+f"(d[26]), "+f"(d[27]), "+f"(d[28]), "+f"(d[29]), "+f"(d[30]), "+f"(d[31]),
          "+f"(d[32]), "+f"(d[33]), "+f"(d[34]), "+f"(d[35]), "+f"(d[36]), "+f"(d[37]), "+f"(d[38]), "+f"(d[39]),
          "+f"(d[40]), "+f"(d[41]), "+f"(d[42]), "+f"(d[43]), "+f"(d[44]), "+f"(d[45]), "+f"(d[46]), "+f"(d[47]),
          "+f"(d[48]), "+f"(d[49]), "+f"(d[50]), "+f"(d[51]), "+f"(d[52]), "+f"(d[53]), "+f"(d[54]), "+f"(d[55]),
          "+f"(d[56]), "+f"(d[57]), "+f"(d[58]), "+f"(d[59]), "+f"(d[60]), "+f"(d[61]), "+f"(d[62]), "+f"(d[63]),
          "+f"(d[64]), "+f"(d[65]), "+f"(d[66]), "+f"(d[67]), "+f"(d[68]), "+f"(d[69]), "+f"(d[70]), "+f"(d[71]),
          "+f"(d[72]), "+f"(d[73]), "+f"(d[74]), "+f"(d[75]), "+f"(d[76]), "+f"(d[77]), "+f"(d[78]), "+f"(d[79]),
          "+f"(d[80]), "+f"(d[81]), "+f"(d[82]), "+f"(d[83]), "+f"(d[84]), "+f"(d[85]), "+f"(d[86]), "+f"(d[87]),
          "+f"(d[88]), "+f"(d[89]), "+f"(d[90]), "+f"(d[91]), "+f"(d[92]), "+f"(d[93]), "+f"(d[94]), "+f"(d[95]),
          "+f"(d[96]), "+f"(d[97]), "+f"(d[98]), "+f"(d[99]), "+f"(d[100]), "+f"(d[101]), "+f"(d[102]), "+f"(d[103]),
          "+f"(d[104]), "+f"(d[105]), "+f"(d[106]), "+f"(d[107]), "+f"(d[108]), "+f"(d[109]), "+f"(d[110]), "+f"(d[111])
        : "r"(a[0]), "r"(a[1]), "r"(a[2]), "r"(a[3]), "r"(db), "r"(scale_d), "n"(TB), "n"(SA));
}

#define TR(idx) do {} while (0)
#define TRL(idx) do {} while (0)
#define TRX(idx) do {} while (0)
#define TRG(idx) do {} while (0)
#define TR_END() do {} while (0)

template<int V> struct Int { static constexpr int value = V; };
constexpr float ATT_SCALE = 0.18898223650461361f;
constexpr float LOG2E = 1.4426950408889634f;
constexpr uint32_t MASKED = 0xce6ece6eu;

__global__ void __cluster_dims__(2, 1, 1) __launch_bounds__(384, 1)
fused_kernel(__nv_bfloat16* __restrict__ out,
    const __grid_constant__ TMaps tm) {
    extern __shared__ __align__(1024) uint8_t smem_raw[];
    const uint32_t sb = smem_u32(smem_raw);
    const uint32_t bars = sb + BAR_OFF;
    const uint32_t bar_full = bars, bar_empty = bars + 32, bar_abf = bars + 64  , bar_ab6 = bars + 120, bar_ab = bars + 128  , bar_free = bars + 296  , bar_halo = bars + 152;
    const uint32_t bar_o = bars + 160, bar_qkv = bars + 176  , bar_sf = bars + 200, bar_se = bar_sf + 32  ;
    const uint32_t bar_fl = bars + 256  , bar_go = bars + 240  , bar_end = bars + 192, bar_af = bars + 312;
    const uint32_t stg = sb + STG_OFF;
    const int cta = blockIdx.x, r = cta & 1, cl = cta >> 1, tq = (cl * 37 - 36 * 37) >> 8;
    const int mt = pick3(cta, r, (cta - 8) & 15, cta - 70 - 14 * tq);
    const int sub = pick3(cta, 4 + cl, (cta - 8) >> 4, 4 + tq);
    const CUtensorMap* tmWd = sub < 4 ? &tm.wdre : &tm.wdim;
    uint32_t t_first = 0;
    if (threadIdx.x < 32 + (((uint32_t)(uintptr_t)tmWd | sb | (mt << 6)) & 32) && elect_one()) {
        prefetch_tmap(tmWd); prefetch_tmap(&tm.xB);
        #pragma unroll
        for (int kb = 0; kb < START_N; kb++) {
            mbar_init(bar_abf + 8 * kb, 1);
            mbar_expect_tx(bar_abf + 8 * kb, AB_BYTES);
            tma_load(sb + kb * AB_BYTES + SLOT_A, tmWd, bar_abf + 8 * kb, kb * 64, (sub & 3) * 112);
            tma_load(sb + kb * AB_BYTES, &tm.xB, bar_abf + 8 * kb, kb * 64, mt * 128);
        }
        t_first = clk32();
    }
    const int tid = threadIdx.x, warp = __shfl_sync(0xffffffffu, tid >> 5, 0), lane = tid & 31;
    const bool late = sub < 4;
    const int nh = sub & 1, part = (sub >> 1) & 1;
    const int nj = late ? 32 - KB_EARLY : KB_EARLY;
    static_assert(KB_EARLY == 14, "order of the k-blocks");
    const uint32_t t0 = clk32();
    auto clear_out = [&]() {
        while ((int)(clk32() - t0) < TP(ZERO_AT)) { }
        uint4* zp = reinterpret_cast<uint4*>(out + (size_t)(mt * 128 + sub * 16 + (warp - 2) * 8) * NOUT + DM) + lane;
        #pragma unroll 1
        for (int j = 0; j < (ABL & 8 ? 0 : 8); j++) {
            while ((int)(clk32() - t0) < TP(ZERO_AT) + j * TP(ZERO_GAP)) { }
            zp[j * (NOUT / 8)] = make_uint4(0, 0, 0, 0);
            if (lane < 24) zp[j * (NOUT / 8) + 32] = make_uint4(0, 0, 0, 0);
        }
    };
    if (warp == 0) {
        if (elect_one()) {
            #pragma unroll
            for (int s = START_N; s < 7; s++) mbar_init(bar_abf + 8 * s, 1);
            #pragma unroll
            for (int s = 0; s < NSLOT; s++) { mbar_init(bar_full + 8 * s, 1); mbar_init(bar_empty + 8 * s, 4); }
            asm volatile("fence.mbarrier_init.release.cluster;" ::: "memory");
        }
        __syncwarp();
        cluster_arrive();
        if (elect_one()) {
            #pragma unroll 1
            for (int kb = START_N; kb < 7; kb++) {
                while ((int)(clk32() - t_first) < TP(START_GAP1) + (kb - START_N) * TP(START_GAP)) { }
                const uint32_t a = sb + kb * AB_BYTES, fb = bar_abf + 8 * kb;
                mbar_expect_tx(fb, AB_BYTES);
                tma_load(a, &tm.xB, fb, kb * 64, mt * 128);
                tma_load(a + SLOT_A, tmWd, fb, kb * 64, (sub & 3) * 112);
            }
            TR(2);
            prefetch_tmap(&tm.xA3); prefetch_tmap(&tm.wqkv3);
            if (TP(PF0_N) > 0) {
                while ((int)(clk32() - t_first) < TP(PF0_AT)) { }
                #pragma unroll 1
                for (int it = 0; it < TP(PF0_N); it++) {
                    if (PF0_ALL || (sub & 3) == it) tma_prefetch3(&tm.xA3, it * 64, mt * 64);
                    if (PF0_ALL || (mt >> 1) == it) tma_prefetch3(&tm.wqkv3, sub * 56 - (sub & 1) * 8, it * 64 + r * 32);
                }
            }
        }
        __syncwarp();
    } else if (warp < 4) {
        cluster_arrive();
        if (warp >= 2) clear_out();
    }
    if (warp < 4) {
      reg_set<REG_AUX>();
      const CUtensorMap* tmB = r ? &tm.abP3 : &tm.abP4;
      const uint32_t boff = SLOT_A + r * 16384;
      const int bgrp = part * 14 + nh * 7 + r * 4;
      if (warp == 0) {
        cluster_wait();
        if (elect_one()) {
        uint32_t slot = sb, fb = bar_full, par = 0;
        auto advance = [&]() { if (fb == bar_full + 24) { fb = bar_full; slot = sb; par ^= 1; } else { fb += 8; slot += SLOT_BYTES; } };
        const CUtensorMap* tmW = part ? &tm.wim : &tm.wre;
        const CUtensorMap* tmH = part ? &tm.wimH : &tm.wreH;
        const int qc = sub * 56 - (sub & 1) * 8;
        auto next_kc = [&](int kc, int wi) { return wi == 3 ? (late ? 14 * 64 : 2 * 64) : wi == nj / 2 - 1 ? (late ? 15 * 64 : 64) : kc + (FLIP && wi == 1 ? -768 : wi < nj / 2 ? 256 : 128); };
        #pragma unroll 1
        for (int it = 0; it < 7; it++) {
            mbar_wait_p(fb + 32, par);
            mbar_expect_tx(fb, SLOT_A + 3 * 8192);
            tma_load3(slot, &tm.xA3, fb, it * 64, mt * 64);
            tma_load3_mc(slot + SLOT_A + r * 12288, &tm.wqkv3, fb, qc, it * 64 + r * 32, 0);
            TRL(64 + it);
            if (r && it == 2) {
                const int c = (7 - sub) * 8 + (mt >> 1), c7 = (c * 37) >> 8;
                tma_prefetch3(&tm.xA3, (3 + (sub >> 1)) * 64, (mt - (sub & 1)) * 64);
                if (c7 < 8) tma_prefetch3(&tm.wqkv3, (c - 7 * c7) * 64, 192 + c7 * 32);
            }
            if (it == 1) { prefetch_tmap(tmW); prefetch_tmap(tmB); prefetch_tmap(tmH); }
            advance();
        }
        int kc = (late ? 1024 : 0) + 512 * FLIP;
        #pragma unroll 1
        for (int wi = 0; wi < nj - late; wi++) {
            mbar_wait_p(fb + 32, par);
            if (TP(W_GAP) && wi > 0 && wi < 4) { const uint32_t t1 = clk32() + TP(W_GAP); while ((int)(clk32() - t1) < 0) { } }
            mbar_expect_tx(fb, SLOT_BYTES);
            tma_load(slot, tmW, fb, kc, mt * 128);
            TR(224 + 7 + wi);
            if (wi >= 4) {
                if (wi == 4 || wi == nj / 2) mbar_wait(bar_fl + (wi == 4 ? 16 : 24), 0);
                tma_load5_mc(slot + boff, tmB, fb, kc, bgrp);
                TR(64 + 7 + wi);
            } else mbar_arrive(bar_go + 8 * wi);
            advance();
            kc = next_kc(kc, wi);
            if (wi == (late ? TP(PF_L) : TP(PF_E))) tma_prefetch(tmH, (late ? 29 : 13) * 64, mt * 128 + nh * 64);
            if (late) {
                if (wi == TP(L_XAT) - 1) {
                    mbar_wait(bar_se, 0);
                    mbar_expect_tx(bar_sf, SLOT_BYTES);
                    tma_load5_mc(stg + boff, tmB, bar_sf, 31 * 64, bgrp);
                }
                if (wi == TP(L_XAT)) tma_load(stg, tmW, bar_sf, 31 * 64, mt * 128);
            } else if (wi == TP(WB_AT)) {
                mbar_wait(bar_se, 0);
                #pragma unroll
                for (int j = 0; j < 6; j += 2) tma_load_mc(sb + OUT_B(j) + r * 8192, &tm.wo64, bar_abf, 256 + 48 * (sub & 3), (j + r) * 64);
            } else if (wi == TP(WO_AT) - 1) {
                const int c = mt * 4 + (sub & 3), c7 = (c * 37) >> 8;
                if (c < 49) tma_prefetch(&tm.wo64, (c - 7 * c7) * 64, c7 * 64); else prefetch_tmap(&tm.wo64);
            }
        }
        if (!late) {
            const uint4* const po = g_o + mt * 7168;
            const int ca = 64 * (sub & 3), cb = 256 + 48 * (sub & 3);
            auto load_w = [&](int d0, int c0, int j0, int d1, int c1, int j1, int g) { tma_load_mc(sb + (r ? d1 : d0), &tm.wo64, bar_abf + 8 * g, r ? c1 : c0, (r ? j1 : j0) * 64); };
            auto load_o = [&](int p, int j, int n, int g) { bulk_load(sb + OUT_O(p, j), po + p * 3584 + j * 512, n * 8192, bar_abf + 8 * g); };
            #pragma unroll
            for (int g = 0; g < 6; g++) mbar_expect_tx(bar_abf + 8 * g, (g == 0 ? 11 : g == 1 ? 4 : g == 2 ? 6 : g < 5 ? 3 : 1) * 8192);
            mbar_wait_p(bar_empty + 8, 1);
            load_w(OUT_A(0), ca, 0, OUT_A(1), ca, 1, 0);
            if (r == 0) load_w(OUT_B(6), cb, 6, 0, 0, 0, 0);
            TR(64 + 7 + KB_EARLY);
            mbar_wait_p(bar_fl + 32, 0);
            TR(3);
            load_o(0, 0, 2, 0);
            mbar_wait_p(bar_af, 0);
            load_w(OUT_A(2), ca, 2, OUT_A(3), ca, 3, 1); load_o(0, 2, 2, 1); load_w(OUT_A(4), ca, 4, OUT_A(6), ca, 6, 2);
            TR(64 + 7 + KB_EARLY + 1);
            mbar_wait_p(bar_empty + 16, 1);
            if (r) load_w(0, 0, 0, OUT_A(5), ca, 5, 2);
            load_o(0, 4, 3, 2);
            TR(64 + 7 + KB_EARLY + 2);
            mbar_wait_p(bar_empty + 24, 1);
            load_o(1, 0, 3, 3);
            TR(64 + 7 + KB_EARLY + 3);
            mbar_wait_p(bar_empty, 0);
            load_o(1, 3, 3, 4);
            TR(64 + 7 + KB_EARLY + 4);
            mbar_wait_p(bar_ab6, 0);
            load_o(1, 6, 1, 5);
            TR(64 + 7 + KB_EARLY + 5);
        }
        mbar_arrive(bar_end);
        }
      } else {
        const unsigned epoch = ld_relaxed(&g_epoch[cta * 8]) + 1;
        cluster_wait();
        auto forward = [&](const unsigned* fl, unsigned target, auto first, uint32_t bar, uint32_t again) {
            for (int spin = 0; !__all_sync(0xffffffffu, (int)(ld_acquire(fl) - target) >= 0);) {
                if ((int)(clk32() - again) < 0) { while ((int)(clk32() - again) < 0) { } } else __nanosleep(target != epoch ? TP(OPOLL_NS) : TP(POLL_NS));
                if (++spin > SPIN_LIMIT) give_up();
            }
            if (elect_one()) {
                fence_async_global();
                if constexpr (decltype(first)::value == 2) { if (atomicExch(reinterpret_cast<unsigned*>(smem_raw + BAR_OFF + 144), 1u) == 0) mbar_arrive(bar); }
                else if constexpr (!decltype(first)::value) mbar_arrive(bar);
                else {
                    #pragma unroll
                    for (int i = 0; i < 2; i++) {
                        const int wi = 2 * (warp - 2) + i, sl = (wi + 3) & 3;
                        mbar_wait_limit(bar_go + 8 * wi, 0);
                        tma_load5_mc(sb + sl * SLOT_BYTES + boff, tmB, bar_full + 8 * sl, (late ? 1024 : 0) + 256 * (wi ^ 2 * FLIP), bgrp);
                        TR(64 + 7 + wi);
                        if (i == 0) { const uint32_t t1 = clk32() + TP(BIG_GAP); while ((int)(clk32() - t1) < 0) { } }
                    }
                }
            }
            __syncwarp();
        };
        const int frow = part * 4 + nh * 2 + (lane & 1), st0 = late ? 8 : 0;
        const int ft = late ? min(7 + (lane >> 1), 15) : min(lane >> 1, 6);
        const unsigned* const fl2 = &g_flag_ab[(32 + frow) * 32 + (late ? min(7 + (lane & 14), 15) : min(1 + (lane & 14), 5))];
        const unsigned* const fl3 = &g_flag_ab[(16 + 8 * (ft & 1) + frow) * 32 + ft];
        if (warp == 1) {
            if (elect_one()) {
                prefetch_tmap(&tm.abH); if (BIG_ST) { prefetch_tmap(&tm.ab80); prefetch_tmap(&tm.ab32); }
                const int e0 = pin(sub * 112 - (sub & 2) * 16), e1 = pin((sub & 3) == 2 ? 224 : 0);
                #pragma unroll 1
                for (int hf = 0; hf < 2; hf++) {
                    const int gap = pin(hf ? (r ? TP(ABS_GAP3) : TP(ABS_GAP2)) : (r ? TP(ABS_GAP) : 0)), sc = pin(mt * 128 + hf * 64);
                    const uint32_t src = pin(hf ? stg : sb + 7 * AB_BYTES);
                    unsigned* const fl = pin(&g_flag_ab[((hf ? 2 + r : r ? 4 : URG(mt)) * 8 + sub) * 32 + mt]);
                    mbar_wait(bar_ab + 8 * hf, 0);
                    fence_async_smem();
                    uint32_t t1 = clk32() + (hf ? 0 : r ? TP(ABS_AT) : URG(mt) * TP(ABS_AT1));
                    if (BIG_ST && (hf | r) == 0) {
                        if (URG(mt)) { while ((int)(clk32() - t1) < 0) { } }
                        TR(4);
                        tma_store(&tm.ab80, src + 4096, sc, e0 + 32);
                        tma_store(&tm.ab32, src, sc, e0 + e1);
                    } else
                    #pragma unroll
                    for (int i = 0; i < 7; i++) {
                        if (i == 0 || gap) { while ((int)(clk32() - t1) < 0) { } }
                        t1 += gap;
                        if (i == 0 && hf == 0) TR(4);
                        if (hf > r && i % 3 == 0 && i / 3 < TP(PF_N)) tma_prefetch(part ? &tm.wim : &tm.wre, (late ? 1024 : 0) + ((i / 3) ^ 2 * FLIP) * 256, (mt + nh) * 128);
                        tma_store(&tm.abH, src + i * 2048, sc, e0 + i * 16 + (i < 2 ? e1 : 0));
                    }
                    bulk_commit();
                    bulk_wait_all();
                    if (hf) TR(5);
                    mbar_arrive(bar_free + 8 * hf);
                    st_release(fl, epoch);
                    TR(hf ? 6 : 38);
                }
                uint4* const po = pin(g_o + mt * 7168 + sub * 448);
                mbar_wait(bar_o, 0);
                fence_async_smem();
                TR(9);
                {
                    uint32_t t2 = clk32();
                    #pragma unroll 1
                    for (int i = 0; i < 2 * O_N; i++) {
                        while ((int)(clk32() - t2) < 0) { }
                        t2 += TP(O_GAP);
                        bulk_store(po + (i >= O_N ? 3584 - 448 : 0) + i * (448 / O_N), stg + i * (7168 / O_N), 7168 / O_N);
                    }
                }
                bulk_commit();
                TR(62);
                bulk_wait_all();
                TR(111);
                mbar_arrive(bar_se); mbar_arrive_remote(bar_se, r ^ 1);
                red_release(&g_flag_o[mt * 32], 1);
                TR(17); TRG(102);
                if (!late) {
                    prefetch_tmap(&tm.outA); prefetch_tmap(&tm.outB);
                    #pragma unroll
                    for (int c = 0; c < 2; c++) {
                        mbar_wait(bar_qkv + 8 * c, 1);
                        fence_async_smem();
                        tma_store3(c ? &tm.outB : &tm.outA, sb + OUT_O(0, 1) + c * 8192, mt * 64, sub & 3);
                    }
                    bulk_commit();
                    asm volatile("cp.async.bulk.wait_group.read 0;" ::: "memory");
                    TR(19);
                }
            }
            __syncwarp();
        } else {
            asm volatile("st.shared.u32 [%0], %1;" :: "r"(bars + 168), "r"(epoch) : "memory");
            if (OPOLL2_ON) asm volatile("st.shared.u32 [%0], %1;" :: "r"(bars + 144), "r"(0) : "memory");
            __syncwarp();
            if (lane == 0) mbar_arrive(bar_ab + 8);
            mbar_wait_limit(bar_ab, 0);
            const uint32_t ta = clk32();
            if (tid == 96) TRG(98);
            const bool rest = warp == 3 && __all_sync(0xffffffffu, (int)(ld_acquire(lane >= 22 ? fl2 : fl3) - epoch) >= 0);
            forward(&g_flag_ab[((warp - 2) * 8 + frow) * 32 + st0 + 4 * ((warp - 2) ^ FLIP) + (lane & 2)], epoch, Int<1>(), 0, ta + (warp == 2 ? TP(POLL_AT) : TP(POLL_AT1)));
            if (warp == 2) {
                const uint4* const hp = pin(g_halo + (max(mt - 1, 0) * 8 + sub) * 320 + lane);
                const uint32_t ha = pin(stg + KV_OFF + (lane & 7) * KV_PITCH + (lane >> 3) * 16);
                mbar_wait(mt > 0 ? bar_go + 24 : bar_qkv, 0);
                uint4 v[10];
                if (mt > 0) {
                    const uint32_t tq = clk32();
                    while ((int)(clk32() - tq) < TP(HALO_WAIT)) { }
                    #pragma unroll 1
                    for (;;) {
                        uint32_t bad = 0;
                        #pragma unroll
                        for (int j = 0; j < 10; j++) v[j] = ld_b128_relaxed(hp + j * 32);
                        #pragma unroll
                        for (int j = 0; j < 10; j++) bad |= v[j].w ^ epoch;
                        if (__all_sync(0xffffffffu, bad == 0) || (ABL & 1)) break;
                        __nanosleep(200);
                    }
                } else {
                    const uint32_t r0 = stg + KV_OFF + 8 * KV_PITCH + 112 + (lane & 3) * 4;
                    v[0].x = v[0].y = v[0].z = v[1].x = v[1].y = v[1].z = v[2].x = 0;
                    v[2].y = lds32(r0); v[2].z = lds32(r0 + 16); v[3].x = lds32(r0 + 32); v[3].y = lds32(r0 + 48); v[3].z = lds32(r0 + 64); v[4].x = lds32(r0 + 80); v[4].y = lds32(r0 + 96);
                    #pragma unroll
                    for (int j = 0; j < 5; j++) v[5 + j] = v[j];
                }
                mbar_wait(bar_free, 0);
                #pragma unroll
                for (int p = 0; p < 2; p++) {
                    const uint4* u = v + 5 * p;
                    stsm_x4(ha + p * KV_PAR, u[0].x, u[0].y, u[0].z, u[1].x);
                    stsm_x4(ha + p * KV_PAR + 64, u[1].y, u[1].z, u[2].x, u[2].y);
                    stsm_x4(ha + p * KV_PAR + 128, u[2].z, u[3].x, u[3].y, u[3].z);
                    stsm_x2(ha + p * KV_PAR + 192, u[4].x, u[4].y);
                }
                __syncwarp();
                if (lane == 0) { mbar_arrive(bar_halo); TR(10); TRG(100); }
                if (OPOLL2_ON && !late) {
                    mbar_wait(bar_ab + 8, 0);
                    const uint32_t at = ta + TP(OPOLL_AT) + TP(OPOLL2);
                    while ((int)(clk32() - at) < 0) { }
                    forward(&g_flag_o[mt * 32], epoch * 8, Int<2>(), bar_fl + 32, at);
                }
            } else {
                #pragma unroll 1
                for (int j = 2; j < (late ? 4 : 5); j++) {
                    const unsigned* const fl = j == 2 ? fl2 : j == 4 ? &g_flag_o[mt * 32] : lane < 24 ? fl3 : &g_flag_ab[(16 + 8 * r + (lane & 7)) * 32 + mt];
                    const uint32_t at = ta + (j == 2 ? TP(POLL_AT2) : j == 3 ? TP(POLL_AT3) : TP(OPOLL_AT));
                    if (!rest) { while ((int)(clk32() - at) < 0) { } }
                    if (OPOLL2_ON && j == 4) { mbar_wait(bar_ab + 8, 0); forward(fl, epoch * 8, Int<2>(), bar_fl + 32, at); } else
                    forward(fl, j == 4 ? epoch * 8 : epoch, Int<0>(), bar_fl + 8 * j, at);
                    if (lane == 0) TR(j == 3 ? 39 : j == 4 ? 13 : 35 + j);
                }
                mbar_wait_limit(bar_end, 0);
            }
            __syncwarp();
        }
      }
      TR_END();
    } else {
        if (tid == 128) {
            mbar_init(bar_ab6, 1); mbar_init(bar_ab, 4); mbar_init(bar_ab + 8, 6); mbar_init(bar_free, 1); mbar_init(bar_free + 8, 1); mbar_init(bar_qkv, 4); mbar_init(bar_qkv + 8, 4); mbar_init(bar_o, 8);
            mbar_init(bar_halo, 1); mbar_init(bar_end, 3);
            #pragma unroll
            for (int j = 0; j < 7; j++) mbar_init(bar_go + 8 * j, 1);
            mbar_init(bar_sf, 1); mbar_init(bar_se, 2); mbar_init(bar_af, 4);
            asm volatile("fence.mbarrier_init.release.cluster;" ::: "memory");
        }
        __syncwarp();
        cluster_arrive();
        if (warp >= 8) {
            float d[4];
            #pragma unroll 1
            for (int i = 0; i < TP(WARM_N); i++) {
                const uint32_t t1 = clk32();
                wgmma_fence();
                wgmma_n8<1, 0>(d, desc_k(sb + 7 * AB_BYTES), desc_k(sb + 7 * AB_BYTES), 0);
                wgmma_commit();
                wgmma_wait<0>();
                while ((int)(clk32() - t1) < TP(WARM_GAP)) { }
                __syncwarp();
            }
        }
        cluster_wait();
        const int wg = warp >> 3, w = warp & 3, cw = warp - 4;

        const bool sig_local = (tid & 127) == 0;
        const int i8 = lane & 7, m = lane >> 3;
        const bool sig = (tid & 95) == 0;
        uint32_t rel;
        asm("mapa.shared::cluster.u32 %0, %1, %2;" : "=r"(rel) : "r"(bar_empty), "r"(r ^ (w & 1)));
        auto done = [&](int it) { (void)it; if ((tid & 127) == 64) TRL(160 + it); };
        auto release = [&](int s) { if (sig) asm volatile("mbarrier.arrive.shared::cluster.b64 _, [%0];" :: "r"(rel + 8 * s) : "memory"); };
        const uint32_t dA = desc_k(sb + wg * 8192), dB = desc_k(sb + SLOT_A), dBt = desc_mn(sb + SLOT_A);
        const uint32_t a_frag = sb + wg * 8192 + (w * 16 + (lane & 15)) * 128 + (((lane >> 4) ^ i8) << 4);
        auto wait_full = [&](int it) { mbar_wait(bar_full + 8 * (it & 3), (it >> 2) & 1); if (sig_local) TR(128 + wg * 64 + it); };
        uint32_t kq[4][4], vq[14], qb[2][8];
        {
            float aq[28], ak[28], av[28];
            uint32_t mh0 = 0;
            uint32_t af[2][4][4];
            auto load_af = [&](int it) {
                wait_full(it);
                #pragma unroll
                for (int k = 0; k < 4; k++) ldsm_x4((a_frag ^ (k << 5)) + (it & 3) * SLOT_BYTES, af[it & 1][k][0], af[it & 1][k][1], af[it & 1][k][2], af[it & 1][k][3]);
            };
            uint32_t abw[28], base;
            auto stage_ab = [&](int j0, int j1) {
                #pragma unroll
                for (int j = j0; j < j1; j++) {
                    if (j < 7) stsm_x4_t(base + j * 2048, abw[4 * j], abw[4 * j + 1], abw[4 * j + 2], abw[4 * j + 3]);
                    else { __syncwarp(); if (lane == 0) mbar_arrive(bar_ab + 8 * wg); }
                }
            };
            {
                float bacc[56];
                base = pin((wg ? stg : sb + 7 * AB_BYTES) + (((2 * w + (m & 1)) ^ i8) << 4) + ((m >> 1) * 8 + i8) * 128);
                auto ab_loop = [&](auto sign) {
                auto ab_issue = [&](int kb) {
                    mbar_wait_p(bar_abf + 8 * kb, 0);
                    if (kb == 0 && wg == 1) asm volatile("bar.sync 3, 256;" ::: "memory");
                    if (sig_local) TR(112 + wg * 8 + kb);
                    wgmma_fence();
                    #pragma unroll
                    for (int k = 0; k < 4; k++) wgmma_n112<decltype(sign)::value, 0>(bacc, dA + kb * (AB_BYTES >> 4) + 2 * k, dB + kb * (AB_BYTES >> 4) + 2 * k, (kb | k) != 0);
                    wgmma_commit();
                    if (kb == 0 && wg == 0) asm volatile("bar.arrive 3, 256;" ::: "memory");
                };
                #pragma unroll
                for (int kb = 0; kb < 5; kb++) {
                    ab_issue(kb);
                    if (kb > 0) wgmma_wait<1>();
                    if (kb == 2 || kb == 3) release(kb - 2);
                }
                if (wg == 0) {
                    ab_issue(5);
                    ab_issue(6);
                    asm volatile("bar.arrive 4, 256;" ::: "memory");
                    wgmma_wait<2>();
                    release(2);
                } else {
                    uint32_t xf[8][4];
                    #pragma unroll
                    for (int j = 0; j < 8; j++) {
                        if ((j & 3) == 0) mbar_wait(bar_abf + 8 * (5 + (j >> 2)), 0);
                        ldsm_x4((a_frag ^ ((j & 3) << 5)) + (5 + (j >> 2)) * AB_BYTES, xf[j][0], xf[j][1], xf[j][2], xf[j][3]);
                    }
                    wgmma_wait<0>();
                    release(2);
                    asm volatile("bar.sync 4, 256;" ::: "memory");
                    wgmma_fence();
                    #pragma unroll
                    for (int j = 0; j < 8; j++) {
                        wgmma_rs_n112<0, decltype(sign)::value>(bacc, xf[j], dB + (5 + (j >> 2)) * (AB_BYTES >> 4) + 2 * (j & 3), 1);
                        if ((j & 3) == 3) wgmma_commit();
                    }
                }
                };
                if (sub >> 2) ab_loop(Int<-1>()); else ab_loop(Int<1>());
                wgmma_wait<1>();
                release(3);
                reg_set<REG_CONS>();
                if (wg == 1) load_af(0);
                wgmma_wait<0>();
                if (sig_local) TRX(21 + wg);
                if (AB_ST) { if (wg == 0) asm volatile("bar.arrive 3, 256;" ::: "memory"); else asm volatile("bar.sync 3, 256;" ::: "memory"); }
                #pragma unroll
                for (int j = 0; j < 28; j++) abw[j] = pack_bf16(bacc[2 * j], bacc[2 * j + 1]);
                stage_ab(0, AB_ST);
                if (wg == 0 || AB_ST == 7) stage_ab(AB_ST, 8);
            }
            const uint32_t dQ = dBt + (sub & 1);
            #pragma unroll
            for (int it = 0; it < 7; it++) {
                const uint32_t o = (it & 3) * (SLOT_BYTES >> 4);
                if (it > 0 || wg == 0) load_af(it);
                if (it == 5) mh0 = pin((lane & 3) < 2 ? 0xffffffffu : 0u);
                if (AB_ST < 7 && wg == 1) { if (it == 1) stage_ab(AB_ST, AB_ST2); if (it == 2) stage_ab(AB_ST2, 8); }
                wgmma_wait<0>();
                if (it > 0) { release((it - 1) & 3); done(it - 1); }
                if (it == 0 && sig_local) TRL(60 + wg);
                if (wg == 0) { if (it > 0) asm volatile("bar.sync 6, 256;" ::: "memory"); } else asm volatile("bar.sync 8, 256;" ::: "memory");
                wgmma_fence();
                #pragma unroll
                for (int j = 0; j < 12; j++) {
                    const int k = it < 6 || !KV_FIRST ? j / 3 : j < 8 ? j >> 1 : j - 8, x = it < 6 || !KV_FIRST ? j % 3 : j < 8 ? j & 1 : 2;
                    const uint32_t d = dQ + o + (k >> 1) * 768 + (k & 1) * 128;
                    if (j == Q_ARR) { if (wg == 0) asm volatile("bar.arrive 8, 256;" ::: "memory"); else asm volatile("bar.arrive 6, 256;" ::: "memory"); }
                    if (x == 0) wgmma_rs_n56<1>(ak, af[it & 1][k], d + 256, (it | k) != 0);
                    if (x == 1) wgmma_rs_n56<1>(av, af[it & 1][k], d + 512, (it | k) != 0);
                    if (x == 2) wgmma_rs_n56<1>(aq, af[it & 1][k], d, (it | k) != 0);
                    if (KV_FIRST && it == 6 && j == 7) wgmma_commit();
                }
                wgmma_commit();
            }
            uint4* const hp = pin(g_halo + (mt * 8 + sub) * 320 + wg * 160 + lane);
            mbar_wait(bar_ab + 8, 0);
            const uint32_t epoch = lds32(bars + 168);
            wgmma_wait<KV_FIRST>();
            #pragma unroll
            for (int j = 0; j < 16; j++) kq[j >> 2][j & 3] = pin(pack_bf16(ak[2 * (j - 2 * (j > 7))], ak[1 + 2 * (j - 2 * (j > 7))]));
            #pragma unroll
            for (int j = 0; j < 14; j++) vq[j] = pin(pack_bf16(av[2 * j], av[2 * j + 1]));
            if (w == 3 && !(ABL & 1)) {
                st_b128_relaxed(hp, kq[0][1], kq[0][3], kq[1][1], epoch);
                st_b128_relaxed(hp + 32, kq[1][3], kq[2][3], kq[3][1], epoch);
                st_b128_relaxed(hp + 64, kq[3][3], vq[1], vq[3], epoch);
                st_b128_relaxed(hp + 96, vq[5], vq[7], vq[9], epoch);
                st_b128_relaxed(hp + 128, vq[11], vq[13], 0u, epoch);
                if (lane == 0) TR(8);
            }
            wgmma_wait<0>();
            release(6 & 3);
            if (sig_local) TRX(23 + wg);
            #pragma unroll
            for (int j = 0; j < 14; j++) qb[j & 1][(j >> 1) + (j > 7)] = pin(pack_bf16(aq[2 * j], aq[2 * j + 1]));
            #pragma unroll
            for (int j = 0; j < 2; j++) { qb[j][4] = qb[j][3] & ~mh0; qb[j][3] &= mh0; }
        }
        float acc[112];
        const int it1 = 7 + nj;
        auto big_issue = [&](int slot, bool first) {
            wgmma_fence();
            #pragma unroll
            for (int k = 0; k < 4; k++) wgmma_n224<1, 0>(acc, dA + slot * (SLOT_BYTES >> 4) + 2 * k, dB + slot * (SLOT_BYTES >> 4) + 2 * k, !first || k != 0);
            wgmma_commit();
        };
        if (wg == 1) {
            asm volatile("bar.sync 7, 256;" ::: "memory");
            big_issue(3, true);
        } else {
            wait_full(7);
            asm volatile("bar.sync 6, 256;" ::: "memory");
            big_issue(3, true);
            asm volatile("bar.arrive 7, 256;" ::: "memory");
            if (sig_local) TR(20);
        }
        {
            auto plain = [&](int it) {
                wait_full(it); wgmma_wait<0>(); release((it - 1) & 3); done(it - 1); big_issue(it & 3, false);
                mbar_wait(bar_free, 0);
            };
            auto before_mma = [&](int it, int last) {
                if (wg == last) {
                    mbar_wait_limit(bar_full + 8 * (it & 3), (it >> 2) & 1);
                    if (sig_local) TR(128 + last * 64 + it);
                    asm volatile("bar.sync 2, 256;" ::: "memory");
                    wgmma_wait<0>();
                    release((it - 1) & 3);
                    done(it - 1);
                } else {
                    if (GAP_FLIP) { wgmma_wait<0>(); release((it - 1) & 3); }
                    asm volatile("bar.arrive 2, 256;" ::: "memory");
                }
            };
            auto after_mma = [&](int it, int last) {
                if (wg == (last ^ 1)) {
                    if (!GAP_FLIP) { wgmma_wait<0>(); release((it - 1) & 3); }
                    asm volatile("bar.sync 7, 256;" ::: "memory");
                    big_issue(it & 3, false);
                } else {
                    big_issue(it & 3, false);
                    asm volatile("bar.arrive 7, 256;" ::: "memory");
                }
            };
            const uint32_t kvw = stg + KV_OFF + wg * KV_PAR + (w * 16 + i8) * KV_PITCH;
            const uint32_t a_k = kvw + (m & 1) * 8 * KV_PITCH + (m >> 1) * 16, a_v = kvw + (m >> 1) * 8 * KV_PITCH + 112 + (m & 1) * 16;
            mbar_wait(bar_free, 0);
            #pragma unroll
            for (int u = 0; u < (ABL & 64 ? 0 : 3); u++) stsm_x4(a_k + 8 * KV_PITCH + 112 + u * 32, vq[4 * u], vq[4 * u + 1], vq[4 * u + 2], vq[4 * u + 3]);
            if (!(ABL & 64)) stsm_x2(a_k + 8 * KV_PITCH + 112 + 96, vq[12], vq[13]);
            plain(8);
            #pragma unroll
            for (int u = 0; u < (ABL & 64 ? 1 : 4); u++) stsm_x4(a_k + 8 * KV_PITCH + (2 * u - (u > 1)) * 16, kq[u][0], kq[u][1], kq[u][2], kq[u][3]);
            __syncwarp();
            if (lane == 0) mbar_arrive(bar_qkv + 8 * wg);
            if (sig_local) TR(25 + wg);
            uint32_t kp[4][4], vt[8][4], pb[4][2];
            auto load_v = [&](int n) {
                #pragma unroll
                for (int u = 0; u < 4; u++) {
                    if ((ABL & 64) && u > 0) { vt[2 * u + n][0] = vq[u]; vt[2 * u + n][1] = vq[u + 4]; vt[2 * u + n][2] = vq[u + 8]; vt[2 * u + n][3] = vq[u + n]; } else
                    ldsm_x4_t(a_v + n * 8 * KV_PITCH + (2 * u - (u > 1)) * 16, vt[2 * u + n][0], vt[2 * u + n][1], vt[2 * u + n][2], vt[2 * u + n][3]);
                }
            };
            load_v(1);
            plain(9);
            if (QK_AT > 10) plain(10);
            mbar_wait(w == 0 && !(ABL & 2) ? bar_halo : bar_qkv + 8 * wg, 0);
            #pragma unroll
            for (int u = 0; u < 4; u++) {
                if ((ABL & 64) && u > 0) { kp[u][0] = kq[u][1]; kp[u][1] = kq[u][0]; kp[u][2] = kq[u][3]; kp[u][3] = kq[u][2]; } else
                ldsm_x4(a_k + (2 * u - (u > 1)) * 16, kp[u][0], kp[u][1], kp[u][2], kp[u][3]);
            }
            if (sig_local) TR(54 + wg);
            before_mma(QK_AT, GAP_FLIP);
            float s[4][4];
            #pragma unroll
            for (int i = 0; i < 16; i++) s[i >> 2][i & 3] = 0.f;
            #pragma unroll
            for (int i = 0; i < (ABL & 4 ? 0 : 8); i++) {
                const int n = i & 1, h = (i >> 1) & 1, ks = 2 * h + (i >> 2);
                if (n) mma16816(s[i & 3], kq[ks][0], kq[ks][1], kq[ks][2], kq[ks][3], qb[1][2 * ks], qb[1][2 * ks + 1]);
                else mma16816(s[i & 3], kp[ks][0], kp[ks][1], kp[ks][2], kp[ks][3], qb[0][2 * ks], qb[0][2 * ks + 1]);
            }
            #pragma unroll
            for (int i = 0; i < 16; i++) asm volatile("" : "+f"(s[i >> 2][i & 3]) :: "memory");
            after_mma(QK_AT, GAP_FLIP);
            if (sig_local) TR(48 + wg);
            const int g = lane >> 2, t2 = 2 * (lane & 3);
            const uint32_t mlo = (t2 > g ? 0xffffu : 0u) | (t2 + 1 > g ? 0xffff0000u : 0u), before = (mt | w) == 0 ? mlo : 0u;
            uint32_t y[4], mx[2];
            #pragma unroll
            for (int i = 0; i < 4; i++) {
                const uint32_t x = pack_bf16(g > t2 ? s[i][0] : s[i][2], g > t2 + 1 ? s[i][1] : s[i][3]);
                y[i] = movm_t(pack_bf16(bf_lo(x) * ATT_SCALE, bf_hi(x) * ATT_SCALE));
                if (!(i & 1)) y[i] = (y[i] & ~before) | (MASKED & before);
            }
            #pragma unroll
            for (int h = 0; h < 2; h++) {
                mx[h] = max_bf16x2(__byte_perm(y[2 * h], y[2 * h + 1], 0x5410), __byte_perm(y[2 * h], y[2 * h + 1], 0x7632));
                mx[h] = pin(max_bf16x2(mx[h], __shfl_xor_sync(0xffffffffu, mx[h], 1)));
            }
            load_v(0);
            if (sig_local) TR(50 + wg);
            plain(QK_AT + 1);
            #pragma unroll
            for (int h = 0; h < 2; h++) mx[h] = max_bf16x2(mx[h], __shfl_xor_sync(0xffffffffu, mx[h], 2));
            #pragma unroll
            for (int i = 0; i < 4; i++) {
                const float mi = i & 1 ? bf_hi(mx[i >> 1]) : bf_lo(mx[i >> 1]);
                const float e0 = ex2_approx((bf_lo(y[i]) - mi) * LOG2E), e1 = ex2_approx((bf_hi(y[i]) - mi) * LOG2E);
                float sum = e0 + e1;
                sum += __shfl_xor_sync(0xffffffffu, sum, 1);
                sum += __shfl_xor_sync(0xffffffffu, sum, 2);
                const float inv = rcp_approx(sum);
                const uint32_t p = pack_bf16(e0 * inv, e1 * inv);
                pb[i][0] = pin(p & mlo); pb[i][1] = pin(p & ~mlo);
            }
            if (sig_local) TR(52 + wg);
            before_mma(QK_AT + 2, 0);
            float ao[8][4];
            #pragma unroll
            for (int i = 0; i < 8; i++) {
                ao[i][0] = ao[i][1] = ao[i][2] = ao[i][3] = 0.f;
                if (!(ABL & 4)) mma16816(ao[i], vt[i][0], vt[i][1], vt[i][2], vt[i][3], pb[(i >> 2) * 2 + (i & 1)][0], pb[(i >> 2) * 2 + (i & 1)][1]);
            }
            #pragma unroll
            for (int i = 0; i < 32; i++) asm volatile("" : "+f"(ao[i >> 2][i & 3]) :: "memory");
            after_mma(QK_AT + 2, 0);
            if (sig_local) TRX(11 + wg);
            if (g >= 4) { ao[2][2] = ao[4][0]; ao[2][3] = ao[4][1]; ao[3][2] = ao[5][0]; ao[3][3] = ao[5][1]; }
            mbar_wait(bar_free + 8, 0);
            const uint32_t orow = stg + wg * 7168 + (m >> 1) * 1024 + (w * 16 + (lane & 15)) * 16;
            stsm_x4_t(orow, pack_bf16(ao[0][0], ao[0][1]), pack_bf16(ao[1][0], ao[1][1]), pack_bf16(ao[0][2], ao[0][3]), pack_bf16(ao[1][2], ao[1][3]));
            stsm_x4_t(orow + 2048, pack_bf16(ao[2][0], ao[2][1]), pack_bf16(ao[3][0], ao[3][1]), pack_bf16(ao[2][2], ao[2][3]), pack_bf16(ao[3][2], ao[3][3]));
            stsm_x4_t(orow + 4096, pack_bf16(ao[4][2], ao[4][3]), pack_bf16(ao[5][2], ao[5][3]), pack_bf16(ao[6][0], ao[6][1]), pack_bf16(ao[7][0], ao[7][1]));
            stsm_x2_t(orow + 6144, pack_bf16(ao[6][2], ao[6][3]), pack_bf16(ao[7][2], ao[7][3]));
            __syncwarp();
            if (lane == 0) mbar_arrive(bar_o);
        }
        uint32_t af[12][4];
        #pragma unroll 1
        for (int it = QK_AT + 3; it < it1 - 3; it++) {
            wait_full(it);
            wgmma_wait<0>();
            if (it != 7 + 32 - KB_EARLY - 4) release((it - 1) & 3);
            done(it - 1);
            big_issue(it & 3, false);
            if (L_PRE && it == 7 + 32 - KB_EARLY - 5) {
                mbar_wait(bar_sf, 0);
                #pragma unroll
                for (int k = 0; k < 4; k++) ldsm_x4((a_frag ^ (k << 5)) + NSLOT * SLOT_BYTES, af[k][0], af[k][1], af[k][2], af[k][3]);
            }
        }
        mbar_wait(bar_fl + 24, 0);
        if (tid == 128) atomicAdd(&g_epoch[cta * 8], 1);
        __nv_bfloat16* const yp = pin(out + (size_t)(mt * 128 + cw * 16 + (lane >> 2)) * NOUT + DM + nh * 256 + (lane & 3) * 8);
        const int y6 = 192 - nh * 224;
        #define Y_WORD(A, i, jj) pack_bf16(A[16 * ((i) >> 1) + 4 * (jj) + 2 * ((i) & 1)], A[16 * ((i) >> 1) + 4 * (jj) + 2 * ((i) & 1) + 1])
        #define Y_ADDR(i) (yp + ((i) & 1) * 8 * NOUT + ((i) < 12 ? ((i) >> 1) * 32 : y6))
        const bool odd = lane & 4;
        __nv_bfloat16* const yq = pin(odd ? yp - NOUT + 32 : yp);
        #define Y_PAIR(A, i, B, j, rh, C, PAUSE) do { \
            uint32_t x_[4], y_[4]; \
            _Pragma("unroll") \
            for (int jj = 0; jj < 4; jj++) { \
                const uint32_t u_ = Y_WORD(A, 2 * (i) + (rh), jj), v_ = Y_WORD(B, 2 * (j) + (rh), jj), o_ = __shfl_xor_sync(0xffffffffu, odd ? u_ : v_, 4); \
                x_[jj] = odd ? o_ : u_; y_[jj] = odd ? v_ : o_; \
            } \
            red_add_bf16x8(yq + (rh) * 8 * NOUT + (C), x_[0], x_[1], x_[2], x_[3]); \
            PAUSE; \
            red_add_bf16x8(yq + ((rh) * 8 + 1) * NOUT + (C), y_[0], y_[1], y_[2], y_[3]); \
        } while (0)
        if (late) {
            constexpr int IT = 7 + 32 - KB_EARLY - 3;
            #define L_SLOT(j) ((j) == 0 ? NSLOT : (IT + (j) - 1) & 3)
            auto load_af = [&](int j) {
                if (j == 0) mbar_wait(bar_sf, 0); else wait_full(IT + j - 1);
                #pragma unroll
                for (int k = 0; k < 4; k++) ldsm_x4((a_frag ^ (k << 5)) + L_SLOT(j) * SLOT_BYTES, af[4 * j + k][0], af[4 * j + k][1], af[4 * j + k][2], af[4 * j + k][3]);
            };
            if (!L_PRE) load_af(0);
            load_af(1);
            if (L_UP) load_af(2);
            wgmma_wait<0>();
            done(IT - 1);
            if (!L_UP && wg == 1) load_af(2);
            auto issue = [&](auto& p, auto c0, int j0, int j1, bool first, bool last) {
                constexpr int W = sizeof(p) / 2, C0 = decltype(c0)::value;
                if (wg == 0) { if (!first) asm volatile("bar.sync 9, 256;" ::: "memory"); } else asm volatile("bar.sync 5, 256;" ::: "memory");
                wgmma_fence();
                #pragma unroll
                for (int j = j0; j < j1; j++) {
                    if (!L_UP && first && j == 8) { if (wg == 0) load_af(2); wgmma_fence(); }
                    if (j == j1 - 12 + L_ARR) { if (wg == 0) asm volatile("bar.arrive 5, 256;" ::: "memory"); else if (!last) asm volatile("bar.arrive 9, 256;" ::: "memory"); }
                    const uint32_t d = dB + L_SLOT(j >> 2) * (SLOT_BYTES >> 4) + C0 * 8 + 2 * (j & 3);
                    if constexpr (W == 64) wgmma_rs_n64<0>(p, af[j], d, 1); else wgmma_rs_n32<0>(p, af[j], d, 1);
                }
                wgmma_commit();
            };
            float p0[32], p1[32], p2[32], p3[16];
            #pragma unroll
            for (int i = 0; i < 16; i++) asm volatile("mov.b32 %0, %1;" : "=f"(p3[i]) : "f"(acc[96 + i]));
            #pragma unroll
            for (int i = 0; i < 32; i++) asm volatile("mov.b32 %0, %1;" : "=f"(p2[i]) : "f"(acc[64 + i]));
            #pragma unroll
            for (int i = 0; i < 32; i++) asm volatile("mov.b32 %0, %1;" : "=f"(p1[i]) : "f"(acc[32 + i]));
            #pragma unroll
            for (int i = 0; i < 32; i++) asm volatile("mov.b32 %0, %1;" : "=f"(p0[i]) : "f"(acc[i]));
            issue(p0, Int<0>(), 0, 12, true, false);
            wgmma_wait<0>();
            if (sig_local) TRL(14 + wg);
            Y_PAIR(p0, 0, p0, 1, 0, 0, ); Y_PAIR(p0, 0, p0, 1, 1, 0, );
            issue(p1, Int<64>(), 0, 12, false, false);
            wgmma_wait<0>();
            Y_PAIR(p1, 0, p1, 1, 0, 64, ); Y_PAIR(p1, 0, p1, 1, 1, 64, );
            issue(p2, Int<128>(), 0, 12, false, false);
            wgmma_wait<0>();
            if (L_SPLIT < 2 || wg == 0) Y_PAIR(p2, 0, p2, 1, 0, 128, );
            if (L_SPLIT < 1 || wg == 0) Y_PAIR(p2, 0, p2, 1, 1, 128, );
            issue(p3, Int<192>(), 0, 12, false, true);
            if (sig_local) mbar_arrive(bar_end);
            if (L_SPLIT >= 2 && wg == 1) Y_PAIR(p2, 0, p2, 1, 0, 128, );
            if (L_SPLIT >= 1 && wg == 1) Y_PAIR(p2, 0, p2, 1, 1, 128, );
            wgmma_wait<0>();
            if (sig_local) TRX(27 + wg);
            #pragma unroll
            for (int i = 0; i < 2; i++) red_add_bf16x8(Y_ADDR(12 + i), Y_WORD(p3, i, 0), Y_WORD(p3, i, 1), Y_WORD(p3, i, 2), Y_WORD(p3, i, 3));
            if (sig_local) TR(29 + wg);
        } else {
        constexpr int IT0 = 7 + KB_EARLY;
        auto load_af = [&](int j) {
            wait_full(IT0 - 3 + j);
            #pragma unroll
            for (int k = 0; k < 4; k++) ldsm_x4((a_frag ^ (k << 5)) + ((IT0 - 3 + j) & 3) * SLOT_BYTES, af[4 * j + k][0], af[4 * j + k][1], af[4 * j + k][2], af[4 * j + k][3]);
        };
        wait_full(IT0 - 3);
        wgmma_wait<0>();
        release((IT0 - 4) & 3);
        done(IT0 - 4);
        if (wg == 1) {
            load_af(0); load_af(1); load_af(2);
            asm volatile("bar.sync 5, 256;" ::: "memory");
            release((bar_af - bar_empty) / 8);
            #pragma unroll
            for (int it = IT0 - 3; it < IT0; it++) {
                if (it == IT0 - 1) { wgmma_wait<1>(); release((it - 2) & 3); }
                wgmma_fence();
                #pragma unroll
                for (int k = 0; k < 4; k++) wgmma_rs_n224<0>(acc, af[4 * (it - IT0 + 3) + k], dB + (it & 3) * (SLOT_BYTES >> 4) + 2 * k, 1);
                wgmma_commit();
            }
            asm volatile("bar.arrive 9, 256;" ::: "memory");
            wgmma_wait<1>();
            release((IT0 - 2) & 3);
            wgmma_wait<0>();
            release((IT0 - 1) & 3);
            if (sig_local) { mbar_arrive(bar_end); TRL(28); }
            const uint32_t t1 = clk32() + TP(RED_AT1);
            auto pause = [&](int i) { while ((int)(clk32() - t1) < i * TP(RED_GAP1)) { } };
            #pragma unroll
            for (int i = 0; i < 2; i++) { pause(i); red_add_bf16x8(Y_ADDR(12 + i), Y_WORD(acc, 12 + i, 0), Y_WORD(acc, 12 + i, 1), Y_WORD(acc, 12 + i, 2), Y_WORD(acc, 12 + i, 3)); }
            #pragma unroll
            for (int i = 0; i < 6; i++) { pause(2 + 2 * i); Y_PAIR(acc, i & 6, acc, (i & 6) + 1, i & 1, 32 * (i & 6), pause(3 + 2 * i)); }
            if (sig_local) TRX(30);
        } else {
            float lo[64], hi[48];
            #pragma unroll
            for (int i = 0; i < 48; i++) asm volatile("mov.b32 %0, %1;" : "=f"(hi[i]) : "f"(acc[64 + i]));
            #pragma unroll
            for (int i = 0; i < 64; i++) asm volatile("mov.b32 %0, %1;" : "=f"(lo[i]) : "f"(acc[i]));
            #pragma unroll
            for (int it = IT0 - 3; it < IT0; it++) {
                if (it == IT0 - 1) {
                    #pragma unroll
                    for (int k = 0; k < E_FILL; k++) wgmma_n96<1, 0>(hi, dA + ((IT0 - 3 + (k >> 2)) & 3) * (SLOT_BYTES >> 4) + 2 * (k & 3), dB + ((IT0 - 3 + (k >> 2)) & 3) * (SLOT_BYTES >> 4) + 1024 + 2 * (k & 3), 1);
                }
                if (it > IT0 - 3) wait_full(it);
                wgmma_fence();
                #pragma unroll
                for (int k = 0; k < 4; k++) wgmma_n128<1, 0>(lo, dA + (it & 3) * (SLOT_BYTES >> 4) + 2 * k, dB + (it & 3) * (SLOT_BYTES >> 4) + 2 * k, 1);
            }
            wgmma_commit();
            #define E_RED(i) do { if ((i) < 8) red_add_bf16x8(Y_ADDR(i), Y_WORD(lo, (i) & 7, 0), Y_WORD(lo, (i) & 7, 1), Y_WORD(lo, (i) & 7, 2), Y_WORD(lo, (i) & 7, 3)); \
                                  else red_add_bf16x8(Y_ADDR(i), Y_WORD(hi, (i) & 7, 0), Y_WORD(hi, (i) & 7, 1), Y_WORD(hi, (i) & 7, 2), Y_WORD(hi, (i) & 7, 3)); } while (0)
            #pragma unroll
            for (int j = E_FILL; j < 12; j++) {
                const int it = IT0 - 3 + (j >> 2), k = j & 3;
                if (j == E_FILL + E_SPLIT) {
                    wgmma_commit();
                    wgmma_wait<1>();
                    if (sig_local) TR(14);
                    #pragma unroll
                    for (int i = 0; i < RED_A; i++) E_RED(i);
                    wgmma_fence();
                }
                wgmma_n96<1, 0>(hi, dA + (it & 3) * (SLOT_BYTES >> 4) + 2 * k, dB + (it & 3) * (SLOT_BYTES >> 4) + 1024 + 2 * k, 1);
            }
            wgmma_commit();
            asm volatile("bar.arrive 5, 256;" ::: "memory");
            #pragma unroll
            for (int i = RED_A; i < RED_FAST; i++) E_RED(i);
            wgmma_wait<0>();
            release((bar_af - bar_empty) / 8); release((IT0 - 3) & 3); release((IT0 - 2) & 3); release((IT0 - 1) & 3);
            if (sig_local) TRL(27);
            const uint32_t t1 = clk32();
            #pragma unroll
            for (int i = RED_FAST; i < 14 - E_LATE; i++) {
                while ((int)(clk32() - t1) < (i - RED_FAST) * TP(RED_GAP)) { }
                E_RED(i);
            }
            if (sig_local) TR(29);
            float o0[56], o1[56];
            auto out_issue = [&](float (&oa)[56], int p, int j) {
                wgmma_fence();
                #pragma unroll
                for (int k = 0; k < (ABL & 32 ? 0 : 4); k++) wgmma_n112<1, 1, 8>(oa, dB + (63 << 16) + ((OUT_O(p, j) - SLOT_A) >> 4) + 128 * k, dB + ((((OUT_B(j) - OUT_A(j)) >> 4) - 1) << 16) + ((OUT_A(j) - SLOT_A) >> 4) + 128 * k, (j | k) != 0);
                wgmma_commit();
            };
            const uint32_t wa = pin(sb + w * 2048 + ((m & 1) * 8 + i8) * 128 + (((m >> 1) ^ i8) << 4)), ra = pin(sb + w * 2048 + m * 128 + ((i8 ^ m) << 4));
            auto stage = [&](float (&oa)[56], int buf, int u) {
                stsm_x4((wa ^ ((u & 3) << 5)) + buf + (u >> 2) * 8192, pack_bf16(oa[8 * u], oa[8 * u + 1]), pack_bf16(oa[8 * u + 2], oa[8 * u + 3]),
                        pack_bf16(oa[8 * u + 4], oa[8 * u + 5]), pack_bf16(oa[8 * u + 6], oa[8 * u + 7]));
            };
            __nv_bfloat16* const op = pin(out + (size_t)(mt * 128 + 1 + w * 32 + 2 * m) * NOUT + (sub & 3) * 64 + i8 * 8);
            const int c1 = 256 - (sub & 3) * 16;
            asm volatile("bar.sync 9, 256;" ::: "memory");
            #pragma unroll
            for (int j = 0; j < 7; j++) {
                if (j == 0 || j == 2 || j == 4) { mbar_wait(bar_abf + 4 * j, 1); if (sig_local) TR(128 + IT0 + j); }
                out_issue(o0, 0, j);
                if (j < E_LATE) E_RED(14 - E_LATE + j);
                if (j == 2) { wgmma_wait<2>(); if (sig_local) mbar_arrive(bar_ab6); }
            }
            #undef E_RED
            #pragma unroll
            for (int j = 0; j < 7; j++) {
                if (j % 3 == 0) { mbar_wait(bar_abf + 24 + 8 * (j / 3), 1); if (sig_local) TR(192 + IT0 + j); }
                out_issue(o1, 1, j);
                if (j == 1) { wgmma_wait<2>(); if (sig_local) TR(31); }
                if (j >= 1 && j < 5) {
                    stage(o0, OUT_O(0, 1), 2 * j - 2);
                    if (j < 4) stage(o0, OUT_O(0, 1), 2 * j - 1);
                    if (j == 2 || j == 4) { __syncwarp(); if (lane == 0) mbar_arrive(bar_qkv + 4 * j - 8); }
                }
            }
            if (sig_local) mbar_arrive(bar_end);
            wgmma_wait<0>();
            if (sig_local) TRL(32);
            #pragma unroll
            for (int c = 0; c < 2; c++) {
                #pragma unroll
                for (int u = 4 * c; u < (c ? 7 : 4); u++) stage(o1, 0, u);
                __syncwarp();
                #pragma unroll
                for (int q = 0; q < 4; q++) {
                    uint4 v;
                    asm volatile("ld.shared.v4.u32 {%0, %1, %2, %3}, [%4];" : "=r"(v.x), "=r"(v.y), "=r"(v.z), "=r"(v.w) : "r"((ra ^ ((q & 1) << 6)) + c * 8192 + q * 512) : "memory");
                    if (c == 0 || i8 < 6) *reinterpret_cast<uint4*>(op + q * 8 * NOUT + (c ? c1 : 0)) = v;
                }
            }
        }
        }
        #undef Y_PAIR
        #undef Y_WORD
        #undef Y_ADDR
        if (sig_local) { TRX(33 + wg); if (wg == (late ? 1 : 0)) TRG(104); }
        TR_END();
    }
}

typedef CUresult (*EncodeFn)(CUtensorMap*, CUtensorMapDataType, cuuint32_t, void*, const cuuint64_t*, const cuuint64_t*,
                             const cuuint32_t*, const cuuint32_t*, CUtensorMapInterleave, CUtensorMapSwizzle,
                             CUtensorMapL2promotion, CUtensorMapFloatOOBfill);

void make_map(EncodeFn fn, CUtensorMap* tm, const void* ptr, uint64_t inner, uint64_t outer, uint32_t box_inner, uint32_t box_outer,
              CUtensorMapSwizzle sw = CU_TENSOR_MAP_SWIZZLE_128B, uint64_t clip = 0) {
    cuuint64_t gd[2] = {clip ? clip : inner, outer};
    cuuint64_t gs[1] = {inner * 2};
    cuuint32_t bd[2] = {box_inner, box_outer};
    cuuint32_t es[2] = {1, 1};
    fn(tm, CU_TENSOR_MAP_DATA_TYPE_BFLOAT16, 2, const_cast<void*>(ptr), gd, gs, bd, es, CU_TENSOR_MAP_INTERLEAVE_NONE,
       sw, CU_TENSOR_MAP_L2_PROMOTION_L2_128B, CU_TENSOR_MAP_FLOAT_OOB_FILL_NONE);
}
void make_map3(EncodeFn fn, CUtensorMap* tm, const void* ptr, uint64_t n0, uint64_t n1, uint64_t s1, uint64_t n2, uint64_t s2, uint32_t b1, uint32_t b2) {
    cuuint64_t gd[3] = {n0, n1, n2};
    cuuint64_t gs[2] = {s1 * 2, s2 * 2};
    cuuint32_t bd[3] = {64, b1, b2};
    cuuint32_t es[3] = {1, 1, 1};
    fn(tm, CU_TENSOR_MAP_DATA_TYPE_BFLOAT16, 3, const_cast<void*>(ptr), gd, gs, bd, es, CU_TENSOR_MAP_INTERLEAVE_NONE,
       CU_TENSOR_MAP_SWIZZLE_128B, CU_TENSOR_MAP_L2_PROMOTION_L2_128B, CU_TENSOR_MAP_FLOAT_OOB_FILL_NONE);
}
void make_map_perm(EncodeFn fn, CUtensorMap* tm, void* ptr, uint32_t n) {
    cuuint64_t gd[5] = {SEQ, 2, 4, 4, 28};
    cuuint64_t gs[4] = {SEQ * 2, 8 * SEQ * 2, 2 * SEQ * 2, 32 * SEQ * 2};
    cuuint32_t bd[5] = {64, 2, 4, 4, n};
    cuuint32_t es[5] = {1, 1, 1, 1, 1};
    fn(tm, CU_TENSOR_MAP_DATA_TYPE_BFLOAT16, 5, ptr, gd, gs, bd, es, CU_TENSOR_MAP_INTERLEAVE_NONE,
       CU_TENSOR_MAP_SWIZZLE_128B, CU_TENSOR_MAP_L2_PROMOTION_L2_128B, CU_TENSOR_MAP_FLOAT_OOB_FILL_NONE);
}

}

extern "C" void kernel_launch(void* const* d_in, const int* in_sizes, int n_in, void* d_out, int out_size) {
    (void)in_sizes; (void)n_in; (void)out_size;
    static EncodeFn fn = nullptr;
    static void* p_abT = nullptr;
    if (!fn) {
        void* p = nullptr; cudaDriverEntryPointQueryResult qr;
        cudaGetDriverEntryPoint("cuTensorMapEncodeTiled", &p, cudaEnableDefault, &qr);
        fn = (EncodeFn)p;
        cudaGetSymbolAddress(&p_abT, g_abT);
        cudaFuncSetAttribute(fused_kernel, cudaFuncAttributeMaxDynamicSharedMemorySize, SMEM_BYTES);
    }
    TMaps tm;
    make_map3(fn, &tm.xA3, d_in[0], DM, SEQ / 2, 2 * DM, 2, DM, 64, 2);
    make_map3(fn, &tm.wqkv3, d_in[1], DM, DM, 3 * DM, 3, DM, 32, 3);
    make_map(fn, &tm.wo64, d_in[2], DM, DM, 64, 64);
    make_map3(fn, &tm.outA, d_out, 64, SEQ / 2, 2 * NOUT, 4, 64, 64, 1);
    make_map3(fn, &tm.outB, (const __nv_bfloat16*)d_out + 256, 48, SEQ / 2, 2 * NOUT, 4, 48, 64, 1);
    make_map(fn, &tm.xB, d_in[3], DM, SEQ, 64, 128);
    make_map(fn, &tm.wre, d_in[4], SEQ, SEQ, 64, 128);
    make_map(fn, &tm.wim, d_in[5], SEQ, SEQ, 64, 128);
    make_map(fn, &tm.wreH, d_in[4], SEQ, SEQ, 64, 64);
    make_map(fn, &tm.wimH, d_in[5], SEQ, SEQ, 64, 64);
    make_map(fn, &tm.wdre, d_in[6], DM, DM, 64, 112);
    make_map(fn, &tm.wdim, d_in[7], DM, DM, 64, 112);
    make_map_perm(fn, &tm.abP4, p_abT, 4);
    make_map_perm(fn, &tm.abP3, p_abT, 3);
    make_map(fn, &tm.abH, p_abT, SEQ, 896, 64, 16);
    make_map(fn, &tm.ab32, p_abT, SEQ, 896, 64, 32);
    make_map(fn, &tm.ab80, p_abT, SEQ, 896, 64, 80);
    fused_kernel<<<NCTA, 384, SMEM_BYTES, cudaStreamPerThread>>>((__nv_bfloat16*)d_out,
        tm);
}
```

```cpp
#include <cuda_runtime.h>
#include <cuda_bf16.h>
#include <cuda.h>
#include <stdint.h>

namespace {

constexpr int SEQ = 2048, DM = 448, NOUT = 896;
constexpr int NCTA = 128;
constexpr int SLOT_A = 16384, SLOT_B = 28672, SLOT_BYTES = SLOT_A + SLOT_B, NSLOT = 4;
constexpr int AB_BYTES = SLOT_A + 112 * 128;
constexpr int STG_OFF = NSLOT * SLOT_BYTES;
constexpr int STG_BYTES = 7 * 7168;
constexpr int KV_PITCH = 240;
constexpr int KV_OFF = 2 * 7168, KV_PAR = 72 * KV_PITCH;
#define OUT_A(j) (((j) < 2 ? 44 + 8 * (j) : (j) < 4 ? 116 + 8 * (j) : (j) == 5 ? 124 : 4 * (j) - 16) * 1024)
#define OUT_B(j) (((j) < 6 ? 176 + 8 * (j) : 60) * 1024)
#define OUT_O(p, j) (((p) ? ((j) < 3 ? 148 + 8 * (j) : (j) < 6 ? 8 * (j) - 8 : 68) : 68 + 8 * (j)) * 1024)
constexpr int BAR_OFF = STG_OFF + STG_BYTES;
constexpr int TR_OFF = BAR_OFF + 512;
constexpr int SMEM_BYTES = TR_OFF + 1024;
constexpr int SPIN_LIMIT = 1 << 24;
#define TUNE_LIST(X) \
    X(START_GAP1, 400, 50, 0, 900)   \
    X(START_GAP, 280, 30, 0, 500)   \
    X(PF0_N, 0, 1, 0, 3)   \
    X(PF0_AT, 1800, 200, 0, 3000)   \
    X(WARM_N, 3, 1, 0, 6)   \
    X(WARM_GAP, 150, 50, 50, 500)   \
    X(ZERO_GAP, 100, 50, 0, 300)   \
    X(ZERO_AT, 900, 200, 0, 2400)   \
    X(ABS_AT1, 500, 100, 0, 1000)   \
    X(ABS_AT, 1500, 150, 300, 3000)   \
    X(ABS_GAP, 60, 40, 0, 400)   \
    X(ABS_GAP2, 230, 40, 0, 400)   \
    X(ABS_GAP3, 100, 40, 0, 400)   \
    X(POLL_AT, 3100, 100, 2000, 4000)   \
    X(POLL_AT1, 3600, 150, 2000, 5000)   \
    X(POLL_AT2, 6300, 200, 4000, 8000)   \
    X(POLL_AT3, 9200, 200, 6000, 11000)   \
    X(OPOLL_AT, 15100, 200, 13000, 17500)   \
    X(OPOLL2, 500, 100, -1000, 1500)   \
    X(POLL_NS, 50, 100, 0, 800)   \
    X(OPOLL_NS, 100, 60, 0, 600)   \
    X(BIG_GAP, 250, 100, 0, 1000)   \
    X(W_GAP, 180, 100, 0, 900)   \
    X(HALO_WAIT, 350, 100, 0, 1500)   \
    X(O_GAP, 130, 60, 10, 600)   \
    X(PF_N, 0, 1, 0, 3)   \
    X(PF_E, 6, 1, 4, 13)   \
    X(PF_L, 14, 1, 4, 17)   \
    X(WO_AT, 7, 1, 5, 10)   \
    X(WB_AT, 10, 1, 10, 13)   \
    X(L_XAT, 13, 1, 10, 13)   \
    X(RED_GAP, 185, 30, 0, 300)   \
    X(RED_AT1, 0, 100, 0, 1000)   \
    X(RED_GAP1, 80, 30, 0, 300)   \

#define X(n, d, s, lo, hi) constexpr int n = d;
TUNE_LIST(X)
#undef X
#define TP(n) n
#define L_UP 1
#define ABL 0
#define BIG_ST 1
#define FLIP 1
#define URG(mt) ((((mt) >> 2) & 1) ^ FLIP)
#define AB_ST 7
#define AB_ST2 8
#define GAP_FLIP 1
#define L_PRE 1
#define E_FILL 2
#define KB_EARLY 14
#define O_N 2
#define QK_AT 10
#define WAIT_KIND 1
#define KV_FIRST 1
#define Q_ARR 11
#define E_SPLIT 7
#define RED_A 4
#define RED_FAST 6
#define L_ARR 11
#define PF0_ALL 0
#define OPOLL2_ON 1
#define E_LATE 2
#define L_SPLIT 0
#define ROLE2 1
#define ODD2 0
#define START_N 2
#define REG_CONS 200
#define REG_AUX 104

struct __align__(64) TMaps { CUtensorMap xB, wdre, wdim, wre, wim, abP4, abP3, abH, ab32, ab80, wreH, wimH, wo64, xA3, wqkv3, outA, outB; };

__device__ __nv_bfloat16 g_abT[896 * SEQ];
__device__ uint4 g_o[SEQ * DM / 8];
__device__ uint4 g_halo[16 * 8 * 2 * 160];
__device__ unsigned g_flag_ab[40 * 32];
__device__ unsigned g_flag_o[16 * 32];
__device__ unsigned g_epoch[NCTA * 8];

__device__ __forceinline__ uint32_t smem_u32(const void* p) { return (uint32_t)__cvta_generic_to_shared(p); }
__device__ __forceinline__ uint32_t clk32() { uint32_t c; asm volatile("mov.u32 %0, %%clock;" : "=r"(c) :: "memory"); return c; }
__device__ __forceinline__ void give_up() { asm volatile("st.global.u32 [%0], 0;" :: "l"(0ull) : "memory"); }
__device__ __forceinline__ void mbar_init(uint32_t bar, uint32_t count) { asm volatile("mbarrier.init.shared::cta.b64 [%0], %1;" :: "r"(bar), "r"(count) : "memory"); }
__device__ __forceinline__ void mbar_expect_tx(uint32_t bar, uint32_t bytes) { asm volatile("mbarrier.arrive.expect_tx.shared::cta.b64 _, [%0], %1;" :: "r"(bar), "r"(bytes) : "memory"); }
__device__ __forceinline__ void mbar_arrive(uint32_t bar) { asm volatile("mbarrier.arrive.shared::cta.b64 _, [%0];" :: "r"(bar) : "memory"); }
__device__ __forceinline__ void mbar_arrive_remote(uint32_t bar, uint32_t cta) {
    asm volatile("{\n.reg .b32 ra;\nmapa.shared::cluster.u32 ra, %0, %1;\nmbarrier.arrive.shared::cluster.b64 _, [ra];\n}" :: "r"(bar), "r"(cta) : "memory");
}
__device__ __forceinline__ bool mbar_try_wait(uint32_t bar, uint32_t parity) {
    uint32_t ok;
    asm volatile("{\n.reg .pred p;\nmbarrier.try_wait.parity.shared::cta.b64 p, [%1], %2;\nselp.u32 %0, 1, 0, p;\n}" : "=r"(ok) : "r"(bar), "r"(parity) : "memory");
    return ok;
}
__device__ __forceinline__ bool mbar_test_wait(uint32_t bar, uint32_t parity) {
    uint32_t ok;
    asm volatile("{\n.reg .pred p;\nmbarrier.test_wait.parity.shared::cta.b64 p, [%1], %2;\nselp.u32 %0, 1, 0, p;\n}" : "=r"(ok) : "r"(bar), "r"(parity) : "memory");
    return ok;
}
#define WAIT_OP "pmevent 0;\nmbarrier.try_wait.parity.shared::cta.b64 p, [%0], %1;\n"
__device__ __forceinline__ void mbar_wait(uint32_t bar, uint32_t parity) {
    asm volatile("{\n.reg .pred p;\nWAIT:\n" WAIT_OP "@!p bra WAIT;\n}" :: "r"(bar), "r"(parity) : "memory");
}
__device__ __forceinline__ void mbar_wait_p(uint32_t bar, uint32_t parity) {
    asm volatile("{\n.reg .pred p;\nWAIT:\nmbarrier.try_wait.parity.shared::cta.b64 p, [%0], %1;\n@!p bra WAIT;\n}" :: "r"(bar), "r"(parity) : "memory");
}
__device__ __forceinline__ void mbar_wait_limit(uint32_t bar, uint32_t parity) {
    int it = 0;
    while (!mbar_try_wait(bar, parity)) { if (++it > SPIN_LIMIT) give_up(); }
}
__device__ __forceinline__ void tma_load(uint32_t dst, const CUtensorMap* tm, uint32_t bar, int c0, int c1) {
    asm volatile("cp.async.bulk.tensor.2d.shared::cluster.global.mbarrier::complete_tx::bytes [%0], [%1, {%3, %4}], [%2];"
        :: "r"(dst), "l"(tm), "r"(bar), "r"(c0), "r"(c1) : "memory");
}
__device__ __forceinline__ void tma_load_mc(uint32_t dst, const CUtensorMap* tm, uint32_t bar, int c0, int c1) {
    asm volatile("cp.async.bulk.tensor.2d.shared::cluster.global.mbarrier::complete_tx::bytes.multicast::cluster [%0], [%1, {%3, %4}], [%2], %5;"
        :: "r"(dst), "l"(tm), "r"(bar), "r"(c0), "r"(c1), "h"((uint16_t)3) : "memory");
}
__device__ __forceinline__ void tma_load3(uint32_t dst, const CUtensorMap* tm, uint32_t bar, int c0, int c1) {
    asm volatile("cp.async.bulk.tensor.3d.shared::cluster.global.mbarrier::complete_tx::bytes [%0], [%1, {%3, %4, %5}], [%2];"
        :: "r"(dst), "l"(tm), "r"(bar), "r"(c0), "r"(c1), "r"(0) : "memory");
}
__device__ __forceinline__ void tma_load3_mc(uint32_t dst, const CUtensorMap* tm, uint32_t bar, int c0, int c1, int c2) {
    asm volatile("cp.async.bulk.tensor.3d.shared::cluster.global.mbarrier::complete_tx::bytes.multicast::cluster [%0], [%1, {%3, %4, %6}], [%2], %5;"
        :: "r"(dst), "l"(tm), "r"(bar), "r"(c0), "r"(c1), "h"((uint16_t)3), "r"(c2) : "memory");
}
__device__ __forceinline__ void tma_prefetch(const CUtensorMap* tm, int c0, int c1) {
    asm volatile("cp.async.bulk.prefetch.tensor.2d.L2.global [%0, {%1, %2}];" :: "l"(tm), "r"(c0), "r"(c1) : "memory");
}
__device__ __forceinline__ void tma_prefetch3(const CUtensorMap* tm, int c0, int c1) {
    asm volatile("cp.async.bulk.prefetch.tensor.3d.L2.global [%0, {%1, %2, %3}];" :: "l"(tm), "r"(c0), "r"(c1), "r"(0) : "memory");
}
__device__ __forceinline__ void tma_store(const CUtensorMap* tm, uint32_t src, int c0, int c1) {
    asm volatile("cp.async.bulk.tensor.2d.global.shared::cta.bulk_group [%0, {%2, %3}], [%1];" :: "l"(tm), "r"(src), "r"(c0), "r"(c1) : "memory");
}
__device__ __forceinline__ void tma_store3(const CUtensorMap* tm, uint32_t src, int c1, int c2) {
    asm volatile("cp.async.bulk.tensor.3d.global.shared::cta.bulk_group [%0, {%2, %3, %4}], [%1];" :: "l"(tm), "r"(src), "r"(0), "r"(c1), "r"(c2) : "memory");
}
__device__ __forceinline__ void bulk_load(uint32_t dst, const void* src, uint32_t bytes, uint32_t bar) {
    asm volatile("cp.async.bulk.shared::cluster.global.mbarrier::complete_tx::bytes [%0], [%1], %2, [%3];" :: "r"(dst), "l"(src), "r"(bytes), "r"(bar) : "memory");
}
__device__ __forceinline__ void bulk_store(void* dst, uint32_t src, uint32_t bytes) {
    asm volatile("cp.async.bulk.global.shared::cta.bulk_group [%0], [%1], %2;" :: "l"(dst), "r"(src), "r"(bytes) : "memory");
}
__device__ __forceinline__ void tma_load5_mc(uint32_t dst, const CUtensorMap* tm, uint32_t bar, int c0, int c4) {
    asm volatile("cp.async.bulk.tensor.5d.shared::cluster.global.mbarrier::complete_tx::bytes.multicast::cluster [%0], [%1, {%3, %6, %6, %6, %4}], [%2], %5;"
        :: "r"(dst), "l"(tm), "r"(bar), "r"(c0), "r"(c4), "h"((uint16_t)3), "r"(0) : "memory");
}
__device__ __forceinline__ void red_add_bf16x8(__nv_bfloat16* p, uint32_t w0, uint32_t w1, uint32_t w2, uint32_t w3) {
    asm volatile("red.relaxed.gpu.global.add.noftz.v4.bf16x2 [%0], {%1, %2, %3, %4};" :: "l"(p), "r"(w0), "r"(w1), "r"(w2), "r"(w3) : "memory");
}
__device__ __forceinline__ void prefetch_tmap(const CUtensorMap* tm) { asm volatile("prefetch.tensormap [%0];" :: "l"(tm) : "memory"); }
__device__ __forceinline__ void cluster_arrive() { asm volatile("barrier.cluster.arrive.relaxed.aligned;" ::: "memory"); }
__device__ __forceinline__ void cluster_wait() { asm volatile("barrier.cluster.wait.aligned;" ::: "memory"); }
__device__ __forceinline__ void wgmma_fence() { asm volatile("wgmma.fence.sync.aligned;" ::: "memory"); }
__device__ __forceinline__ void wgmma_commit() { asm volatile("wgmma.commit_group.sync.aligned;" ::: "memory"); }
template<int N> __device__ __forceinline__ void wgmma_wait() { asm volatile("wgmma.wait_group.sync.aligned %0;" :: "n"(N) : "memory"); }
__device__ __forceinline__ void fence_async_smem() { asm volatile("fence.proxy.async.shared::cta;" ::: "memory"); }
__device__ __forceinline__ void fence_async_global() { asm volatile("fence.proxy.async.global;" ::: "memory"); }
__device__ __forceinline__ uint32_t desc_k(uint32_t addr) { return ((addr & 0x3FFFF) >> 4) | (1u << 16); }
__device__ __forceinline__ uint32_t desc_mn(uint32_t addr) { return ((addr & 0x3FFFF) >> 4) | ((8192u >> 4) << 16); }
template<int R> __device__ __forceinline__ void reg_set() {
    if (R > 168) asm volatile("setmaxnreg.inc.sync.aligned.u32 %0;" :: "n"(R));
    if (R < 168) asm volatile("setmaxnreg.dec.sync.aligned.u32 %0;" :: "n"(R));
}
__device__ __forceinline__ unsigned ld_acquire(const unsigned* p) { unsigned v; asm volatile("ld.acquire.gpu.global.u32 %0, [%1];" : "=r"(v) : "l"(p) : "memory"); return v; }
__device__ __forceinline__ unsigned ld_relaxed(const unsigned* p) { unsigned v; asm volatile("ld.relaxed.gpu.global.u32 %0, [%1];" : "=r"(v) : "l"(p) : "memory"); return v; }
__device__ __forceinline__ void st_release(unsigned* p, unsigned v) { asm volatile("fence.proxy.async.global;\nst.release.gpu.global.u32 [%0], %1;" :: "l"(p), "r"(v) : "memory"); }
__device__ __forceinline__ void red_release(unsigned* p, unsigned v) { asm volatile("fence.proxy.async.global;\nred.release.gpu.global.add.u32 [%0], %1;" :: "l"(p), "r"(v) : "memory"); }
__device__ __forceinline__ bool elect_one() {
    uint32_t pred;
    asm volatile("{\n.reg .pred p;\nelect.sync _|p, 0xffffffff;\nselp.u32 %0, 1, 0, p;\n}" : "=r"(pred));
    return pred;
}
__device__ __forceinline__ int pick3(int cta, int a, int b, int c) {
    int v;
    asm("{\n.reg .pred p, q;\nsetp.lt.s32 p, %1, 8;\nsetp.lt.s32 q, %1, 72;\nselp.b32 %0, %3, %4, q;\nselp.b32 %0, %2, %0, p;\n}" : "=&r"(v) : "r"(cta), "r"(a), "r"(b), "r"(c));
    return v;
}
template<typename T> __device__ __forceinline__ T pin(T v) {
    if constexpr (sizeof(T) == 8) asm volatile("" : "+l"(v) :: "memory"); else asm volatile("" : "+r"(v) :: "memory");
    return v;
}
__device__ __forceinline__ void bulk_commit() { asm volatile("cp.async.bulk.commit_group;" ::: "memory"); }
__device__ __forceinline__ void bulk_wait_all() { asm volatile("cp.async.bulk.wait_group 0;" ::: "memory"); }
__device__ __forceinline__ uint32_t pack_bf16(float lo, float hi) { uint32_t r; asm("cvt.rn.bf16x2.f32 %0, %1, %2;" : "=r"(r) : "f"(hi), "f"(lo)); return r; }
__device__ __forceinline__ float bf_lo(uint32_t w) { return __uint_as_float(w << 16); }
__device__ __forceinline__ float bf_hi(uint32_t w) { return __uint_as_float(w & 0xffff0000u); }
__device__ __forceinline__ void stsm_x4(uint32_t addr, uint32_t r0, uint32_t r1, uint32_t r2, uint32_t r3) {
    asm volatile("stmatrix.sync.aligned.m8n8.x4.shared.b16 [%0], {%1, %2, %3, %4};" :: "r"(addr), "r"(r0), "r"(r1), "r"(r2), "r"(r3) : "memory");
}
__device__ __forceinline__ void stsm_x2(uint32_t addr, uint32_t r0, uint32_t r1) {
    asm volatile("stmatrix.sync.aligned.m8n8.x2.shared.b16 [%0], {%1, %2};" :: "r"(addr), "r"(r0), "r"(r1) : "memory");
}
__device__ __forceinline__ void stsm_x4_t(uint32_t addr, uint32_t r0, uint32_t r1, uint32_t r2, uint32_t r3) {
    asm volatile("stmatrix.sync.aligned.m8n8.x4.trans.shared.b16 [%0], {%1, %2, %3, %4};" :: "r"(addr), "r"(r0), "r"(r1), "r"(r2), "r"(r3) : "memory");
}
__device__ __forceinline__ void stsm_x2_t(uint32_t addr, uint32_t r0, uint32_t r1) {
    asm volatile("stmatrix.sync.aligned.m8n8.x2.trans.shared.b16 [%0], {%1, %2};" :: "r"(addr), "r"(r0), "r"(r1) : "memory");
}
__device__ __forceinline__ uint32_t movm_t(uint32_t x) { uint32_t r; asm volatile("movmatrix.sync.aligned.m8n8.trans.b16 %0, %1;" : "=r"(r) : "r"(x)); return r; }
__device__ __forceinline__ void ldsm_x4(uint32_t addr, uint32_t& r0, uint32_t& r1, uint32_t& r2, uint32_t& r3) {
    asm volatile("ldmatrix.sync.aligned.m8n8.x4.shared.b16 {%0, %1, %2, %3}, [%4];" : "=r"(r0), "=r"(r1), "=r"(r2), "=r"(r3) : "r"(addr) : "memory");
}
__device__ __forceinline__ void ldsm_x4_t(uint32_t addr, uint32_t& r0, uint32_t& r1, uint32_t& r2, uint32_t& r3) {
    asm volatile("ldmatrix.sync.aligned.m8n8.x4.trans.shared.b16 {%0, %1, %2, %3}, [%4];" : "=r"(r0), "=r"(r1), "=r"(r2), "=r"(r3) : "r"(addr) : "memory");
}
__device__ __forceinline__ void mma16816(float (&d)[4], uint32_t a0, uint32_t a1, uint32_t a2, uint32_t a3, uint32_t b0, uint32_t b1) {
    asm("mma.sync.aligned.m16n8k16.row.col.f32.bf16.bf16.f32 {%0, %1, %2, %3}, {%4, %5, %6, %7}, {%8, %9}, {%0, %1, %2, %3};"
        : "+f"(d[0]), "+f"(d[1]), "+f"(d[2]), "+f"(d[3]) : "r"(a0), "r"(a1), "r"(a2), "r"(a3), "r"(b0), "r"(b1));
}
__device__ __forceinline__ void mma1688(float (&d)[4], uint32_t a0, uint32_t a1, uint32_t b0) {
    asm("mma.sync.aligned.m16n8k8.row.col.f32.bf16.bf16.f32 {%0, %1, %2, %3}, {%4, %5}, {%6}, {%0, %1, %2, %3};"
        : "+f"(d[0]), "+f"(d[1]), "+f"(d[2]), "+f"(d[3]) : "r"(a0), "r"(a1), "r"(b0));
}
__device__ __forceinline__ uint32_t max_bf16x2(uint32_t a, uint32_t b) { uint32_t r; asm("max.bf16x2 %0, %1, %2;" : "=r"(r) : "r"(a), "r"(b)); return r; }
__device__ __forceinline__ float bf16_round(float x) { return __bfloat162float(__float2bfloat16_rn(x)); }
__device__ __forceinline__ uint32_t lds32(uint32_t addr) { uint32_t v; asm volatile("ld.shared.u32 %0, [%1];" : "=r"(v) : "r"(addr)); return v; }
__device__ __forceinline__ float ex2_approx(float x) { float y; asm("ex2.approx.ftz.f32 %0, %1;" : "=f"(y) : "f"(x)); return y; }
__device__ __forceinline__ float rcp_approx(float x) { float y; asm("rcp.approx.ftz.f32 %0, %1;" : "=f"(y) : "f"(x)); return y; }
__device__ __forceinline__ void st_b128_relaxed(uint4* p, uint32_t w0, uint32_t w1, uint32_t w2, uint32_t w3) {
    asm volatile("{\n.reg .b128 t;\n.reg .b64 lo, hi;\nmov.b64 lo, {%1, %2};\nmov.b64 hi, {%3, %4};\nmov.b128 t, {lo, hi};\nst.relaxed.gpu.global.b128 [%0], t;\n}"
        :: "l"(p), "r"(w0), "r"(w1), "r"(w2), "r"(w3) : "memory");
}
__device__ __forceinline__ uint4 ld_b128_relaxed(const uint4* p) {
    uint4 v;
    asm volatile("{\n.reg .b128 t;\n.reg .b64 lo, hi;\nld.relaxed.gpu.global.b128 t, [%4];\nmov.b128 {lo, hi}, t;\nmov.b64 {%0, %1}, lo;\nmov.b64 {%2, %3}, hi;\n}"
        : "=r"(v.x), "=r"(v.y), "=r"(v.z), "=r"(v.w) : "l"(p) : "memory");
    return v;
}

template<int SA, int TB, int HA = 0x40000040, int M>
__device__ __forceinline__ void wgmma_n8(float (&d)[M], uint32_t da, uint32_t db, int scale_d) {
    asm volatile("{\n.reg .pred p;\n.reg .b32 hi, ha;\n.reg .b64 da, db;\nmov.b32 hi, 0x40000040;\nmov.b32 ha, %9;\nmov.b64 da, {%4, ha};\nmov.b64 db, {%5, hi};\nsetp.ne.b32 p, %6, 0;\n"
        "wgmma.mma_async.sync.aligned.m64n8k16.f32.bf16.bf16 "
        "{%0, %1, %2, %3}, "
        "da, db, p, %8, 1, 0, %7;\n}\n"
        : "+f"(d[0]), "+f"(d[1]), "+f"(d[2]), "+f"(d[3])
        : "r"(da), "r"(db), "r"(scale_d), "n"(TB), "n"(SA), "n"(HA));
}
template<int SA, int TB, int HA = 0x40000040, int M>
__device__ __forceinline__ void wgmma_n96(float (&d)[M], uint32_t da, uint32_t db, int scale_d) {
    asm volatile("{\n.reg .pred p;\n.reg .b32 hi, ha;\n.reg .b64 da, db;\nmov.b32 hi, 0x40000040;\nmov.b32 ha, %53;\nmov.b64 da, {%48, ha};\nmov.b64 db, {%49, hi};\nsetp.ne.b32 p, %50, 0;\n"
        "wgmma.mma_async.sync.aligned.m64n96k16.f32.bf16.bf16 "
        "{%0, %1, %2, %3, %4, %5, %6, %7, %8, %9, %10, %11, %12, %13, %14, %15, "
        "%16, %17, %18, %19, %20, %21, %22, %23, %24, %25, %26, %27, %28, %29, %30, %31, "
        "%32, %33, %34, %35, %36, %37, %38, %39, %40, %41, %42, %43, %44, %45, %46, %47}, "
        "da, db, p, %52, 1, 0, %51;\n}\n"
        : "+f"(d[0]), "+f"(d[1]), "+f"(d[2]), "+f"(d[3]), "+f"(d[4]), "+f"(d[5]), "+f"(d[6]), "+f"(d[7]),
          "+f"(d[8]), "+f"(d[9]), "+f"(d[10]), "+f"(d[11]), "+f"(d[12]), "+f"(d[13]), "+f"(d[14]), "+f"(d[15]),
          "+f"(d[16]), "+f"(d[17]), "+f"(d[18]), "+f"(d[19]), "+f"(d[20]), "+f"(d[21]), "+f"(d[22]), "+f"(d[23]),
          "+f"(d[24]), "+f"(d[25]), "+f"(d[26]), "+f"(d[27]), "+f"(d[28]), "+f"(d[29]), "+f"(d[30]), "+f"(d[31]),
          "+f"(d[32]), "+f"(d[33]), "+f"(d[34]), "+f"(d[35]), "+f"(d[36]), "+f"(d[37]), "+f"(d[38]), "+f"(d[39]),
          "+f"(d[40]), "+f"(d[41]), "+f"(d[42]), "+f"(d[43]), "+f"(d[44]), "+f"(d[45]), "+f"(d[46]), "+f"(d[47])
        : "r"(da), "r"(db), "r"(scale_d), "n"(TB), "n"(SA), "n"(HA));
}
template<int SA, int TB, int HA = 0x40000040, int M>
__device__ __forceinline__ void wgmma_n112(float (&d)[M], uint32_t da, uint32_t db, int scale_d) {
    asm volatile("{\n.reg .pred p;\n.reg .b32 hi, ha;\n.reg .b64 da, db;\nmov.b32 hi, 0x40000040;\nmov.b32 ha, %61;\nmov.b64 da, {%56, ha};\nmov.b64 db, {%57, hi};\nsetp.ne.b32 p, %58, 0;\n"
        "wgmma.mma_async.sync.aligned.m64n112k16.f32.bf16.bf16 "
        "{%0, %1, %2, %3, %4, %5, %6, %7, %8, %9, %10, %11, %12, %13, %14, %15, "
        "%16, %17, %18, %19, %20, %21, %22, %23, %24, %25, %26, %27, %28, %29, %30, %31, "
        "%32, %33, %34, %35, %36, %37, %38, %39, %40, %41, %42, %43, %44, %45, %46, %47, "
        "%48, %49, %50, %51, %52, %53, %54, %55}, "
        "da, db, p, %60, 1, 0, %59;\n}\n"
        : "+f"(d[0]), "+f"(d[1]), "+f"(d[2]), "+f"(d[3]), "+f"(d[4]), "+f"(d[5]), "+f"(d[6]), "+f"(d[7]),
          "+f"(d[8]), "+f"(d[9]), "+f"(d[10]), "+f"(d[11]), "+f"(d[12]), "+f"(d[13]), "+f"(d[14]), "+f"(d[15]),
          "+f"(d[16]), "+f"(d[17]), "+f"(d[18]), "+f"(d[19]), "+f"(d[20]), "+f"(d[21]), "+f"(d[22]), "+f"(d[23]),
          "+f"(d[24]), "+f"(d[25]), "+f"(d[26]), "+f"(d[27]), "+f"(d[28]), "+f"(d[29]), "+f"(d[30]), "+f"(d[31]),
          "+f"(d[32]), "+f"(d[33]), "+f"(d[34]), "+f"(d[35]), "+f"(d[36]), "+f"(d[37]), "+f"(d[38]), "+f"(d[39]),
          "+f"(d[40]), "+f"(d[41]), "+f"(d[42]), "+f"(d[43]), "+f"(d[44]), "+f"(d[45]), "+f"(d[46]), "+f"(d[47]),
          "+f"(d[48]), "+f"(d[49]), "+f"(d[50]), "+f"(d[51]), "+f"(d[52]), "+f"(d[53]), "+f"(d[54]), "+f"(d[55])
        : "r"(da), "r"(db), "r"(scale_d), "n"(TB), "n"(SA), "n"(HA));
}
template<int SA, int TB, int HA = 0x40000040, int M>
__device__ __forceinline__ void wgmma_n128(float (&d)[M], uint32_t da, uint32_t db, int scale_d) {
    asm volatile("{\n.reg .pred p;\n.reg .b32 hi, ha;\n.reg .b64 da, db;\nmov.b32 hi, 0x40000040;\nmov.b32 ha, %69;\nmov.b64 da, {%64, ha};\nmov.b64 db, {%65, hi};\nsetp.ne.b32 p, %66, 0;\n"
        "wgmma.mma_async.sync.aligned.m64n128k16.f32.bf16.bf16 "
        "{%0, %1, %2, %3, %4, %5, %6, %7, %8, %9, %10, %11, %12, %13, %14, %15, "
        "%16, %17, %18, %19, %20, %21, %22, %23, %24, %25, %26, %27, %28, %29, %30, %31, "
        "%32, %33, %34, %35, %36, %37, %38, %39, %40, %41, %42, %43, %44, %45, %46, %47, "
        "%48, %49, %50, %51, %52, %53, %54, %55, %56, %57, %58, %59, %60, %61, %62, %63}, "
        "da, db, p, %68, 1, 0, %67;\n}\n"
        : "+f"(d[0]), "+f"(d[1]), "+f"(d[2]), "+f"(d[3]), "+f"(d[4]), "+f"(d[5]), "+f"(d[6]), "+f"(d[7]),
          "+f"(d[8]), "+f"(d[9]), "+f"(d[10]), "+f"(d[11]), "+f"(d[12]), "+f"(d[13]), "+f"(d[14]), "+f"(d[15]),
          "+f"(d[16]), "+f"(d[17]), "+f"(d[18]), "+f"(d[19]), "+f"(d[20]), "+f"(d[21]), "+f"(d[22]), "+f"(d[23]),
          "+f"(d[24]), "+f"(d[25]), "+f"(d[26]), "+f"(d[27]), "+f"(d[28]), "+f"(d[29]), "+f"(d[30]), "+f"(d[31]),
          "+f"(d[32]), "+f"(d[33]), "+f"(d[34]), "+f"(d[35]), "+f"(d[36]), "+f"(d[37]), "+f"(d[38]), "+f"(d[39]),
          "+f"(d[40]), "+f"(d[41]), "+f"(d[42]), "+f"(d[43]), "+f"(d[44]), "+f"(d[45]), "+f"(d[46]), "+f"(d[47]),
          "+f"(d[48]), "+f"(d[49]), "+f"(d[50]), "+f"(d[51]), "+f"(d[52]), "+f"(d[53]), "+f"(d[54]), "+f"(d[55]),
          "+f"(d[56]), "+f"(d[57]), "+f"(d[58]), "+f"(d[59]), "+f"(d[60]), "+f"(d[61]), "+f"(d[62]), "+f"(d[63])
        : "r"(da), "r"(db), "r"(scale_d), "n"(TB), "n"(SA), "n"(HA));
}
template<int SA, int TB, int HA = 0x40000040, int M>
__device__ __forceinline__ void wgmma_n224(float (&d)[M], uint32_t da, uint32_t db, int scale_d) {
    asm volatile("{\n.reg .pred p;\n.reg .b32 hi, ha;\n.reg .b64 da, db;\nmov.b32 hi, 0x40000040;\nmov.b32 ha, %117;\nmov.b64 da, {%112, ha};\nmov.b64 db, {%113, hi};\nsetp.ne.b32 p, %114, 0;\n"
        "wgmma.mma_async.sync.aligned.m64n224k16.f32.bf16.bf16 "
        "{%0, %1, %2, %3, %4, %5, %6, %7, %8, %9, %10, %11, %12, %13, %14, %15, "
        "%16, %17, %18, %19, %20, %21, %22, %23, %24, %25, %26, %27, %28, %29, %30, %31, "
        "%32, %33, %34, %35, %36, %37, %38, %39, %40, %41, %42, %43, %44, %45, %46, %47, "
        "%48, %49, %50, %51, %52, %53, %54, %55, %56, %57, %58, %59, %60, %61, %62, %63, "
        "%64, %65, %66, %67, %68, %69, %70, %71, %72, %73, %74, %75, %76, %77, %78, %79, "
        "%80, %81, %82, %83, %84, %85, %86, %87, %88, %89, %90, %91, %92, %93, %94, %95, "
        "%96, %97, %98, %99, %100, %101, %102, %103, %104, %105, %106, %107, %108, %109, %110, %111}, "
        "da, db, p, %116, 1, 0, %115;\n}\n"
        : "+f"(d[0]), "+f"(d[1]), "+f"(d[2]), "+f"(d[3]), "+f"(d[4]), "+f"(d[5]), "+f"(d[6]), "+f"(d[7]),
          "+f"(d[8]), "+f"(d[9]), "+f"(d[10]), "+f"(d[11]), "+f"(d[12]), "+f"(d[13]), "+f"(d[14]), "+f"(d[15]),
          "+f"(d[16]), "+f"(d[17]), "+f"(d[18]), "+f"(d[19]), "+f"(d[20]), "+f"(d[21]), "+f"(d[22]), "+f"(d[23]),
          "+f"(d[24]), "+f"(d[25]), "+f"(d[26]), "+f"(d[27]), "+f"(d[28]), "+f"(d[29]), "+f"(d[30]), "+f"(d[31]),
          "+f"(d[32]), "+f"(d[33]), "+f"(d[34]), "+f"(d[35]), "+f"(d[36]), "+f"(d[37]), "+f"(d[38]), "+f"(d[39]),
          "+f"(d[40]), "+f"(d[41]), "+f"(d[42]), "+f"(d[43]), "+f"(d[44]), "+f"(d[45]), "+f"(d[46]), "+f"(d[47]),
          "+f"(d[48]), "+f"(d[49]), "+f"(d[50]), "+f"(d[51]), "+f"(d[52]), "+f"(d[53]), "+f"(d[54]), "+f"(d[55]),
          "+f"(d[56]), "+f"(d[57]), "+f"(d[58]), "+f"(d[59]), "+f"(d[60]), "+f"(d[61]), "+f"(d[62]), "+f"(d[63]),
          "+f"(d[64]), "+f"(d[65]), "+f"(d[66]), "+f"(d[67]), "+f"(d[68]), "+f"(d[69]), "+f"(d[70]), "+f"(d[71]),
          "+f"(d[72]), "+f"(d[73]), "+f"(d[74]), "+f"(d[75]), "+f"(d[76]), "+f"(d[77]), "+f"(d[78]), "+f"(d[79]),
          "+f"(d[80]), "+f"(d[81]), "+f"(d[82]), "+f"(d[83]), "+f"(d[84]), "+f"(d[85]), "+f"(d[86]), "+f"(d[87]),
          "+f"(d[88]), "+f"(d[89]), "+f"(d[90]), "+f"(d[91]), "+f"(d[92]), "+f"(d[93]), "+f"(d[94]), "+f"(d[95]),
          "+f"(d[96]), "+f"(d[97]), "+f"(d[98]), "+f"(d[99]), "+f"(d[100]), "+f"(d[101]), "+f"(d[102]), "+f"(d[103]),
          "+f"(d[104]), "+f"(d[105]), "+f"(d[106]), "+f"(d[107]), "+f"(d[108]), "+f"(d[109]), "+f"(d[110]), "+f"(d[111])
        : "r"(da), "r"(db), "r"(scale_d), "n"(TB), "n"(SA), "n"(HA));
}
template<int TB, int SA = 1>
__device__ __forceinline__ void wgmma_rs_n32(float (&d)[16], const uint32_t (&a)[4], uint32_t db, int scale_d) {
    asm volatile("{\n.reg .pred p;\n.reg .b32 hi;\n.reg .b64 db;\nmov.b32 hi, 0x40000040;\nmov.b64 db, {%20, hi};\nsetp.ne.b32 p, %21, 0;\n"
        "wgmma.mma_async.sync.aligned.m64n32k16.f32.bf16.bf16 "
        "{%0, %1, %2, %3, %4, %5, %6, %7, %8, %9, %10, %11, %12, %13, %14, %15}, "
        "{%16, %17, %18, %19}, db, p, %23, 1, %22;\n}\n"
        : "+f"(d[0]), "+f"(d[1]), "+f"(d[2]), "+f"(d[3]), "+f"(d[4]), "+f"(d[5]), "+f"(d[6]), "+f"(d[7]),
          "+f"(d[8]), "+f"(d[9]), "+f"(d[10]), "+f"(d[11]), "+f"(d[12]), "+f"(d[13]), "+f"(d[14]), "+f"(d[15])
        : "r"(a[0]), "r"(a[1]), "r"(a[2]), "r"(a[3]), "r"(db), "r"(scale_d), "n"(TB), "n"(SA));
}
template<int TB, int SA = 1>
__device__ __forceinline__ void wgmma_rs_n56(float (&d)[28], const uint32_t (&a)[4], uint32_t db, int scale_d) {
    asm volatile("{\n.reg .pred p;\n.reg .b32 hi;\n.reg .b64 db;\nmov.b32 hi, 0x40000040;\nmov.b64 db, {%32, hi};\nsetp.ne.b32 p, %33, 0;\n"
        "wgmma.mma_async.sync.aligned.m64n56k16.f32.bf16.bf16 "
        "{%0, %1, %2, %3, %4, %5, %6, %7, %8, %9, %10, %11, %12, %13, %14, %15, "
        "%16, %17, %18, %19, %20, %21, %22, %23, %24, %25, %26, %27}, "
        "{%28, %29, %30, %31}, db, p, %35, 1, %34;\n}\n"
        : "+f"(d[0]), "+f"(d[1]), "+f"(d[2]), "+f"(d[3]), "+f"(d[4]), "+f"(d[5]), "+f"(d[6]), "+f"(d[7]),
          "+f"(d[8]), "+f"(d[9]), "+f"(d[10]), "+f"(d[11]), "+f"(d[12]), "+f"(d[13]), "+f"(d[14]), "+f"(d[15]),
          "+f"(d[16]), "+f"(d[17]), "+f"(d[18]), "+f"(d[19]), "+f"(d[20]), "+f"(d[21]), "+f"(d[22]), "+f"(d[23]),
          "+f"(d[24]), "+f"(d[25]), "+f"(d[26]), "+f"(d[27])
        : "r"(a[0]), "r"(a[1]), "r"(a[2]), "r"(a[3]), "r"(db), "r"(scale_d), "n"(TB), "n"(SA));
}
template<int TB, int SA = 1>
__device__ __forceinline__ void wgmma_rs_n64(float (&d)[32], const uint32_t (&a)[4], uint32_t db, int scale_d) {
    asm volatile("{\n.reg .pred p;\n.reg .b32 hi;\n.reg .b64 db;\nmov.b32 hi, 0x40000040;\nmov.b64 db, {%36, hi};\nsetp.ne.b32 p, %37, 0;\n"
        "wgmma.mma_async.sync.aligned.m64n64k16.f32.bf16.bf16 "
        "{%0, %1, %2, %3, %4, %5, %6, %7, %8, %9, %10, %11, %12, %13, %14, %15, "
        "%16, %17, %18, %19, %20, %21, %22, %23, %24, %25, %26, %27, %28, %29, %30, %31}, "
        "{%32, %33, %34, %35}, db, p, %39, 1, %38;\n}\n"
        : "+f"(d[0]), "+f"(d[1]), "+f"(d[2]), "+f"(d[3]), "+f"(d[4]), "+f"(d[5]), "+f"(d[6]), "+f"(d[7]),
          "+f"(d[8]), "+f"(d[9]), "+f"(d[10]), "+f"(d[11]), "+f"(d[12]), "+f"(d[13]), "+f"(d[14]), "+f"(d[15]),
          "+f"(d[16]), "+f"(d[17]), "+f"(d[18]), "+f"(d[19]), "+f"(d[20]), "+f"(d[21]), "+f"(d[22]), "+f"(d[23]),
          "+f"(d[24]), "+f"(d[25]), "+f"(d[26]), "+f"(d[27]), "+f"(d[28]), "+f"(d[29]), "+f"(d[30]), "+f"(d[31])
        : "r"(a[0]), "r"(a[1]), "r"(a[2]), "r"(a[3]), "r"(db), "r"(scale_d), "n"(TB), "n"(SA));
}
template<int TB, int SA = 1>
__device__ __forceinline__ void wgmma_rs_n112(float (&d)[56], const uint32_t (&a)[4], uint32_t db, int scale_d) {
    asm volatile("{\n.reg .pred p;\n.reg .b32 hi;\n.reg .b64 db;\nmov.b32 hi, 0x40000040;\nmov.b64 db, {%60, hi};\nsetp.ne.b32 p, %61, 0;\n"
        "wgmma.mma_async.sync.aligned.m64n112k16.f32.bf16.bf16 "
        "{%0, %1, %2, %3, %4, %5, %6, %7, %8, %9, %10, %11, %12, %13, %14, %15, "
        "%16, %17, %18, %19, %20, %21, %22, %23, %24, %25, %26, %27, %28, %29, %30, %31, "
        "%32, %33, %34, %35, %36, %37, %38, %39, %40, %41, %42, %43, %44, %45, %46, %47, "
        "%48, %49, %50, %51, %52, %53, %54, %55}, "
        "{%56, %57, %58, %59}, db, p, %63, 1, %62;\n}\n"
        : "+f"(d[0]), "+f"(d[1]), "+f"(d[2]), "+f"(d[3]), "+f"(d[4]), "+f"(d[5]), "+f"(d[6]), "+f"(d[7]),
          "+f"(d[8]), "+f"(d[9]), "+f"(d[10]), "+f"(d[11]), "+f"(d[12]), "+f"(d[13]), "+f"(d[14]), "+f"(d[15]),
          "+f"(d[16]), "+f"(d[17]), "+f"(d[18]), "+f"(d[19]), "+f"(d[20]), "+f"(d[21]), "+f"(d[22]), "+f"(d[23]),
          "+f"(d[24]), "+f"(d[25]), "+f"(d[26]), "+f"(d[27]), "+f"(d[28]), "+f"(d[29]), "+f"(d[30]), "+f"(d[31]),
          "+f"(d[32]), "+f"(d[33]), "+f"(d[34]), "+f"(d[35]), "+f"(d[36]), "+f"(d[37]), "+f"(d[38]), "+f"(d[39]),
          "+f"(d[40]), "+f"(d[41]), "+f"(d[42]), "+f"(d[43]), "+f"(d[44]), "+f"(d[45]), "+f"(d[46]), "+f"(d[47]),
          "+f"(d[48]), "+f"(d[49]), "+f"(d[50]), "+f"(d[51]), "+f"(d[52]), "+f"(d[53]), "+f"(d[54]), "+f"(d[55])
        : "r"(a[0]), "r"(a[1]), "r"(a[2]), "r"(a[3]), "r"(db), "r"(scale_d), "n"(TB), "n"(SA));
}
template<int TB, int SA = 1>
__device__ __forceinline__ void wgmma_rs_n224(float (&d)[112], const uint32_t (&a)[4], uint32_t db, int scale_d) {
    asm volatile("{\n.reg .pred p;\n.reg .b32 hi;\n.reg .b64 db;\nmov.b32 hi, 0x40000040;\nmov.b64 db, {%116, hi};\nsetp.ne.b32 p, %117, 0;\n"
        "wgmma.mma_async.sync.aligned.m64n224k16.f32.bf16.bf16 "
        "{%0, %1, %2, %3, %4, %5, %6, %7, %8, %9, %10, %11, %12, %13, %14, %15, "
        "%16, %17, %18, %19, %20, %21, %22, %23, %24, %25, %26, %27, %28, %29, %30, %31, "
        "%32, %33, %34, %35, %36, %37, %38, %39, %40, %41, %42, %43, %44, %45, %46, %47, "
        "%48, %49, %50, %51, %52, %53, %54, %55, %56, %57, %58, %59, %60, %61, %62, %63, "
        "%64, %65, %66, %67, %68, %69, %70, %71, %72, %73, %74, %75, %76, %77, %78, %79, "
        "%80, %81, %82, %83, %84, %85, %86, %87, %88, %89, %90, %91, %92, %93, %94, %95, "
        "%96, %97, %98, %99, %100, %101, %102, %103, %104, %105, %106, %107, %108, %109, %110, %111}, "
        "{%112, %113, %114, %115}, db, p, %119, 1, %118;\n}\n"
        : "+f"(d[0]), "+f"(d[1]), "+f"(d[2]), "+f"(d[3]), "+f"(d[4]), "+f"(d[5]), "+f"(d[6]), "+f"(d[7]),
          "+f"(d[8]), "+f"(d[9]), "+f"(d[10]), "+f"(d[11]), "+f"(d[12]), "+f"(d[13]), "+f"(d[14]), "+f"(d[15]),
          "+f"(d[16]), "+f"(d[17]), "+f"(d[18]), "+f"(d[19]), "+f"(d[20]), "+f"(d[21]), "+f"(d[22]), "+f"(d[23]),
          "+f"(d[24]), "+f"(d[25]), "+f"(d[26]), "+f"(d[27]), "+f"(d[28]), "+f"(d[29]), "+f"(d[30]), "+f"(d[31]),
          "+f"(d[32]), "+f"(d[33]), "+f"(d[34]), "+f"(d[35]), "+f"(d[36]), "+f"(d[37]), "+f"(d[38]), "+f"(d[39]),
          "+f"(d[40]), "+f"(d[41]), "+f"(d[42]), "+f"(d[43]), "+f"(d[44]), "+f"(d[45]), "+f"(d[46]), "+f"(d[47]),
          "+f"(d[48]), "+f"(d[49]), "+f"(d[50]), "+f"(d[51]), "+f"(d[52]), "+f"(d[53]), "+f"(d[54]), "+f"(d[55]),
          "+f"(d[56]), "+f"(d[57]), "+f"(d[58]), "+f"(d[59]), "+f"(d[60]), "+f"(d[61]), "+f"(d[62]), "+f"(d[63]),
          "+f"(d[64]), "+f"(d[65]), "+f"(d[66]), "+f"(d[67]), "+f"(d[68]), "+f"(d[69]), "+f"(d[70]), "+f"(d[71]),
          "+f"(d[72]), "+f"(d[73]), "+f"(d[74]), "+f"(d[75]), "+f"(d[76]), "+f"(d[77]), "+f"(d[78]), "+f"(d[79]),
          "+f"(d[80]), "+f"(d[81]), "+f"(d[82]), "+f"(d[83]), "+f"(d[84]), "+f"(d[85]), "+f"(d[86]), "+f"(d[87]),
          "+f"(d[88]), "+f"(d[89]), "+f"(d[90]), "+f"(d[91]), "+f"(d[92]), "+f"(d[93]), "+f"(d[94]), "+f"(d[95]),
          "+f"(d[96]), "+f"(d[97]), "+f"(d[98]), "+f"(d[99]), "+f"(d[100]), "+f"(d[101]), "+f"(d[102]), "+f"(d[103]),
          "+f"(d[104]), "+f"(d[105]), "+f"(d[106]), "+f"(d[107]), "+f"(d[108]), "+f"(d[109]), "+f"(d[110]), "+f"(d[111])
        : "r"(a[0]), "r"(a[1]), "r"(a[2]), "r"(a[3]), "r"(db), "r"(scale_d), "n"(TB), "n"(SA));
}

#define TR(idx) do {} while (0)
#define TRL(idx) do {} while (0)
#define TRX(idx) do {} while (0)
#define TRG(idx) do {} while (0)
#define TR_END() do {} while (0)

template<int V> struct Int { static constexpr int value = V; };
constexpr float ATT_SCALE = 0.18898223650461361f;
constexpr float LOG2E = 1.4426950408889634f;
constexpr uint32_t MASKED = 0xce6ece6eu;

__global__ void __cluster_dims__(2, 1, 1) __launch_bounds__(384, 1)
fused_kernel(__nv_bfloat16* __restrict__ out,
    const __grid_constant__ TMaps tm) {
    extern __shared__ __align__(1024) uint8_t smem_raw[];
    const uint32_t sb = smem_u32(smem_raw);
    const uint32_t bars = sb + BAR_OFF;
    const uint32_t bar_full = bars, bar_empty = bars + 32, bar_abf = bars + 64  , bar_ab6 = bars + 120, bar_ab = bars + 128  , bar_free = bars + 296  , bar_halo = bars + 152;
    const uint32_t bar_o = bars + 160, bar_qkv = bars + 176  , bar_sf = bars + 200, bar_se = bar_sf + 32  ;
    const uint32_t bar_fl = bars + 256  , bar_go = bars + 240  , bar_end = bars + 192, bar_af = bars + 312;
    const uint32_t stg = sb + STG_OFF;
    const int cta = blockIdx.x, r = cta & 1, cl = cta >> 1;
    const int place = pick3(cta, 32 + 8 * cl, cl - 4, cl - 3 + ((cl * 37 - 36 * 37) >> 8));
    const int mt = (place & 7) * 2 + r;
    const int sub = place >> 3;
    const CUtensorMap* tmWd = sub < 4 ? &tm.wdre : &tm.wdim;
    uint32_t t_first = 0;
    if (threadIdx.x < 32 + (((uint32_t)(uintptr_t)tmWd | (ODD2 ? sb >> 20 : sb) | (mt << 6)) & 32) && elect_one()) {
        prefetch_tmap(tmWd); prefetch_tmap(&tm.xB);
        #pragma unroll
        for (int kb = 0; kb < START_N; kb++) {
            mbar_init(bar_abf + 8 * kb, 1);
            mbar_expect_tx(bar_abf + 8 * kb, AB_BYTES);
            tma_load(sb + kb * AB_BYTES + SLOT_A, tmWd, bar_abf + 8 * kb, kb * 64, (sub & 3) * 112);
            tma_load(sb + kb * AB_BYTES, &tm.xB, bar_abf + 8 * kb, kb * 64, mt * 128);
        }
        t_first = clk32();
    }
    const int tid = threadIdx.x, warp = __shfl_sync(0xffffffffu, tid >> 5, 0), lane = tid & 31;
    const bool late = sub < 4;
    const int nh = sub & 1, part = (sub >> 1) & 1;
    const int nj = late ? 32 - KB_EARLY : KB_EARLY;
    static_assert(KB_EARLY == 14, "order of the k-blocks");
    const uint32_t t0 = clk32();
    auto clear_out = [&]() {
        while ((int)(clk32() - t0) < TP(ZERO_AT)) { }
        uint4* zp = reinterpret_cast<uint4*>(out + (size_t)(mt * 128 + sub * 16 + (warp - 2) * 8) * NOUT + DM) + lane;
        #pragma unroll 1
        for (int j = 0; j < (ABL & 8 ? 0 : 8); j++) {
            while ((int)(clk32() - t0) < TP(ZERO_AT) + j * TP(ZERO_GAP)) { }
            zp[j * (NOUT / 8)] = make_uint4(0, 0, 0, 0);
            if (lane < 24) zp[j * (NOUT / 8) + 32] = make_uint4(0, 0, 0, 0);
        }
    };
    if (warp == 0) {
        if (elect_one()) {
            #pragma unroll
            for (int s = START_N; s < 7; s++) mbar_init(bar_abf + 8 * s, 1);
            #pragma unroll
            for (int s = 0; s < NSLOT; s++) { mbar_init(bar_full + 8 * s, 1); mbar_init(bar_empty + 8 * s, 4); }
            asm volatile("fence.mbarrier_init.release.cluster;" ::: "memory");
        }
        __syncwarp();
        cluster_arrive();
        if (elect_one()) {
            #pragma unroll 1
            for (int kb = START_N; kb < 7; kb++) {
                while ((int)(clk32() - t_first) < TP(START_GAP1) + (kb - START_N) * TP(START_GAP)) { }
                const uint32_t a = sb + kb * AB_BYTES, fb = bar_abf + 8 * kb;
                mbar_expect_tx(fb, AB_BYTES);
                tma_load(a, &tm.xB, fb, kb * 64, mt * 128);
                tma_load(a + SLOT_A, tmWd, fb, kb * 64, (sub & 3) * 112);
            }
            TR(2);
            prefetch_tmap(&tm.xA3); prefetch_tmap(&tm.wqkv3);
            if (TP(PF0_N) > 0) {
                while ((int)(clk32() - t_first) < TP(PF0_AT)) { }
                #pragma unroll 1
                for (int it = 0; it < TP(PF0_N); it++) {
                    if (PF0_ALL || (sub & 3) == it) tma_prefetch3(&tm.xA3, it * 64, mt * 64);
                    if (PF0_ALL || (mt >> 1) == it) tma_prefetch3(&tm.wqkv3, sub * 56 - (sub & 1) * 8, it * 64 + r * 32);
                }
            }
        }
        __syncwarp();
    } else if (warp < 4) {
        cluster_arrive();
        if (warp >= 2) clear_out();
    }
    if (warp < 4) {
      reg_set<REG_AUX>();
      const CUtensorMap* tmB = r ? &tm.abP3 : &tm.abP4;
      const uint32_t boff = SLOT_A + r * 16384;
      const int bgrp = part * 14 + nh * 7 + r * 4;
      if (warp == 0) {
        cluster_wait();
        if (elect_one()) {
        uint32_t slot = sb, fb = bar_full, par = 0;
        auto advance = [&]() { if (fb == bar_full + 24) { fb = bar_full; slot = sb; par ^= 1; } else { fb += 8; slot += SLOT_BYTES; } };
        const CUtensorMap* tmW = part ? &tm.wim : &tm.wre;
        const CUtensorMap* tmH = part ? &tm.wimH : &tm.wreH;
        const int qc = sub * 56 - (sub & 1) * 8;
        auto next_kc = [&](int kc, int wi) { return wi == 3 ? (late ? 14 * 64 : 2 * 64) : wi == nj / 2 - 1 ? (late ? 15 * 64 : 64) : kc + (FLIP && wi == 1 ? -768 : wi < nj / 2 ? 256 : 128); };
        #pragma unroll 1
        for (int it = 0; it < 7; it++) {
            mbar_wait_p(fb + 32, par);
            mbar_expect_tx(fb, SLOT_A + 3 * 8192);
            tma_load3(slot, &tm.xA3, fb, it * 64, mt * 64);
            tma_load3_mc(slot + SLOT_A + r * 12288, &tm.wqkv3, fb, qc, it * 64 + r * 32, 0);
            TRL(64 + it);
            if (r && it == 2) {
                const int c = (7 - sub) * 8 + (mt >> 1), c7 = (c * 37) >> 8;
                tma_prefetch3(&tm.xA3, (3 + (sub >> 1)) * 64, (mt - (sub & 1)) * 64);
                if (c7 < 8) tma_prefetch3(&tm.wqkv3, (c - 7 * c7) * 64, 192 + c7 * 32);
            }
            if (it == 1) { prefetch_tmap(tmW); prefetch_tmap(tmB); prefetch_tmap(tmH); }
            advance();
        }
        int kc = (late ? 1024 : 0) + 512 * FLIP;
        #pragma unroll 1
        for (int wi = 0; wi < nj - late; wi++) {
            mbar_wait_p(fb + 32, par);
            if (TP(W_GAP) && wi > 0 && wi < 4) { const uint32_t t1 = clk32() + TP(W_GAP); while ((int)(clk32() - t1) < 0) { } }
            mbar_expect_tx(fb, SLOT_BYTES);
            tma_load(slot, tmW, fb, kc, mt * 128);
            TR(224 + 7 + wi);
            if (wi >= 4) {
                if (wi == 4 || wi == nj / 2) mbar_wait(bar_fl + (wi == 4 ? 16 : 24), 0);
                tma_load5_mc(slot + boff, tmB, fb, kc, bgrp);
                TR(64 + 7 + wi);
            } else mbar_arrive(bar_go + 8 * wi);
            advance();
            kc = next_kc(kc, wi);
            if (wi == (late ? TP(PF_L) : TP(PF_E))) tma_prefetch(tmH, (late ? 29 : 13) * 64, mt * 128 + nh * 64);
            if (late) {
                if (wi == TP(L_XAT) - 1) {
                    mbar_wait(bar_se, 0);
                    mbar_expect_tx(bar_sf, SLOT_BYTES);
                    tma_load5_mc(stg + boff, tmB, bar_sf, 31 * 64, bgrp);
                }
                if (wi == TP(L_XAT)) tma_load(stg, tmW, bar_sf, 31 * 64, mt * 128);
            } else if (wi == TP(WB_AT)) {
                mbar_wait(bar_se, 0);
                #pragma unroll
                for (int j = 0; j < 6; j += 2) tma_load_mc(sb + OUT_B(j) + r * 8192, &tm.wo64, bar_abf, 256 + 48 * (sub & 3), (j + r) * 64);
            } else if (wi == TP(WO_AT) - 1) {
                const int c = mt * 4 + (sub & 3), c7 = (c * 37) >> 8;
                if (c < 49) tma_prefetch(&tm.wo64, (c - 7 * c7) * 64, c7 * 64); else prefetch_tmap(&tm.wo64);
            }
        }
        if (!late) {
            const uint4* const po = g_o + mt * 7168;
            const int ca = 64 * (sub & 3), cb = 256 + 48 * (sub & 3);
            auto load_w = [&](int d0, int c0, int j0, int d1, int c1, int j1, int g) { tma_load_mc(sb + (r ? d1 : d0), &tm.wo64, bar_abf + 8 * g, r ? c1 : c0, (r ? j1 : j0) * 64); };
            auto load_o = [&](int p, int j, int n, int g) { bulk_load(sb + OUT_O(p, j), po + p * 3584 + j * 512, n * 8192, bar_abf + 8 * g); };
            #pragma unroll
            for (int g = 0; g < 6; g++) mbar_expect_tx(bar_abf + 8 * g, (g == 0 ? 11 : g == 1 ? 4 : g == 2 ? 6 : g < 5 ? 3 : 1) * 8192);
            mbar_wait_p(bar_empty + 8, 1);
            load_w(OUT_A(0), ca, 0, OUT_A(1), ca, 1, 0);
            if (r == 0) load_w(OUT_B(6), cb, 6, 0, 0, 0, 0);
            TR(64 + 7 + KB_EARLY);
            mbar_wait_p(bar_fl + 32, 0);
            TR(3);
            load_o(0, 0, 2, 0);
            mbar_wait_p(bar_af, 0);
            load_w(OUT_A(2), ca, 2, OUT_A(3), ca, 3, 1); load_o(0, 2, 2, 1); load_w(OUT_A(4), ca, 4, OUT_A(6), ca, 6, 2);
            TR(64 + 7 + KB_EARLY + 1);
            mbar_wait_p(bar_empty + 16, 1);
            if (r) load_w(0, 0, 0, OUT_A(5), ca, 5, 2);
            load_o(0, 4, 3, 2);
            TR(64 + 7 + KB_EARLY + 2);
            mbar_wait_p(bar_empty + 24, 1);
            load_o(1, 0, 3, 3);
            TR(64 + 7 + KB_EARLY + 3);
            mbar_wait_p(bar_empty, 0);
            load_o(1, 3, 3, 4);
            TR(64 + 7 + KB_EARLY + 4);
            mbar_wait_p(bar_ab6, 0);
            load_o(1, 6, 1, 5);
            TR(64 + 7 + KB_EARLY + 5);
        }
        mbar_arrive(bar_end);
        }
      } else {
        const unsigned epoch = ld_relaxed(&g_epoch[cta * 8]) + 1;
        cluster_wait();
        auto forward = [&](const unsigned* fl, unsigned target, auto first, uint32_t bar, uint32_t again) {
            for (int spin = 0; !__all_sync(0xffffffffu, (int)(ld_acquire(fl) - target) >= 0);) {
                if ((int)(clk32() - again) < 0) { while ((int)(clk32() - again) < 0) { } } else __nanosleep(target != epoch ? TP(OPOLL_NS) : TP(POLL_NS));
                if (++spin > SPIN_LIMIT) give_up();
            }
            if (elect_one()) {
                fence_async_global();
                if constexpr (decltype(first)::value == 2) { if (atomicExch(reinterpret_cast<unsigned*>(smem_raw + BAR_OFF + 144), 1u) == 0) mbar_arrive(bar); }
                else if constexpr (!decltype(first)::value) mbar_arrive(bar);
                else {
                    #pragma unroll
                    for (int i = 0; i < 2; i++) {
                        const int wi = 2 * (warp - 2) + i, sl = (wi + 3) & 3;
                        mbar_wait_limit(bar_go + 8 * wi, 0);
                        tma_load5_mc(sb + sl * SLOT_BYTES + boff, tmB, bar_full + 8 * sl, (late ? 1024 : 0) + 256 * (wi ^ 2 * FLIP), bgrp);
                        TR(64 + 7 + wi);
                        if (i == 0) { const uint32_t t1 = clk32() + TP(BIG_GAP); while ((int)(clk32() - t1) < 0) { } }
                    }
                }
            }
            __syncwarp();
        };
        const int frow = part * 4 + nh * 2 + (lane & 1), st0 = late ? 8 : 0;
        const int ft = late ? min(7 + (lane >> 1), 15) : min(lane >> 1, 6);
        const unsigned* const fl2 = &g_flag_ab[(32 + frow) * 32 + (late ? min(7 + (lane & 14), 15) : min(1 + (lane & 14), 5))];
        const unsigned* const fl3 = &g_flag_ab[(16 + 8 * (ft & 1) + frow) * 32 + ft];
        if (warp == 1) {
            if (elect_one()) {
                prefetch_tmap(&tm.abH); if (BIG_ST) { prefetch_tmap(&tm.ab80); prefetch_tmap(&tm.ab32); }
                const int e0 = pin(sub * 112 - (sub & 2) * 16), e1 = pin((sub & 3) == 2 ? 224 : 0);
                #pragma unroll 1
                for (int hf = 0; hf < 2; hf++) {
                    const int gap = pin(hf ? (r ? TP(ABS_GAP3) : TP(ABS_GAP2)) : (r ? TP(ABS_GAP) : 0)), sc = pin(mt * 128 + hf * 64);
                    const uint32_t src = pin(hf ? stg : sb + 7 * AB_BYTES);
                    unsigned* const fl = pin(&g_flag_ab[((hf ? 2 + r : r ? 4 : URG(mt)) * 8 + sub) * 32 + mt]);
                    mbar_wait(bar_ab + 8 * hf, 0);
                    fence_async_smem();
                    uint32_t t1 = clk32() + (hf ? 0 : r ? TP(ABS_AT) : URG(mt) * TP(ABS_AT1));
                    if (BIG_ST && (hf | r) == 0) {
                        if (URG(mt)) { while ((int)(clk32() - t1) < 0) { } }
                        TR(4);
                        tma_store(&tm.ab80, src + 4096, sc, e0 + 32);
                        tma_store(&tm.ab32, src, sc, e0 + e1);
                    } else
                    #pragma unroll
                    for (int i = 0; i < 7; i++) {
                        if (i == 0 || gap) { while ((int)(clk32() - t1) < 0) { } }
                        t1 += gap;
                        if (i == 0 && hf == 0) TR(4);
                        if (hf > r && i % 3 == 0 && i / 3 < TP(PF_N)) tma_prefetch(part ? &tm.wim : &tm.wre, (late ? 1024 : 0) + ((i / 3) ^ 2 * FLIP) * 256, (mt + nh) * 128);
                        tma_store(&tm.abH, src + i * 2048, sc, e0 + i * 16 + (i < 2 ? e1 : 0));
                    }
                    bulk_commit();
                    bulk_wait_all();
                    if (hf) TR(5);
                    mbar_arrive(bar_free + 8 * hf);
                    st_release(fl, epoch);
                    TR(hf ? 6 : 38);
                }
                uint4* const po = pin(g_o + mt * 7168 + sub * 448);
                mbar_wait(bar_o, 0);
                fence_async_smem();
                TR(9);
                {
                    uint32_t t2 = clk32();
                    #pragma unroll 1
                    for (int i = 0; i < 2 * O_N; i++) {
                        while ((int)(clk32() - t2) < 0) { }
                        t2 += TP(O_GAP);
                        bulk_store(po + (i >= O_N ? 3584 - 448 : 0) + i * (448 / O_N), stg + i * (7168 / O_N), 7168 / O_N);
                    }
                }
                bulk_commit();
                TR(62);
                bulk_wait_all();
                TR(111);
                mbar_arrive(bar_se); mbar_arrive_remote(bar_se, r ^ 1);
                red_release(&g_flag_o[mt * 32], 1);
                TR(17); TRG(102);
                if (!late) {
                    prefetch_tmap(&tm.outA); prefetch_tmap(&tm.outB);
                    #pragma unroll
                    for (int c = 0; c < 2; c++) {
                        mbar_wait(bar_qkv + 8 * c, 1);
                        fence_async_smem();
                        tma_store3(c ? &tm.outB : &tm.outA, sb + OUT_O(0, 1) + c * 8192, mt * 64, sub & 3);
                    }
                    bulk_commit();
                    asm volatile("cp.async.bulk.wait_group.read 0;" ::: "memory");
                    TR(19);
                }
            }
            __syncwarp();
        } else {
            asm volatile("st.shared.u32 [%0], %1;" :: "r"(bars + 168), "r"(epoch) : "memory");
            if (OPOLL2_ON) asm volatile("st.shared.u32 [%0], %1;" :: "r"(bars + 144), "r"(0) : "memory");
            __syncwarp();
            if (lane == 0) mbar_arrive(bar_ab + 8);
            mbar_wait_limit(bar_ab, 0);
            const uint32_t ta = clk32();
            if (tid == 96) TRG(98);
            const bool rest = warp == 3 && __all_sync(0xffffffffu, (int)(ld_acquire(lane >= 22 ? fl2 : fl3) - epoch) >= 0);
            forward(&g_flag_ab[((warp - 2) * 8 + frow) * 32 + st0 + 4 * ((warp - 2) ^ FLIP) + (lane & 2)], epoch, Int<1>(), 0, ta + (warp == 2 ? TP(POLL_AT) : TP(POLL_AT1)));
            if (warp == 2) {
                const uint4* const hp = pin(g_halo + (max(mt - 1, 0) * 8 + sub) * 320 + lane);
                const uint32_t ha = pin(stg + KV_OFF + (lane & 7) * KV_PITCH + (lane >> 3) * 16);
                mbar_wait(mt > 0 ? bar_go + 24 : bar_qkv, 0);
                uint4 v[10];
                if (mt > 0) {
                    const uint32_t tq = clk32();
                    while ((int)(clk32() - tq) < TP(HALO_WAIT)) { }
                    #pragma unroll 1
                    for (;;) {
                        uint32_t bad = 0;
                        #pragma unroll
                        for (int j = 0; j < 10; j++) v[j] = ld_b128_relaxed(hp + j * 32);
                        #pragma unroll
                        for (int j = 0; j < 10; j++) bad |= v[j].w ^ epoch;
                        if (__all_sync(0xffffffffu, bad == 0) || (ABL & 1)) break;
                        __nanosleep(200);
                    }
                } else {
                    const uint32_t r0 = stg + KV_OFF + 8 * KV_PITCH + 112 + (lane & 3) * 4;
                    v[0].x = v[0].y = v[0].z = v[1].x = v[1].y = v[1].z = v[2].x = 0;
                    v[2].y = lds32(r0); v[2].z = lds32(r0 + 16); v[3].x = lds32(r0 + 32); v[3].y = lds32(r0 + 48); v[3].z = lds32(r0 + 64); v[4].x = lds32(r0 + 80); v[4].y = lds32(r0 + 96);
                    #pragma unroll
                    for (int j = 0; j < 5; j++) v[5 + j] = v[j];
                }
                mbar_wait(bar_free, 0);
                #pragma unroll
                for (int p = 0; p < 2; p++) {
                    const uint4* u = v + 5 * p;
                    stsm_x4(ha + p * KV_PAR, u[0].x, u[0].y, u[0].z, u[1].x);
                    stsm_x4(ha + p * KV_PAR + 64, u[1].y, u[1].z, u[2].x, u[2].y);
                    stsm_x4(ha + p * KV_PAR + 128, u[2].z, u[3].x, u[3].y, u[3].z);
                    stsm_x2(ha + p * KV_PAR + 192, u[4].x, u[4].y);
                }
                __syncwarp();
                if (lane == 0) { mbar_arrive(bar_halo); TR(10); TRG(100); }
                if (OPOLL2_ON && !late) {
                    mbar_wait(bar_ab + 8, 0);
                    const uint32_t at = ta + TP(OPOLL_AT) + TP(OPOLL2);
                    while ((int)(clk32() - at) < 0) { }
                    forward(&g_flag_o[mt * 32], epoch * 8, Int<2>(), bar_fl + 32, at);
                }
            } else {
                #pragma unroll 1
                for (int j = 2; j < (late ? 4 : 5); j++) {
                    const unsigned* const fl = j == 2 ? fl2 : j == 4 ? &g_flag_o[mt * 32] : lane < 24 ? fl3 : &g_flag_ab[(16 + 8 * r + (lane & 7)) * 32 + mt];
                    const uint32_t at = ta + (j == 2 ? TP(POLL_AT2) : j == 3 ? TP(POLL_AT3) : TP(OPOLL_AT));
                    if (!rest) { while ((int)(clk32() - at) < 0) { } }
                    if (OPOLL2_ON && j == 4) { mbar_wait(bar_ab + 8, 0); forward(fl, epoch * 8, Int<2>(), bar_fl + 32, at); } else
                    forward(fl, j == 4 ? epoch * 8 : epoch, Int<0>(), bar_fl + 8 * j, at);
                    if (lane == 0) TR(j == 3 ? 39 : j == 4 ? 13 : 35 + j);
                }
                mbar_wait_limit(bar_end, 0);
            }
            __syncwarp();
        }
      }
      TR_END();
    } else {
        if (tid == 128) {
            mbar_init(bar_ab6, 1); mbar_init(bar_ab, 4); mbar_init(bar_ab + 8, 6); mbar_init(bar_free, 1); mbar_init(bar_free + 8, 1); mbar_init(bar_qkv, 4); mbar_init(bar_qkv + 8, 4); mbar_init(bar_o, 8);
            mbar_init(bar_halo, 1); mbar_init(bar_end, 3);
            #pragma unroll
            for (int j = 0; j < 7; j++) mbar_init(bar_go + 8 * j, 1);
            mbar_init(bar_sf, 1); mbar_init(bar_se, 2); mbar_init(bar_af, 4);
            asm volatile("fence.mbarrier_init.release.cluster;" ::: "memory");
        }
        __syncwarp();
        cluster_arrive();
        if (warp >= 8) {
            float d[4];
            #pragma unroll 1
            for (int i = 0; i < TP(WARM_N); i++) {
                const uint32_t t1 = clk32();
                wgmma_fence();
                wgmma_n8<1, 0>(d, desc_k(sb + 7 * AB_BYTES), desc_k(sb + 7 * AB_BYTES), 0);
                wgmma_commit();
                wgmma_wait<0>();
                while ((int)(clk32() - t1) < TP(WARM_GAP)) { }
                __syncwarp();
            }
        }
        cluster_wait();
        const int wg = warp >> 3, w = warp & 3, cw = warp - 4;

        const bool sig_local = (tid & 127) == 0;
        const int i8 = lane & 7, m = lane >> 3;
        const bool sig = (tid & 95) == 0;
        uint32_t rel;
        asm("mapa.shared::cluster.u32 %0, %1, %2;" : "=r"(rel) : "r"(bar_empty), "r"(r ^ (w & 1)));
        auto done = [&](int it) { (void)it; if ((tid & 127) == 64) TRL(160 + it); };
        auto release = [&](int s) { if (sig) asm volatile("mbarrier.arrive.shared::cluster.b64 _, [%0];" :: "r"(rel + 8 * s) : "memory"); };
        const uint32_t dA = desc_k(sb + wg * 8192), dB = desc_k(sb + SLOT_A), dBt = desc_mn(sb + SLOT_A);
        const uint32_t a_frag = sb + wg * 8192 + (w * 16 + (lane & 15)) * 128 + (((lane >> 4) ^ i8) << 4);
        auto wait_full = [&](int it) { mbar_wait(bar_full + 8 * (it & 3), (it >> 2) & 1); if (sig_local) TR(128 + wg * 64 + it); };
        uint32_t kq[4][4], vq[14], qb[2][8];
        {
            float aq[28], ak[28], av[28];
            uint32_t mh0 = 0;
            uint32_t af[2][4][4];
            auto load_af = [&](int it) {
                wait_full(it);
                #pragma unroll
                for (int k = 0; k < 4; k++) ldsm_x4((a_frag ^ (k << 5)) + (it & 3) * SLOT_BYTES, af[it & 1][k][0], af[it & 1][k][1], af[it & 1][k][2], af[it & 1][k][3]);
            };
            uint32_t abw[28], base;
            auto stage_ab = [&](int j0, int j1) {
                #pragma unroll
                for (int j = j0; j < j1; j++) {
                    if (j < 7) stsm_x4_t(base + j * 2048, abw[4 * j], abw[4 * j + 1], abw[4 * j + 2], abw[4 * j + 3]);
                    else { __syncwarp(); if (lane == 0) mbar_arrive(bar_ab + 8 * wg); }
                }
            };
            {
                float bacc[56];
                base = pin((wg ? stg : sb + 7 * AB_BYTES) + (((2 * w + (m & 1)) ^ i8) << 4) + ((m >> 1) * 8 + i8) * 128);
                auto ab_loop = [&](auto sign) {
                auto ab_issue = [&](int kb) {
                    mbar_wait_p(bar_abf + 8 * kb, 0);
                    if (kb == 0 && wg == 1) asm volatile("bar.sync 3, 256;" ::: "memory");
                    if (sig_local) TR(112 + wg * 8 + kb);
                    wgmma_fence();
                    #pragma unroll
                    for (int k = 0; k < 4; k++) wgmma_n112<decltype(sign)::value, 0>(bacc, dA + kb * (AB_BYTES >> 4) + 2 * k, dB + kb * (AB_BYTES >> 4) + 2 * k, (kb | k) != 0);
                    wgmma_commit();
                    if (kb == 0 && wg == 0) asm volatile("bar.arrive 3, 256;" ::: "memory");
                };
                #pragma unroll
                for (int kb = 0; kb < 5; kb++) {
                    ab_issue(kb);
                    if (kb > 0) wgmma_wait<1>();
                    if (kb == 2 || kb == 3) release(kb - 2);
                }
                if (wg == 0) {
                    ab_issue(5);
                    ab_issue(6);
                    asm volatile("bar.arrive 4, 256;" ::: "memory");
                    wgmma_wait<2>();
                    release(2);
                } else {
                    uint32_t xf[8][4];
                    #pragma unroll
                    for (int j = 0; j < 8; j++) {
                        if ((j & 3) == 0) mbar_wait(bar_abf + 8 * (5 + (j >> 2)), 0);
                        ldsm_x4((a_frag ^ ((j & 3) << 5)) + (5 + (j >> 2)) * AB_BYTES, xf[j][0], xf[j][1], xf[j][2], xf[j][3]);
                    }
                    wgmma_wait<0>();
                    release(2);
                    asm volatile("bar.sync 4, 256;" ::: "memory");
                    wgmma_fence();
                    #pragma unroll
                    for (int j = 0; j < 8; j++) {
                        wgmma_rs_n112<0, decltype(sign)::value>(bacc, xf[j], dB + (5 + (j >> 2)) * (AB_BYTES >> 4) + 2 * (j & 3), 1);
                        if ((j & 3) == 3) wgmma_commit();
                    }
                }
                };
                if (sub >> 2) ab_loop(Int<-1>()); else ab_loop(Int<1>());
                wgmma_wait<1>();
                release(3);
                reg_set<REG_CONS>();
                if (wg == 1) load_af(0);
                wgmma_wait<0>();
                if (sig_local) TRX(21 + wg);
                if (AB_ST) { if (wg == 0) asm volatile("bar.arrive 3, 256;" ::: "memory"); else asm volatile("bar.sync 3, 256;" ::: "memory"); }
                #pragma unroll
                for (int j = 0; j < 28; j++) abw[j] = pack_bf16(bacc[2 * j], bacc[2 * j + 1]);
                stage_ab(0, AB_ST);
                if (wg == 0 || AB_ST == 7) stage_ab(AB_ST, 8);
            }
            const uint32_t dQ = dBt + (sub & 1);
            #pragma unroll
            for (int it = 0; it < 7; it++) {
                const uint32_t o = (it & 3) * (SLOT_BYTES >> 4);
                if (it > 0 || wg == 0) load_af(it);
                if (it == 5) mh0 = pin((lane & 3) < 2 ? 0xffffffffu : 0u);
                if (AB_ST < 7 && wg == 1) { if (it == 1) stage_ab(AB_ST, AB_ST2); if (it == 2) stage_ab(AB_ST2, 8); }
                wgmma_wait<0>();
                if (it > 0) { release((it - 1) & 3); done(it - 1); }
                if (it == 0 && sig_local) TRL(60 + wg);
                if (wg == 0) { if (it > 0) asm volatile("bar.sync 6, 256;" ::: "memory"); } else asm volatile("bar.sync 8, 256;" ::: "memory");
                wgmma_fence();
                #pragma unroll
                for (int j = 0; j < 12; j++) {
                    const int k = it < 6 || !KV_FIRST ? j / 3 : j < 8 ? j >> 1 : j - 8, x = it < 6 || !KV_FIRST ? j % 3 : j < 8 ? j & 1 : 2;
                    const uint32_t d = dQ + o + (k >> 1) * 768 + (k & 1) * 128;
                    if (j == Q_ARR) { if (wg == 0) asm volatile("bar.arrive 8, 256;" ::: "memory"); else asm volatile("bar.arrive 6, 256;" ::: "memory"); }
                    if (x == 0) wgmma_rs_n56<1>(ak, af[it & 1][k], d + 256, (it | k) != 0);
                    if (x == 1) wgmma_rs_n56<1>(av, af[it & 1][k], d + 512, (it | k) != 0);
                    if (x == 2) wgmma_rs_n56<1>(aq, af[it & 1][k], d, (it | k) != 0);
                    if (KV_FIRST && it == 6 && j == 7) wgmma_commit();
                }
                wgmma_commit();
            }
            uint4* const hp = pin(g_halo + (mt * 8 + sub) * 320 + wg * 160 + lane);
            mbar_wait(bar_ab + 8, 0);
            const uint32_t epoch = lds32(bars + 168);
            wgmma_wait<KV_FIRST>();
            #pragma unroll
            for (int j = 0; j < 16; j++) kq[j >> 2][j & 3] = pin(pack_bf16(ak[2 * (j - 2 * (j > 7))], ak[1 + 2 * (j - 2 * (j > 7))]));
            #pragma unroll
            for (int j = 0; j < 14; j++) vq[j] = pin(pack_bf16(av[2 * j], av[2 * j + 1]));
            if (w == 3 && !(ABL & 1)) {
                st_b128_relaxed(hp, kq[0][1], kq[0][3], kq[1][1], epoch);
                st_b128_relaxed(hp + 32, kq[1][3], kq[2][3], kq[3][1], epoch);
                st_b128_relaxed(hp + 64, kq[3][3], vq[1], vq[3], epoch);
                st_b128_relaxed(hp + 96, vq[5], vq[7], vq[9], epoch);
                st_b128_relaxed(hp + 128, vq[11], vq[13], 0u, epoch);
                if (lane == 0) TR(8);
            }
            wgmma_wait<0>();
            release(6 & 3);
            if (sig_local) TRX(23 + wg);
            #pragma unroll
            for (int j = 0; j < 14; j++) qb[j & 1][(j >> 1) + (j > 7)] = pin(pack_bf16(aq[2 * j], aq[2 * j + 1]));
            #pragma unroll
            for (int j = 0; j < 2; j++) { qb[j][4] = qb[j][3] & ~mh0; qb[j][3] &= mh0; }
        }
        float acc[112];
        const int it1 = 7 + nj;
        auto big_issue = [&](int slot, bool first) {
            wgmma_fence();
            #pragma unroll
            for (int k = 0; k < 4; k++) wgmma_n224<1, 0>(acc, dA + slot * (SLOT_BYTES >> 4) + 2 * k, dB + slot * (SLOT_BYTES >> 4) + 2 * k, !first || k != 0);
            wgmma_commit();
        };
        if (wg == 1) {
            asm volatile("bar.sync 7, 256;" ::: "memory");
            big_issue(3, true);
        } else {
            wait_full(7);
            asm volatile("bar.sync 6, 256;" ::: "memory");
            big_issue(3, true);
            asm volatile("bar.arrive 7, 256;" ::: "memory");
            if (sig_local) TR(20);
        }
        {
            auto plain = [&](int it) {
                wait_full(it); wgmma_wait<0>(); release((it - 1) & 3); done(it - 1); big_issue(it & 3, false);
                mbar_wait(bar_free, 0);
            };
            auto before_mma = [&](int it, int last) {
                if (wg == last) {
                    mbar_wait_limit(bar_full + 8 * (it & 3), (it >> 2) & 1);
                    if (sig_local) TR(128 + last * 64 + it);
                    asm volatile("bar.sync 2, 256;" ::: "memory");
                    wgmma_wait<0>();
                    release((it - 1) & 3);
                    done(it - 1);
                } else {
                    if (GAP_FLIP) { wgmma_wait<0>(); release((it - 1) & 3); }
                    asm volatile("bar.arrive 2, 256;" ::: "memory");
                }
            };
            auto after_mma = [&](int it, int last) {
                if (wg == (last ^ 1)) {
                    if (!GAP_FLIP) { wgmma_wait<0>(); release((it - 1) & 3); }
                    asm volatile("bar.sync 7, 256;" ::: "memory");
                    big_issue(it & 3, false);
                } else {
                    big_issue(it & 3, false);
                    asm volatile("bar.arrive 7, 256;" ::: "memory");
                }
            };
            const uint32_t kvw = stg + KV_OFF + wg * KV_PAR + (w * 16 + i8) * KV_PITCH;
            const uint32_t a_k = kvw + (m & 1) * 8 * KV_PITCH + (m >> 1) * 16, a_v = kvw + (m >> 1) * 8 * KV_PITCH + 112 + (m & 1) * 16;
            mbar_wait(bar_free, 0);
            #pragma unroll
            for (int u = 0; u < (ABL & 64 ? 0 : 3); u++) stsm_x4(a_k + 8 * KV_PITCH + 112 + u * 32, vq[4 * u], vq[4 * u + 1], vq[4 * u + 2], vq[4 * u + 3]);
            if (!(ABL & 64)) stsm_x2(a_k + 8 * KV_PITCH + 112 + 96, vq[12], vq[13]);
            plain(8);
            #pragma unroll
            for (int u = 0; u < (ABL & 64 ? 1 : 4); u++) stsm_x4(a_k + 8 * KV_PITCH + (2 * u - (u > 1)) * 16, kq[u][0], kq[u][1], kq[u][2], kq[u][3]);
            __syncwarp();
            if (lane == 0) mbar_arrive(bar_qkv + 8 * wg);
            if (sig_local) TR(25 + wg);
            uint32_t kp[4][4], vt[8][4], pb[4][2];
            auto load_v = [&](int n) {
                #pragma unroll
                for (int u = 0; u < 4; u++) {
                    if ((ABL & 64) && u > 0) { vt[2 * u + n][0] = vq[u]; vt[2 * u + n][1] = vq[u + 4]; vt[2 * u + n][2] = vq[u + 8]; vt[2 * u + n][3] = vq[u + n]; } else
                    ldsm_x4_t(a_v + n * 8 * KV_PITCH + (2 * u - (u > 1)) * 16, vt[2 * u + n][0], vt[2 * u + n][1], vt[2 * u + n][2], vt[2 * u + n][3]);
                }
            };
            load_v(1);
            plain(9);
            if (QK_AT > 10) plain(10);
            mbar_wait(w == 0 && !(ABL & 2) ? bar_halo : bar_qkv + 8 * wg, 0);
            #pragma unroll
            for (int u = 0; u < 4; u++) {
                if ((ABL & 64) && u > 0) { kp[u][0] = kq[u][1]; kp[u][1] = kq[u][0]; kp[u][2] = kq[u][3]; kp[u][3] = kq[u][2]; } else
                ldsm_x4(a_k + (2 * u - (u > 1)) * 16, kp[u][0], kp[u][1], kp[u][2], kp[u][3]);
            }
            if (sig_local) TR(54 + wg);
            before_mma(QK_AT, GAP_FLIP);
            float s[4][4];
            #pragma unroll
            for (int i = 0; i < 16; i++) s[i >> 2][i & 3] = 0.f;
            #pragma unroll
            for (int i = 0; i < (ABL & 4 ? 0 : 8); i++) {
                const int n = i & 1, h = (i >> 1) & 1, ks = 2 * h + (i >> 2);
                if (n) mma16816(s[i & 3], kq[ks][0], kq[ks][1], kq[ks][2], kq[ks][3], qb[1][2 * ks], qb[1][2 * ks + 1]);
                else mma16816(s[i & 3], kp[ks][0], kp[ks][1], kp[ks][2], kp[ks][3], qb[0][2 * ks], qb[0][2 * ks + 1]);
            }
            #pragma unroll
            for (int i = 0; i < 16; i++) asm volatile("" : "+f"(s[i >> 2][i & 3]) :: "memory");
            after_mma(QK_AT, GAP_FLIP);
            if (sig_local) TR(48 + wg);
            const int g = lane >> 2, t2 = 2 * (lane & 3);
            const uint32_t mlo = (t2 > g ? 0xffffu : 0u) | (t2 + 1 > g ? 0xffff0000u : 0u), before = (mt | w) == 0 ? mlo : 0u;
            uint32_t y[4], mx[2];
            #pragma unroll
            for (int i = 0; i < 4; i++) {
                const uint32_t x = pack_bf16(g > t2 ? s[i][0] : s[i][2], g > t2 + 1 ? s[i][1] : s[i][3]);
                y[i] = movm_t(pack_bf16(bf_lo(x) * ATT_SCALE, bf_hi(x) * ATT_SCALE));
                if (!(i & 1)) y[i] = (y[i] & ~before) | (MASKED & before);
            }
            #pragma unroll
            for (int h = 0; h < 2; h++) {
                mx[h] = max_bf16x2(__byte_perm(y[2 * h], y[2 * h + 1], 0x5410), __byte_perm(y[2 * h], y[2 * h + 1], 0x7632));
                mx[h] = pin(max_bf16x2(mx[h], __shfl_xor_sync(0xffffffffu, mx[h], 1)));
            }
            load_v(0);
            if (sig_local) TR(50 + wg);
            plain(QK_AT + 1);
            #pragma unroll
            for (int h = 0; h < 2; h++) mx[h] = max_bf16x2(mx[h], __shfl_xor_sync(0xffffffffu, mx[h], 2));
            #pragma unroll
            for (int i = 0; i < 4; i++) {
                const float mi = i & 1 ? bf_hi(mx[i >> 1]) : bf_lo(mx[i >> 1]);
                const float e0 = ex2_approx((bf_lo(y[i]) - mi) * LOG2E), e1 = ex2_approx((bf_hi(y[i]) - mi) * LOG2E);
                float sum = e0 + e1;
                sum += __shfl_xor_sync(0xffffffffu, sum, 1);
                sum += __shfl_xor_sync(0xffffffffu, sum, 2);
                const float inv = rcp_approx(sum);
                const uint32_t p = pack_bf16(e0 * inv, e1 * inv);
                pb[i][0] = pin(p & mlo); pb[i][1] = pin(p & ~mlo);
            }
            if (sig_local) TR(52 + wg);
            before_mma(QK_AT + 2, 0);
            float ao[8][4];
            #pragma unroll
            for (int i = 0; i < 8; i++) {
                ao[i][0] = ao[i][1] = ao[i][2] = ao[i][3] = 0.f;
                if (!(ABL & 4)) mma16816(ao[i], vt[i][0], vt[i][1], vt[i][2], vt[i][3], pb[(i >> 2) * 2 + (i & 1)][0], pb[(i >> 2) * 2 + (i & 1)][1]);
            }
            #pragma unroll
            for (int i = 0; i < 32; i++) asm volatile("" : "+f"(ao[i >> 2][i & 3]) :: "memory");
            after_mma(QK_AT + 2, 0);
            if (sig_local) TRX(11 + wg);
            if (g >= 4) { ao[2][2] = ao[4][0]; ao[2][3] = ao[4][1]; ao[3][2] = ao[5][0]; ao[3][3] = ao[5][1]; }
            mbar_wait(bar_free + 8, 0);
            const uint32_t orow = stg + wg * 7168 + (m >> 1) * 1024 + (w * 16 + (lane & 15)) * 16;
            stsm_x4_t(orow, pack_bf16(ao[0][0], ao[0][1]), pack_bf16(ao[1][0], ao[1][1]), pack_bf16(ao[0][2], ao[0][3]), pack_bf16(ao[1][2], ao[1][3]));
            stsm_x4_t(orow + 2048, pack_bf16(ao[2][0], ao[2][1]), pack_bf16(ao[3][0], ao[3][1]), pack_bf16(ao[2][2], ao[2][3]), pack_bf16(ao[3][2], ao[3][3]));
            stsm_x4_t(orow + 4096, pack_bf16(ao[4][2], ao[4][3]), pack_bf16(ao[5][2], ao[5][3]), pack_bf16(ao[6][0], ao[6][1]), pack_bf16(ao[7][0], ao[7][1]));
            stsm_x2_t(orow + 6144, pack_bf16(ao[6][2], ao[6][3]), pack_bf16(ao[7][2], ao[7][3]));
            __syncwarp();
            if (lane == 0) mbar_arrive(bar_o);
        }
        uint32_t af[12][4];
        #pragma unroll 1
        for (int it = QK_AT + 3; it < it1 - 3; it++) {
            wait_full(it);
            wgmma_wait<0>();
            if (it != 7 + 32 - KB_EARLY - 4) release((it - 1) & 3);
            done(it - 1);
            big_issue(it & 3, false);
            if (L_PRE && it == 7 + 32 - KB_EARLY - 5) {
                mbar_wait(bar_sf, 0);
                #pragma unroll
                for (int k = 0; k < 4; k++) ldsm_x4((a_frag ^ (k << 5)) + NSLOT * SLOT_BYTES, af[k][0], af[k][1], af[k][2], af[k][3]);
            }
        }
        mbar_wait(bar_fl + 24, 0);
        if (tid == 128) atomicAdd(&g_epoch[cta * 8], 1);
        __nv_bfloat16* const yp = pin(out + (size_t)(mt * 128 + cw * 16 + (lane >> 2)) * NOUT + DM + nh * 256 + (lane & 3) * 8);
        const int y6 = 192 - nh * 224;
        #define Y_WORD(A, i, jj) pack_bf16(A[16 * ((i) >> 1) + 4 * (jj) + 2 * ((i) & 1)], A[16 * ((i) >> 1) + 4 * (jj) + 2 * ((i) & 1) + 1])
        #define Y_ADDR(i) (yp + ((i) & 1) * 8 * NOUT + ((i) < 12 ? ((i) >> 1) * 32 : y6))
        const bool odd = lane & 4;
        __nv_bfloat16* const yq = pin(odd ? yp - NOUT + 32 : yp);
        #define Y_PAIR(A, i, B, j, rh, C, PAUSE) do { \
            uint32_t x_[4], y_[4]; \
            _Pragma("unroll") \
            for (int jj = 0; jj < 4; jj++) { \
                const uint32_t u_ = Y_WORD(A, 2 * (i) + (rh), jj), v_ = Y_WORD(B, 2 * (j) + (rh), jj), o_ = __shfl_xor_sync(0xffffffffu, odd ? u_ : v_, 4); \
                x_[jj] = odd ? o_ : u_; y_[jj] = odd ? v_ : o_; \
            } \
            red_add_bf16x8(yq + (rh) * 8 * NOUT + (C), x_[0], x_[1], x_[2], x_[3]); \
            PAUSE; \
            red_add_bf16x8(yq + ((rh) * 8 + 1) * NOUT + (C), y_[0], y_[1], y_[2], y_[3]); \
        } while (0)
        if (late) {
            constexpr int IT = 7 + 32 - KB_EARLY - 3;
            #define L_SLOT(j) ((j) == 0 ? NSLOT : (IT + (j) - 1) & 3)
            auto load_af = [&](int j) {
                if (j == 0) mbar_wait(bar_sf, 0); else wait_full(IT + j - 1);
                #pragma unroll
                for (int k = 0; k < 4; k++) ldsm_x4((a_frag ^ (k << 5)) + L_SLOT(j) * SLOT_BYTES, af[4 * j + k][0], af[4 * j + k][1], af[4 * j + k][2], af[4 * j + k][3]);
            };
            if (!L_PRE) load_af(0);
            load_af(1);
            if (L_UP) load_af(2);
            wgmma_wait<0>();
            done(IT - 1);
            if (!L_UP && wg == 1) load_af(2);
            auto issue = [&](auto& p, auto c0, int j0, int j1, bool first, bool last) {
                constexpr int W = sizeof(p) / 2, C0 = decltype(c0)::value;
                if (wg == 0) { if (!first) asm volatile("bar.sync 9, 256;" ::: "memory"); } else asm volatile("bar.sync 5, 256;" ::: "memory");
                wgmma_fence();
                #pragma unroll
                for (int j = j0; j < j1; j++) {
                    if (!L_UP && first && j == 8) { if (wg == 0) load_af(2); wgmma_fence(); }
                    if (j == j1 - 12 + L_ARR) { if (wg == 0) asm volatile("bar.arrive 5, 256;" ::: "memory"); else if (!last) asm volatile("bar.arrive 9, 256;" ::: "memory"); }
                    const uint32_t d = dB + L_SLOT(j >> 2) * (SLOT_BYTES >> 4) + C0 * 8 + 2 * (j & 3);
                    if constexpr (W == 64) wgmma_rs_n64<0>(p, af[j], d, 1); else wgmma_rs_n32<0>(p, af[j], d, 1);
                }
                wgmma_commit();
            };
            float p0[32], p1[32], p2[32], p3[16];
            #pragma unroll
            for (int i = 0; i < 16; i++) asm volatile("mov.b32 %0, %1;" : "=f"(p3[i]) : "f"(acc[96 + i]));
            #pragma unroll
            for (int i = 0; i < 32; i++) asm volatile("mov.b32 %0, %1;" : "=f"(p2[i]) : "f"(acc[64 + i]));
            #pragma unroll
            for (int i = 0; i < 32; i++) asm volatile("mov.b32 %0, %1;" : "=f"(p1[i]) : "f"(acc[32 + i]));
            #pragma unroll
            for (int i = 0; i < 32; i++) asm volatile("mov.b32 %0, %1;" : "=f"(p0[i]) : "f"(acc[i]));
            issue(p0, Int<0>(), 0, 12, true, false);
            wgmma_wait<0>();
            if (sig_local) TRL(14 + wg);
            Y_PAIR(p0, 0, p0, 1, 0, 0, ); Y_PAIR(p0, 0, p0, 1, 1, 0, );
            issue(p1, Int<64>(), 0, 12, false, false);
            wgmma_wait<0>();
            Y_PAIR(p1, 0, p1, 1, 0, 64, ); Y_PAIR(p1, 0, p1, 1, 1, 64, );
            issue(p2, Int<128>(), 0, 12, false, false);
            wgmma_wait<0>();
            if (L_SPLIT < 2 || wg == 0) Y_PAIR(p2, 0, p2, 1, 0, 128, );
            if (L_SPLIT < 1 || wg == 0) Y_PAIR(p2, 0, p2, 1, 1, 128, );
            issue(p3, Int<192>(), 0, 12, false, true);
            if (sig_local) mbar_arrive(bar_end);
            if (L_SPLIT >= 2 && wg == 1) Y_PAIR(p2, 0, p2, 1, 0, 128, );
            if (L_SPLIT >= 1 && wg == 1) Y_PAIR(p2, 0, p2, 1, 1, 128, );
            wgmma_wait<0>();
            if (sig_local) TRX(27 + wg);
            #pragma unroll
            for (int i = 0; i < 2; i++) red_add_bf16x8(Y_ADDR(12 + i), Y_WORD(p3, i, 0), Y_WORD(p3, i, 1), Y_WORD(p3, i, 2), Y_WORD(p3, i, 3));
            if (sig_local) TR(29 + wg);
        } else {
        constexpr int IT0 = 7 + KB_EARLY;
        auto load_af = [&](int j) {
            wait_full(IT0 - 3 + j);
            #pragma unroll
            for (int k = 0; k < 4; k++) ldsm_x4((a_frag ^ (k << 5)) + ((IT0 - 3 + j) & 3) * SLOT_BYTES, af[4 * j + k][0], af[4 * j + k][1], af[4 * j + k][2], af[4 * j + k][3]);
        };
        wait_full(IT0 - 3);
        wgmma_wait<0>();
        release((IT0 - 4) & 3);
        done(IT0 - 4);
        if (wg == 1) {
            load_af(0); load_af(1); load_af(2);
            asm volatile("bar.sync 5, 256;" ::: "memory");
            release((bar_af - bar_empty) / 8);
            #pragma unroll
            for (int it = IT0 - 3; it < IT0; it++) {
                if (it == IT0 - 1) { wgmma_wait<1>(); release((it - 2) & 3); }
                wgmma_fence();
                #pragma unroll
                for (int k = 0; k < 4; k++) wgmma_rs_n224<0>(acc, af[4 * (it - IT0 + 3) + k], dB + (it & 3) * (SLOT_BYTES >> 4) + 2 * k, 1);
                wgmma_commit();
            }
            asm volatile("bar.arrive 9, 256;" ::: "memory");
            wgmma_wait<1>();
            release((IT0 - 2) & 3);
            wgmma_wait<0>();
            release((IT0 - 1) & 3);
            if (sig_local) { mbar_arrive(bar_end); TRL(28); }
            const uint32_t t1 = clk32() + TP(RED_AT1);
            auto pause = [&](int i) { while ((int)(clk32() - t1) < i * TP(RED_GAP1)) { } };
            #pragma unroll
            for (int i = 0; i < 2; i++) { pause(i); red_add_bf16x8(Y_ADDR(12 + i), Y_WORD(acc, 12 + i, 0), Y_WORD(acc, 12 + i, 1), Y_WORD(acc, 12 + i, 2), Y_WORD(acc, 12 + i, 3)); }
            #pragma unroll
            for (int i = 0; i < 6; i++) { pause(2 + 2 * i); Y_PAIR(acc, i & 6, acc, (i & 6) + 1, i & 1, 32 * (i & 6), pause(3 + 2 * i)); }
            if (sig_local) TRX(30);
        } else {
            float lo[64], hi[48];
            #pragma unroll
            for (int i = 0; i < 48; i++) asm volatile("mov.b32 %0, %1;" : "=f"(hi[i]) : "f"(acc[64 + i]));
            #pragma unroll
            for (int i = 0; i < 64; i++) asm volatile("mov.b32 %0, %1;" : "=f"(lo[i]) : "f"(acc[i]));
            #pragma unroll
            for (int it = IT0 - 3; it < IT0; it++) {
                if (it == IT0 - 1) {
                    #pragma unroll
                    for (int k = 0; k < E_FILL; k++) wgmma_n96<1, 0>(hi, dA + ((IT0 - 3 + (k >> 2)) & 3) * (SLOT_BYTES >> 4) + 2 * (k & 3), dB + ((IT0 - 3 + (k >> 2)) & 3) * (SLOT_BYTES >> 4) + 1024 + 2 * (k & 3), 1);
                }
                if (it > IT0 - 3) wait_full(it);
                wgmma_fence();
                #pragma unroll
                for (int k = 0; k < 4; k++) wgmma_n128<1, 0>(lo, dA + (it & 3) * (SLOT_BYTES >> 4) + 2 * k, dB + (it & 3) * (SLOT_BYTES >> 4) + 2 * k, 1);
            }
            wgmma_commit();
            #define E_RED(i) do { if ((i) < 8) red_add_bf16x8(Y_ADDR(i), Y_WORD(lo, (i) & 7, 0), Y_WORD(lo, (i) & 7, 1), Y_WORD(lo, (i) & 7, 2), Y_WORD(lo, (i) & 7, 3)); \
                                  else red_add_bf16x8(Y_ADDR(i), Y_WORD(hi, (i) & 7, 0), Y_WORD(hi, (i) & 7, 1), Y_WORD(hi, (i) & 7, 2), Y_WORD(hi, (i) & 7, 3)); } while (0)
            #pragma unroll
            for (int j = E_FILL; j < 12; j++) {
                const int it = IT0 - 3 + (j >> 2), k = j & 3;
                if (j == E_FILL + E_SPLIT) {
                    wgmma_commit();
                    wgmma_wait<1>();
                    if (sig_local) TR(14);
                    #pragma unroll
                    for (int i = 0; i < RED_A; i++) E_RED(i);
                    wgmma_fence();
                }
                wgmma_n96<1, 0>(hi, dA + (it & 3) * (SLOT_BYTES >> 4) + 2 * k, dB + (it & 3) * (SLOT_BYTES >> 4) + 1024 + 2 * k, 1);
            }
            wgmma_commit();
            asm volatile("bar.arrive 5, 256;" ::: "memory");
            #pragma unroll
            for (int i = RED_A; i < RED_FAST; i++) E_RED(i);
            wgmma_wait<0>();
            release((bar_af - bar_empty) / 8); release((IT0 - 3) & 3); release((IT0 - 2) & 3); release((IT0 - 1) & 3);
            if (sig_local) TRL(27);
            const uint32_t t1 = clk32();
            #pragma unroll
            for (int i = RED_FAST; i < 14 - E_LATE; i++) {
                while ((int)(clk32() - t1) < (i - RED_FAST) * TP(RED_GAP)) { }
                E_RED(i);
            }
            if (sig_local) TR(29);
            float o0[56], o1[56];
            auto out_issue = [&](float (&oa)[56], int p, int j) {
                wgmma_fence();
                #pragma unroll
                for (int k = 0; k < (ABL & 32 ? 0 : 4); k++) wgmma_n112<1, 1, 8>(oa, dB + (63 << 16) + ((OUT_O(p, j) - SLOT_A) >> 4) + 128 * k, dB + ((((OUT_B(j) - OUT_A(j)) >> 4) - 1) << 16) + ((OUT_A(j) - SLOT_A) >> 4) + 128 * k, (j | k) != 0);
                wgmma_commit();
            };
            const uint32_t wa = pin(sb + w * 2048 + ((m & 1) * 8 + i8) * 128 + (((m >> 1) ^ i8) << 4)), ra = pin(sb + w * 2048 + m * 128 + ((i8 ^ m) << 4));
            auto stage = [&](float (&oa)[56], int buf, int u) {
                stsm_x4((wa ^ ((u & 3) << 5)) + buf + (u >> 2) * 8192, pack_bf16(oa[8 * u], oa[8 * u + 1]), pack_bf16(oa[8 * u + 2], oa[8 * u + 3]),
                        pack_bf16(oa[8 * u + 4], oa[8 * u + 5]), pack_bf16(oa[8 * u + 6], oa[8 * u + 7]));
            };
            __nv_bfloat16* const op = pin(out + (size_t)(mt * 128 + 1 + w * 32 + 2 * m) * NOUT + (sub & 3) * 64 + i8 * 8);
            const int c1 = 256 - (sub & 3) * 16;
            asm volatile("bar.sync 9, 256;" ::: "memory");
            #pragma unroll
            for (int j = 0; j < 7; j++) {
                if (j == 0 || j == 2 || j == 4) { mbar_wait(bar_abf + 4 * j, 1); if (sig_local) TR(128 + IT0 + j); }
                out_issue(o0, 0, j);
                if (j < E_LATE) E_RED(14 - E_LATE + j);
                if (j == 2) { wgmma_wait<2>(); if (sig_local) mbar_arrive(bar_ab6); }
            }
            #undef E_RED
            #pragma unroll
            for (int j = 0; j < 7; j++) {
                if (j % 3 == 0) { mbar_wait(bar_abf + 24 + 8 * (j / 3), 1); if (sig_local) TR(192 + IT0 + j); }
                out_issue(o1, 1, j);
                if (j == 1) { wgmma_wait<2>(); if (sig_local) TR(31); }
                if (j >= 1 && j < 5) {
                    stage(o0, OUT_O(0, 1), 2 * j - 2);
                    if (j < 4) stage(o0, OUT_O(0, 1), 2 * j - 1);
                    if (j == 2 || j == 4) { __syncwarp(); if (lane == 0) mbar_arrive(bar_qkv + 4 * j - 8); }
                }
            }
            if (sig_local) mbar_arrive(bar_end);
            wgmma_wait<0>();
            if (sig_local) TRL(32);
            #pragma unroll
            for (int c = 0; c < 2; c++) {
                #pragma unroll
                for (int u = 4 * c; u < (c ? 7 : 4); u++) stage(o1, 0, u);
                __syncwarp();
                #pragma unroll
                for (int q = 0; q < 4; q++) {
                    uint4 v;
                    asm volatile("ld.shared.v4.u32 {%0, %1, %2, %3}, [%4];" : "=r"(v.x), "=r"(v.y), "=r"(v.z), "=r"(v.w) : "r"((ra ^ ((q & 1) << 6)) + c * 8192 + q * 512) : "memory");
                    if (c == 0 || i8 < 6) *reinterpret_cast<uint4*>(op + q * 8 * NOUT + (c ? c1 : 0)) = v;
                }
            }
        }
        }
        #undef Y_PAIR
        #undef Y_WORD
        #undef Y_ADDR
        if (sig_local) { TRX(33 + wg); if (wg == (late ? 1 : 0)) TRG(104); }
        TR_END();
    }
}

typedef CUresult (*EncodeFn)(CUtensorMap*, CUtensorMapDataType, cuuint32_t, void*, const cuuint64_t*, const cuuint64_t*,
                             const cuuint32_t*, const cuuint32_t*, CUtensorMapInterleave, CUtensorMapSwizzle,
                             CUtensorMapL2promotion, CUtensorMapFloatOOBfill);

void make_map(EncodeFn fn, CUtensorMap* tm, const void* ptr, uint64_t inner, uint64_t outer, uint32_t box_inner, uint32_t box_outer,
              CUtensorMapSwizzle sw = CU_TENSOR_MAP_SWIZZLE_128B, uint64_t clip = 0) {
    cuuint64_t gd[2] = {clip ? clip : inner, outer};
    cuuint64_t gs[1] = {inner * 2};
    cuuint32_t bd[2] = {box_inner, box_outer};
    cuuint32_t es[2] = {1, 1};
    fn(tm, CU_TENSOR_MAP_DATA_TYPE_BFLOAT16, 2, const_cast<void*>(ptr), gd, gs, bd, es, CU_TENSOR_MAP_INTERLEAVE_NONE,
       sw, CU_TENSOR_MAP_L2_PROMOTION_L2_128B, CU_TENSOR_MAP_FLOAT_OOB_FILL_NONE);
}
void make_map3(EncodeFn fn, CUtensorMap* tm, const void* ptr, uint64_t n0, uint64_t n1, uint64_t s1, uint64_t n2, uint64_t s2, uint32_t b1, uint32_t b2) {
    cuuint64_t gd[3] = {n0, n1, n2};
    cuuint64_t gs[2] = {s1 * 2, s2 * 2};
    cuuint32_t bd[3] = {64, b1, b2};
    cuuint32_t es[3] = {1, 1, 1};
    fn(tm, CU_TENSOR_MAP_DATA_TYPE_BFLOAT16, 3, const_cast<void*>(ptr), gd, gs, bd, es, CU_TENSOR_MAP_INTERLEAVE_NONE,
       CU_TENSOR_MAP_SWIZZLE_128B, CU_TENSOR_MAP_L2_PROMOTION_L2_128B, CU_TENSOR_MAP_FLOAT_OOB_FILL_NONE);
}
void make_map_perm(EncodeFn fn, CUtensorMap* tm, void* ptr, uint32_t n) {
    cuuint64_t gd[5] = {SEQ, 2, 4, 4, 28};
    cuuint64_t gs[4] = {SEQ * 2, 8 * SEQ * 2, 2 * SEQ * 2, 32 * SEQ * 2};
    cuuint32_t bd[5] = {64, 2, 4, 4, n};
    cuuint32_t es[5] = {1, 1, 1, 1, 1};
    fn(tm, CU_TENSOR_MAP_DATA_TYPE_BFLOAT16, 5, ptr, gd, gs, bd, es, CU_TENSOR_MAP_INTERLEAVE_NONE,
       CU_TENSOR_MAP_SWIZZLE_128B, CU_TENSOR_MAP_L2_PROMOTION_L2_128B, CU_TENSOR_MAP_FLOAT_OOB_FILL_NONE);
}

}

extern "C" void kernel_launch(void* const* d_in, const int* in_sizes, int n_in, void* d_out, int out_size) {
    (void)in_sizes; (void)n_in; (void)out_size;
    static EncodeFn fn = nullptr;
    static void* p_abT = nullptr;
    if (!fn) {
        void* p = nullptr; cudaDriverEntryPointQueryResult qr;
        cudaGetDriverEntryPoint("cuTensorMapEncodeTiled", &p, cudaEnableDefault, &qr);
        fn = (EncodeFn)p;
        cudaGetSymbolAddress(&p_abT, g_abT);
        cudaFuncSetAttribute(fused_kernel, cudaFuncAttributeMaxDynamicSharedMemorySize, SMEM_BYTES);
    }
    TMaps tm;
    make_map3(fn, &tm.xA3, d_in[0], DM, SEQ / 2, 2 * DM, 2, DM, 64, 2);
    make_map3(fn, &tm.wqkv3, d_in[1], DM, DM, 3 * DM, 3, DM, 32, 3);
    make_map(fn, &tm.wo64, d_in[2], DM, DM, 64, 64);
    make_map3(fn, &tm.outA, d_out, 64, SEQ / 2, 2 * NOUT, 4, 64, 64, 1);
    make_map3(fn, &tm.outB, (const __nv_bfloat16*)d_out + 256, 48, SEQ / 2, 2 * NOUT, 4, 48, 64, 1);
    make_map(fn, &tm.xB, d_in[3], DM, SEQ, 64, 128);
    make_map(fn, &tm.wre, d_in[4], SEQ, SEQ, 64, 128);
    make_map(fn, &tm.wim, d_in[5], SEQ, SEQ, 64, 128);
    make_map(fn, &tm.wreH, d_in[4], SEQ, SEQ, 64, 64);
    make_map(fn, &tm.wimH, d_in[5], SEQ, SEQ, 64, 64);
    make_map(fn, &tm.wdre, d_in[6], DM, DM, 64, 112);
    make_map(fn, &tm.wdim, d_in[7], DM, DM, 64, 112);
    make_map_perm(fn, &tm.abP4, p_abT, 4);
    make_map_perm(fn, &tm.abP3, p_abT, 3);
    make_map(fn, &tm.abH, p_abT, SEQ, 896, 64, 16);
    make_map(fn, &tm.ab32, p_abT, SEQ, 896, 64, 32);
    make_map(fn, &tm.ab80, p_abT, SEQ, 896, 64, 80);
    fused_kernel<<<NCTA, 384, SMEM_BYTES, cudaStreamPerThread>>>((__nv_bfloat16*)d_out,
        tm);
}
```

```cpp
#include <cuda_runtime.h>
#include <cuda_bf16.h>
#include <cuda.h>
#include <stdint.h>

namespace {

constexpr int SEQ = 2048, DM = 448, NOUT = 896;
constexpr int NCTA = 128;
constexpr int SLOT_A = 16384, SLOT_B = 28672, SLOT_BYTES = SLOT_A + SLOT_B, NSLOT = 4;
constexpr int AB_BYTES = SLOT_A + 112 * 128;
constexpr int STG_OFF = NSLOT * SLOT_BYTES;
constexpr int STG_BYTES = 7 * 7168;
constexpr int KV_PITCH = 240;
constexpr int KV_OFF = 2 * 7168, KV_PAR = 72 * KV_PITCH;
#define OUT_L2 1
#define OUT_A(j) (((j) < 2 ? 48 + 8 * (j) : (j) < 4 ? 8 * (j) - 16 : (j) == 4 ? 136 : 80 + 8 * (j)) * 1024)
#define OUT_B(j) (((j) == 0 ? 80 : 168 + 8 * (j)) * 1024)
#define OUT_O(p, j) (((p) ? ((j) < 3 ? 152 + 8 * (j) : 8 * (j) - 8) : ((j) < 2 ? 64 + 8 * (j) : (j) < 6 ? 72 + 8 * (j) : 144)) * 1024)
#define OUT_ST OUT_O(0, 0)
constexpr int BAR_OFF = STG_OFF + STG_BYTES;
constexpr int TR_OFF = BAR_OFF + 512;
constexpr int SMEM_BYTES = TR_OFF + 1024;
constexpr int SPIN_LIMIT = 1 << 24;
#define TUNE_LIST(X) \
    X(START_GAP1, 400, 50, 0, 900)   \
    X(START_GAP, 280, 30, 0, 500)   \
    X(PF0_N, 0, 1, 0, 3)   \
    X(PF0_AT, 1800, 200, 0, 3000)   \
    X(WARM_N, 3, 1, 0, 6)   \
    X(WARM_GAP, 150, 50, 50, 500)   \
    X(ZERO_GAP, 100, 50, 0, 300)   \
    X(ZERO_AT, 900, 200, 0, 2400)   \
    X(ABS_AT1, 500, 100, 0, 1000)   \
    X(ABS_AT, 1500, 150, 300, 3000)   \
    X(ABS_GAP, 60, 40, 0, 400)   \
    X(ABS_GAP2, 230, 40, 0, 400)   \
    X(ABS_GAP3, 100, 40, 0, 400)   \
    X(POLL_AT, 3100, 100, 2000, 4000)   \
    X(POLL_AT1, 3600, 150, 2000, 5000)   \
    X(POLL_AT2, 6300, 200, 4000, 8000)   \
    X(POLL_AT3, 9200, 200, 6000, 11000)   \
    X(OPOLL_AT, 15100, 200, 13000, 17500)   \
    X(OPOLL2, 500, 100, -1000, 1500)   \
    X(POLL_NS, 50, 100, 0, 800)   \
    X(OPOLL_NS, 100, 60, 0, 600)   \
    X(BIG_GAP, 250, 100, 0, 1000)   \
    X(W_GAP, 180, 100, 0, 900)   \
    X(HALO_WAIT, 350, 100, 0, 1500)   \
    X(O_GAP, 130, 60, 10, 600)   \
    X(PF_N, 0, 1, 0, 3)   \
    X(PF_E, 6, 1, 4, 13)   \
    X(PF_L, 14, 1, 4, 17)   \
    X(WO_AT, 7, 1, 5, 10)   \
    X(WB_AT, 10, 1, 10, 13)   \
    X(L_XAT, 13, 1, 10, 13)   \
    X(RED_GAP, 185, 30, 0, 300)   \
    X(RED_AT1, 0, 100, 0, 1000)   \
    X(RED_GAP1, 80, 30, 0, 300)   \

#define X(n, d, s, lo, hi) constexpr int n = d;
TUNE_LIST(X)
#undef X
#define TP(n) n
#define L_UP 1
#define ABL 0
#define BIG_ST 1
#define FLIP 1
#define URG(mt) ((((mt) >> 2) & 1) ^ FLIP)
#define AB_ST 7
#define AB_ST2 8
#define GAP_FLIP 1
#define L_PRE 1
#define E_FILL 2
#define KB_EARLY 14
#define O_N 2
#define QK_AT 10
#define WAIT_KIND 1
#define KV_FIRST 1
#define Q_ARR 11
#define E_SPLIT 7
#define RED_A 4
#define RED_FAST 6
#define L_ARR 11
#define PF0_ALL 0
#define OPOLL2_ON 1
#define E_LATE 2
#define L_SPLIT 0
#define ROLE2 1
#define ODD2 0
#define L_NB 4
#define L_ORD 1
#define START_N 2
#define REG_CONS 208
#define REG_AUX 88

struct __align__(64) TMaps { CUtensorMap xB, wdre, wdim, wre, wim, abP4, abP3, abH, ab32, ab80, wreH, wimH, wo64, xA3, wqkv3, outA, outB; };

__device__ __nv_bfloat16 g_abT[896 * SEQ];
__device__ uint4 g_o[SEQ * DM / 8];
__device__ uint4 g_halo[16 * 8 * 2 * 160];
__device__ unsigned g_flag_ab[40 * 32];
__device__ unsigned g_flag_o[16 * 32];
__device__ unsigned g_epoch[NCTA * 8];

__device__ __forceinline__ uint32_t smem_u32(const void* p) { return (uint32_t)__cvta_generic_to_shared(p); }
__device__ __forceinline__ uint32_t clk32() { uint32_t c; asm volatile("mov.u32 %0, %%clock;" : "=r"(c) :: "memory"); return c; }
__device__ __forceinline__ void give_up() { asm volatile("st.global.u32 [%0], 0;" :: "l"(0ull) : "memory"); }
__device__ __forceinline__ void mbar_init(uint32_t bar, uint32_t count) { asm volatile("mbarrier.init.shared::cta.b64 [%0], %1;" :: "r"(bar), "r"(count) : "memory"); }
__device__ __forceinline__ void mbar_expect_tx(uint32_t bar, uint32_t bytes) { asm volatile("mbarrier.arrive.expect_tx.shared::cta.b64 _, [%0], %1;" :: "r"(bar), "r"(bytes) : "memory"); }
__device__ __forceinline__ void mbar_arrive(uint32_t bar) { asm volatile("mbarrier.arrive.shared::cta.b64 _, [%0];" :: "r"(bar) : "memory"); }
__device__ __forceinline__ void mbar_arrive_remote(uint32_t bar, uint32_t cta) {
    asm volatile("{\n.reg .b32 ra;\nmapa.shared::cluster.u32 ra, %0, %1;\nmbarrier.arrive.shared::cluster.b64 _, [ra];\n}" :: "r"(bar), "r"(cta) : "memory");
}
__device__ __forceinline__ bool mbar_try_wait(uint32_t bar, uint32_t parity) {
    uint32_t ok;
    asm volatile("{\n.reg .pred p;\nmbarrier.try_wait.parity.shared::cta.b64 p, [%1], %2;\nselp.u32 %0, 1, 0, p;\n}" : "=r"(ok) : "r"(bar), "r"(parity) : "memory");
    return ok;
}
__device__ __forceinline__ bool mbar_test_wait(uint32_t bar, uint32_t parity) {
    uint32_t ok;
    asm volatile("{\n.reg .pred p;\nmbarrier.test_wait.parity.shared::cta.b64 p, [%1], %2;\nselp.u32 %0, 1, 0, p;\n}" : "=r"(ok) : "r"(bar), "r"(parity) : "memory");
    return ok;
}
#define WAIT_OP "pmevent 0;\nmbarrier.try_wait.parity.shared::cta.b64 p, [%0], %1;\n"
__device__ __forceinline__ void mbar_wait(uint32_t bar, uint32_t parity) {
    asm volatile("{\n.reg .pred p;\nWAIT:\n" WAIT_OP "@!p bra WAIT;\n}" :: "r"(bar), "r"(parity) : "memory");
}
__device__ __forceinline__ void mbar_wait_p(uint32_t bar, uint32_t parity) {
    asm volatile("{\n.reg .pred p;\nWAIT:\nmbarrier.try_wait.parity.shared::cta.b64 p, [%0], %1;\n@!p bra WAIT;\n}" :: "r"(bar), "r"(parity) : "memory");
}
__device__ __forceinline__ void mbar_wait_limit(uint32_t bar, uint32_t parity) {
    int it = 0;
    while (!mbar_try_wait(bar, parity)) { if (++it > SPIN_LIMIT) give_up(); }
}
__device__ __forceinline__ void tma_load(uint32_t dst, const CUtensorMap* tm, uint32_t bar, int c0, int c1) {
    asm volatile("cp.async.bulk.tensor.2d.shared::cluster.global.mbarrier::complete_tx::bytes [%0], [%1, {%3, %4}], [%2];"
        :: "r"(dst), "l"(tm), "r"(bar), "r"(c0), "r"(c1) : "memory");
}
__device__ __forceinline__ void tma_load_mc(uint32_t dst, const CUtensorMap* tm, uint32_t bar, int c0, int c1) {
    asm volatile("cp.async.bulk.tensor.2d.shared::cluster.global.mbarrier::complete_tx::bytes.multicast::cluster [%0], [%1, {%3, %4}], [%2], %5;"
        :: "r"(dst), "l"(tm), "r"(bar), "r"(c0), "r"(c1), "h"((uint16_t)3) : "memory");
}
__device__ __forceinline__ void tma_load3(uint32_t dst, const CUtensorMap* tm, uint32_t bar, int c0, int c1) {
    asm volatile("cp.async.bulk.tensor.3d.shared::cluster.global.mbarrier::complete_tx::bytes [%0], [%1, {%3, %4, %5}], [%2];"
        :: "r"(dst), "l"(tm), "r"(bar), "r"(c0), "r"(c1), "r"(0) : "memory");
}
__device__ __forceinline__ void tma_load3_mc(uint32_t dst, const CUtensorMap* tm, uint32_t bar, int c0, int c1, int c2) {
    asm volatile("cp.async.bulk.tensor.3d.shared::cluster.global.mbarrier::complete_tx::bytes.multicast::cluster [%0], [%1, {%3, %4, %6}], [%2], %5;"
        :: "r"(dst), "l"(tm), "r"(bar), "r"(c0), "r"(c1), "h"((uint16_t)3), "r"(c2) : "memory");
}
__device__ __forceinline__ void tma_prefetch(const CUtensorMap* tm, int c0, int c1) {
    asm volatile("cp.async.bulk.prefetch.tensor.2d.L2.global [%0, {%1, %2}];" :: "l"(tm), "r"(c0), "r"(c1) : "memory");
}
__device__ __forceinline__ void tma_prefetch3(const CUtensorMap* tm, int c0, int c1) {
    asm volatile("cp.async.bulk.prefetch.tensor.3d.L2.global [%0, {%1, %2, %3}];" :: "l"(tm), "r"(c0), "r"(c1), "r"(0) : "memory");
}
__device__ __forceinline__ void tma_store(const CUtensorMap* tm, uint32_t src, int c0, int c1) {
    asm volatile("cp.async.bulk.tensor.2d.global.shared::cta.bulk_group [%0, {%2, %3}], [%1];" :: "l"(tm), "r"(src), "r"(c0), "r"(c1) : "memory");
}
__device__ __forceinline__ void tma_store3(const CUtensorMap* tm, uint32_t src, int c1, int c2) {
    asm volatile("cp.async.bulk.tensor.3d.global.shared::cta.bulk_group [%0, {%2, %3, %4}], [%1];" :: "l"(tm), "r"(src), "r"(0), "r"(c1), "r"(c2) : "memory");
}
__device__ __forceinline__ void bulk_load(uint32_t dst, const void* src, uint32_t bytes, uint32_t bar) {
    asm volatile("cp.async.bulk.shared::cluster.global.mbarrier::complete_tx::bytes [%0], [%1], %2, [%3];" :: "r"(dst), "l"(src), "r"(bytes), "r"(bar) : "memory");
}
__device__ __forceinline__ void bulk_store(void* dst, uint32_t src, uint32_t bytes) {
    asm volatile("cp.async.bulk.global.shared::cta.bulk_group [%0], [%1], %2;" :: "l"(dst), "r"(src), "r"(bytes) : "memory");
}
__device__ __forceinline__ void tma_load5_mc(uint32_t dst, const CUtensorMap* tm, uint32_t bar, int c0, int c4) {
    asm volatile("cp.async.bulk.tensor.5d.shared::cluster.global.mbarrier::complete_tx::bytes.multicast::cluster [%0], [%1, {%3, %6, %6, %6, %4}], [%2], %5;"
        :: "r"(dst), "l"(tm), "r"(bar), "r"(c0), "r"(c4), "h"((uint16_t)3), "r"(0) : "memory");
}
__device__ __forceinline__ void red_add_bf16x8(__nv_bfloat16* p, uint32_t w0, uint32_t w1, uint32_t w2, uint32_t w3) {
    asm volatile("red.relaxed.gpu.global.add.noftz.v4.bf16x2 [%0], {%1, %2, %3, %4};" :: "l"(p), "r"(w0), "r"(w1), "r"(w2), "r"(w3) : "memory");
}
__device__ __forceinline__ void prefetch_tmap(const CUtensorMap* tm) { asm volatile("prefetch.tensormap [%0];" :: "l"(tm) : "memory"); }
__device__ __forceinline__ void cluster_arrive() { asm volatile("barrier.cluster.arrive.relaxed.aligned;" ::: "memory"); }
__device__ __forceinline__ void cluster_wait() { asm volatile("barrier.cluster.wait.aligned;" ::: "memory"); }
__device__ __forceinline__ void wgmma_fence() { asm volatile("wgmma.fence.sync.aligned;" ::: "memory"); }
__device__ __forceinline__ void wgmma_commit() { asm volatile("wgmma.commit_group.sync.aligned;" ::: "memory"); }
template<int N> __device__ __forceinline__ void wgmma_wait() { asm volatile("wgmma.wait_group.sync.aligned %0;" :: "n"(N) : "memory"); }
__device__ __forceinline__ void fence_async_smem() { asm volatile("fence.proxy.async.shared::cta;" ::: "memory"); }
__device__ __forceinline__ void fence_async_global() { asm volatile("fence.proxy.async.global;" ::: "memory"); }
__device__ __forceinline__ uint32_t desc_k(uint32_t addr) { return ((addr & 0x3FFFF) >> 4) | (1u << 16); }
__device__ __forceinline__ uint32_t desc_mn(uint32_t addr) { return ((addr & 0x3FFFF) >> 4) | ((8192u >> 4) << 16); }
template<int R> __device__ __forceinline__ void reg_set() {
    if (R > 168) asm volatile("setmaxnreg.inc.sync.aligned.u32 %0;" :: "n"(R));
    if (R < 168) asm volatile("setmaxnreg.dec.sync.aligned.u32 %0;" :: "n"(R));
}
__device__ __forceinline__ unsigned ld_acquire(const unsigned* p) { unsigned v; asm volatile("ld.acquire.gpu.global.u32 %0, [%1];" : "=r"(v) : "l"(p) : "memory"); return v; }
__device__ __forceinline__ unsigned ld_relaxed(const unsigned* p) { unsigned v; asm volatile("ld.relaxed.gpu.global.u32 %0, [%1];" : "=r"(v) : "l"(p) : "memory"); return v; }
__device__ __forceinline__ void st_release(unsigned* p, unsigned v) { asm volatile("fence.proxy.async.global;\nst.release.gpu.global.u32 [%0], %1;" :: "l"(p), "r"(v) : "memory"); }
__device__ __forceinline__ void red_release(unsigned* p, unsigned v) { asm volatile("fence.proxy.async.global;\nred.release.gpu.global.add.u32 [%0], %1;" :: "l"(p), "r"(v) : "memory"); }
__device__ __forceinline__ bool elect_one() {
    uint32_t pred;
    asm volatile("{\n.reg .pred p;\nelect.sync _|p, 0xffffffff;\nselp.u32 %0, 1, 0, p;\n}" : "=r"(pred));
    return pred;
}
__device__ __forceinline__ int pick3(int cta, int a, int b, int c) {
    int v;
    asm("{\n.reg .pred p, q;\nsetp.lt.s32 p, %1, 8;\nsetp.lt.s32 q, %1, 72;\nselp.b32 %0, %3, %4, q;\nselp.b32 %0, %2, %0, p;\n}" : "=&r"(v) : "r"(cta), "r"(a), "r"(b), "r"(c));
    return v;
}
template<typename T> __device__ __forceinline__ T pin(T v) {
    if constexpr (sizeof(T) == 8) asm volatile("" : "+l"(v) :: "memory"); else asm volatile("" : "+r"(v) :: "memory");
    return v;
}
__device__ __forceinline__ void bulk_commit() { asm volatile("cp.async.bulk.commit_group;" ::: "memory"); }
__device__ __forceinline__ void bulk_wait_all() { asm volatile("cp.async.bulk.wait_group 0;" ::: "memory"); }
__device__ __forceinline__ uint32_t pack_bf16(float lo, float hi) { uint32_t r; asm("cvt.rn.bf16x2.f32 %0, %1, %2;" : "=r"(r) : "f"(hi), "f"(lo)); return r; }
__device__ __forceinline__ float bf_lo(uint32_t w) { return __uint_as_float(w << 16); }
__device__ __forceinline__ float bf_hi(uint32_t w) { return __uint_as_float(w & 0xffff0000u); }
__device__ __forceinline__ void stsm_x4(uint32_t addr, uint32_t r0, uint32_t r1, uint32_t r2, uint32_t r3) {
    asm volatile("stmatrix.sync.aligned.m8n8.x4.shared.b16 [%0], {%1, %2, %3, %4};" :: "r"(addr), "r"(r0), "r"(r1), "r"(r2), "r"(r3) : "memory");
}
__device__ __forceinline__ void stsm_x2(uint32_t addr, uint32_t r0, uint32_t r1) {
    asm volatile("stmatrix.sync.aligned.m8n8.x2.shared.b16 [%0], {%1, %2};" :: "r"(addr), "r"(r0), "r"(r1) : "memory");
}
__device__ __forceinline__ void stsm_x4_t(uint32_t addr, uint32_t r0, uint32_t r1, uint32_t r2, uint32_t r3) {
    asm volatile("stmatrix.sync.aligned.m8n8.x4.trans.shared.b16 [%0], {%1, %2, %3, %4};" :: "r"(addr), "r"(r0), "r"(r1), "r"(r2), "r"(r3) : "memory");
}
__device__ __forceinline__ void stsm_x2_t(uint32_t addr, uint32_t r0, uint32_t r1) {
    asm volatile("stmatrix.sync.aligned.m8n8.x2.trans.shared.b16 [%0], {%1, %2};" :: "r"(addr), "r"(r0), "r"(r1) : "memory");
}
__device__ __forceinline__ uint32_t movm_t(uint32_t x) { uint32_t r; asm volatile("movmatrix.sync.aligned.m8n8.trans.b16 %0, %1;" : "=r"(r) : "r"(x)); return r; }
__device__ __forceinline__ void ldsm_x4(uint32_t addr, uint32_t& r0, uint32_t& r1, uint32_t& r2, uint32_t& r3) {
    asm volatile("ldmatrix.sync.aligned.m8n8.x4.shared.b16 {%0, %1, %2, %3}, [%4];" : "=r"(r0), "=r"(r1), "=r"(r2), "=r"(r3) : "r"(addr) : "memory");
}
__device__ __forceinline__ void ldsm_x4_t(uint32_t addr, uint32_t& r0, uint32_t& r1, uint32_t& r2, uint32_t& r3) {
    asm volatile("ldmatrix.sync.aligned.m8n8.x4.trans.shared.b16 {%0, %1, %2, %3}, [%4];" : "=r"(r0), "=r"(r1), "=r"(r2), "=r"(r3) : "r"(addr) : "memory");
}
__device__ __forceinline__ void mma16816(float (&d)[4], uint32_t a0, uint32_t a1, uint32_t a2, uint32_t a3, uint32_t b0, uint32_t b1) {
    asm("mma.sync.aligned.m16n8k16.row.col.f32.bf16.bf16.f32 {%0, %1, %2, %3}, {%4, %5, %6, %7}, {%8, %9}, {%0, %1, %2, %3};"
        : "+f"(d[0]), "+f"(d[1]), "+f"(d[2]), "+f"(d[3]) : "r"(a0), "r"(a1), "r"(a2), "r"(a3), "r"(b0), "r"(b1));
}
__device__ __forceinline__ void mma1688(float (&d)[4], uint32_t a0, uint32_t a1, uint32_t b0) {
    asm("mma.sync.aligned.m16n8k8.row.col.f32.bf16.bf16.f32 {%0, %1, %2, %3}, {%4, %5}, {%6}, {%0, %1, %2, %3};"
        : "+f"(d[0]), "+f"(d[1]), "+f"(d[2]), "+f"(d[3]) : "r"(a0), "r"(a1), "r"(b0));
}
__device__ __forceinline__ uint32_t max_bf16x2(uint32_t a, uint32_t b) { uint32_t r; asm("max.bf16x2 %0, %1, %2;" : "=r"(r) : "r"(a), "r"(b)); return r; }
__device__ __forceinline__ float bf16_round(float x) { return __bfloat162float(__float2bfloat16_rn(x)); }
__device__ __forceinline__ uint32_t lds32(uint32_t addr) { uint32_t v; asm volatile("ld.shared.u32 %0, [%1];" : "=r"(v) : "r"(addr)); return v; }
__device__ __forceinline__ float ex2_approx(float x) { float y; asm("ex2.approx.ftz.f32 %0, %1;" : "=f"(y) : "f"(x)); return y; }
__device__ __forceinline__ float rcp_approx(float x) { float y; asm("rcp.approx.ftz.f32 %0, %1;" : "=f"(y) : "f"(x)); return y; }
__device__ __forceinline__ void st_b128_relaxed(uint4* p, uint32_t w0, uint32_t w1, uint32_t w2, uint32_t w3) {
    asm volatile("{\n.reg .b128 t;\n.reg .b64 lo, hi;\nmov.b64 lo, {%1, %2};\nmov.b64 hi, {%3, %4};\nmov.b128 t, {lo, hi};\nst.relaxed.gpu.global.b128 [%0], t;\n}"
        :: "l"(p), "r"(w0), "r"(w1), "r"(w2), "r"(w3) : "memory");
}
__device__ __forceinline__ uint4 ld_b128_relaxed(const uint4* p) {
    uint4 v;
    asm volatile("{\n.reg .b128 t;\n.reg .b64 lo, hi;\nld.relaxed.gpu.global.b128 t, [%4];\nmov.b128 {lo, hi}, t;\nmov.b64 {%0, %1}, lo;\nmov.b64 {%2, %3}, hi;\n}"
        : "=r"(v.x), "=r"(v.y), "=r"(v.z), "=r"(v.w) : "l"(p) : "memory");
    return v;
}

template<int SA, int TB, int HA = 0x40000040, int M>
__device__ __forceinline__ void wgmma_n8(float (&d)[M], uint32_t da, uint32_t db, int scale_d) {
    asm volatile("{\n.reg .pred p;\n.reg .b32 hi, ha;\n.reg .b64 da, db;\nmov.b32 hi, 0x40000040;\nmov.b32 ha, %9;\nmov.b64 da, {%4, ha};\nmov.b64 db, {%5, hi};\nsetp.ne.b32 p, %6, 0;\n"
        "wgmma.mma_async.sync.aligned.m64n8k16.f32.bf16.bf16 "
        "{%0, %1, %2, %3}, "
        "da, db, p, %8, 1, 0, %7;\n}\n"
        : "+f"(d[0]), "+f"(d[1]), "+f"(d[2]), "+f"(d[3])
        : "r"(da), "r"(db), "r"(scale_d), "n"(TB), "n"(SA), "n"(HA));
}
template<int SA, int TB, int HA = 0x40000040, int M>
__device__ __forceinline__ void wgmma_n96(float (&d)[M], uint32_t da, uint32_t db, int scale_d) {
    asm volatile("{\n.reg .pred p;\n.reg .b32 hi, ha;\n.reg .b64 da, db;\nmov.b32 hi, 0x40000040;\nmov.b32 ha, %53;\nmov.b64 da, {%48, ha};\nmov.b64 db, {%49, hi};\nsetp.ne.b32 p, %50, 0;\n"
        "wgmma.mma_async.sync.aligned.m64n96k16.f32.bf16.bf16 "
        "{%0, %1, %2, %3, %4, %5, %6, %7, %8, %9, %10, %11, %12, %13, %14, %15, "
        "%16, %17, %18, %19, %20, %21, %22, %23, %24, %25, %26, %27, %28, %29, %30, %31, "
        "%32, %33, %34, %35, %36, %37, %38, %39, %40, %41, %42, %43, %44, %45, %46, %47}, "
        "da, db, p, %52, 1, 0, %51;\n}\n"
        : "+f"(d[0]), "+f"(d[1]), "+f"(d[2]), "+f"(d[3]), "+f"(d[4]), "+f"(d[5]), "+f"(d[6]), "+f"(d[7]),
          "+f"(d[8]), "+f"(d[9]), "+f"(d[10]), "+f"(d[11]), "+f"(d[12]), "+f"(d[13]), "+f"(d[14]), "+f"(d[15]),
          "+f"(d[16]), "+f"(d[17]), "+f"(d[18]), "+f"(d[19]), "+f"(d[20]), "+f"(d[21]), "+f"(d[22]), "+f"(d[23]),
          "+f"(d[24]), "+f"(d[25]), "+f"(d[26]), "+f"(d[27]), "+f"(d[28]), "+f"(d[29]), "+f"(d[30]), "+f"(d[31]),
          "+f"(d[32]), "+f"(d[33]), "+f"(d[34]), "+f"(d[35]), "+f"(d[36]), "+f"(d[37]), "+f"(d[38]), "+f"(d[39]),
          "+f"(d[40]), "+f"(d[41]), "+f"(d[42]), "+f"(d[43]), "+f"(d[44]), "+f"(d[45]), "+f"(d[46]), "+f"(d[47])
        : "r"(da), "r"(db), "r"(scale_d), "n"(TB), "n"(SA), "n"(HA));
}
template<int SA, int TB, int HA = 0x40000040, int M>
__device__ __forceinline__ void wgmma_n112(float (&d)[M], uint32_t da, uint32_t db, int scale_d) {
    asm volatile("{\n.reg .pred p;\n.reg .b32 hi, ha;\n.reg .b64 da, db;\nmov.b32 hi, 0x40000040;\nmov.b32 ha, %61;\nmov.b64 da, {%56, ha};\nmov.b64 db, {%57, hi};\nsetp.ne.b32 p, %58, 0;\n"
        "wgmma.mma_async.sync.aligned.m64n112k16.f32.bf16.bf16 "
        "{%0, %1, %2, %3, %4, %5, %6, %7, %8, %9, %10, %11, %12, %13, %14, %15, "
        "%16, %17, %18, %19, %20, %21, %22, %23, %24, %25, %26, %27, %28, %29, %30, %31, "
        "%32, %33, %34, %35, %36, %37, %38, %39, %40, %41, %42, %43, %44, %45, %46, %47, "
        "%48, %49, %50, %51, %52, %53, %54, %55}, "
        "da, db, p, %60, 1, 0, %59;\n}\n"
        : "+f"(d[0]), "+f"(d[1]), "+f"(d[2]), "+f"(d[3]), "+f"(d[4]), "+f"(d[5]), "+f"(d[6]), "+f"(d[7]),
          "+f"(d[8]), "+f"(d[9]), "+f"(d[10]), "+f"(d[11]), "+f"(d[12]), "+f"(d[13]), "+f"(d[14]), "+f"(d[15]),
          "+f"(d[16]), "+f"(d[17]), "+f"(d[18]), "+f"(d[19]), "+f"(d[20]), "+f"(d[21]), "+f"(d[22]), "+f"(d[23]),
          "+f"(d[24]), "+f"(d[25]), "+f"(d[26]), "+f"(d[27]), "+f"(d[28]), "+f"(d[29]), "+f"(d[30]), "+f"(d[31]),
          "+f"(d[32]), "+f"(d[33]), "+f"(d[34]), "+f"(d[35]), "+f"(d[36]), "+f"(d[37]), "+f"(d[38]), "+f"(d[39]),
          "+f"(d[40]), "+f"(d[41]), "+f"(d[42]), "+f"(d[43]), "+f"(d[44]), "+f"(d[45]), "+f"(d[46]), "+f"(d[47]),
          "+f"(d[48]), "+f"(d[49]), "+f"(d[50]), "+f"(d[51]), "+f"(d[52]), "+f"(d[53]), "+f"(d[54]), "+f"(d[55])
        : "r"(da), "r"(db), "r"(scale_d), "n"(TB), "n"(SA), "n"(HA));
}
template<int SA, int TB, int HA = 0x40000040, int M>
__device__ __forceinline__ void wgmma_n128(float (&d)[M], uint32_t da, uint32_t db, int scale_d) {
    asm volatile("{\n.reg .pred p;\n.reg .b32 hi, ha;\n.reg .b64 da, db;\nmov.b32 hi, 0x40000040;\nmov.b32 ha, %69;\nmov.b64 da, {%64, ha};\nmov.b64 db, {%65, hi};\nsetp.ne.b32 p, %66, 0;\n"
        "wgmma.mma_async.sync.aligned.m64n128k16.f32.bf16.bf16 "
        "{%0, %1, %2, %3, %4, %5, %6, %7, %8, %9, %10, %11, %12, %13, %14, %15, "
        "%16, %17, %18, %19, %20, %21, %22, %23, %24, %25, %26, %27, %28, %29, %30, %31, "
        "%32, %33, %34, %35, %36, %37, %38, %39, %40, %41, %42, %43, %44, %45, %46, %47, "
        "%48, %49, %50, %51, %52, %53, %54, %55, %56, %57, %58, %59, %60, %61, %62, %63}, "
        "da, db, p, %68, 1, 0, %67;\n}\n"
        : "+f"(d[0]), "+f"(d[1]), "+f"(d[2]), "+f"(d[3]), "+f"(d[4]), "+f"(d[5]), "+f"(d[6]), "+f"(d[7]),
          "+f"(d[8]), "+f"(d[9]), "+f"(d[10]), "+f"(d[11]), "+f"(d[12]), "+f"(d[13]), "+f"(d[14]), "+f"(d[15]),
          "+f"(d[16]), "+f"(d[17]), "+f"(d[18]), "+f"(d[19]), "+f"(d[20]), "+f"(d[21]), "+f"(d[22]), "+f"(d[23]),
          "+f"(d[24]), "+f"(d[25]), "+f"(d[26]), "+f"(d[27]), "+f"(d[28]), "+f"(d[29]), "+f"(d[30]), "+f"(d[31]),
          "+f"(d[32]), "+f"(d[33]), "+f"(d[34]), "+f"(d[35]), "+f"(d[36]), "+f"(d[37]), "+f"(d[38]), "+f"(d[39]),
          "+f"(d[40]), "+f"(d[41]), "+f"(d[42]), "+f"(d[43]), "+f"(d[44]), "+f"(d[45]), "+f"(d[46]), "+f"(d[47]),
          "+f"(d[48]), "+f"(d[49]), "+f"(d[50]), "+f"(d[51]), "+f"(d[52]), "+f"(d[53]), "+f"(d[54]), "+f"(d[55]),
          "+f"(d[56]), "+f"(d[57]), "+f"(d[58]), "+f"(d[59]), "+f"(d[60]), "+f"(d[61]), "+f"(d[62]), "+f"(d[63])
        : "r"(da), "r"(db), "r"(scale_d), "n"(TB), "n"(SA), "n"(HA));
}
template<int SA, int TB, int HA = 0x40000040, int M>
__device__ __forceinline__ void wgmma_n224(float (&d)[M], uint32_t da, uint32_t db, int scale_d) {
    asm volatile("{\n.reg .pred p;\n.reg .b32 hi, ha;\n.reg .b64 da, db;\nmov.b32 hi, 0x40000040;\nmov.b32 ha, %117;\nmov.b64 da, {%112, ha};\nmov.b64 db, {%113, hi};\nsetp.ne.b32 p, %114, 0;\n"
        "wgmma.mma_async.sync.aligned.m64n224k16.f32.bf16.bf16 "
        "{%0, %1, %2, %3, %4, %5, %6, %7, %8, %9, %10, %11, %12, %13, %14, %15, "
        "%16, %17, %18, %19, %20, %21, %22, %23, %24, %25, %26, %27, %28, %29, %30, %31, "
        "%32, %33, %34, %35, %36, %37, %38, %39, %40, %41, %42, %43, %44, %45, %46, %47, "
        "%48, %49, %50, %51, %52, %53, %54, %55, %56, %57, %58, %59, %60, %61, %62, %63, "
        "%64, %65, %66, %67, %68, %69, %70, %71, %72, %73, %74, %75, %76, %77, %78, %79, "
        "%80, %81, %82, %83, %84, %85, %86, %87, %88, %89, %90, %91, %92, %93, %94, %95, "
        "%96, %97, %98, %99, %100, %101, %102, %103, %104, %105, %106, %107, %108, %109, %110, %111}, "
        "da, db, p, %116, 1, 0, %115;\n}\n"
        : "+f"(d[0]), "+f"(d[1]), "+f"(d[2]), "+f"(d[3]), "+f"(d[4]), "+f"(d[5]), "+f"(d[6]), "+f"(d[7]),
          "+f"(d[8]), "+f"(d[9]), "+f"(d[10]), "+f"(d[11]), "+f"(d[12]), "+f"(d[13]), "+f"(d[14]), "+f"(d[15]),
          "+f"(d[16]), "+f"(d[17]), "+f"(d[18]), "+f"(d[19]), "+f"(d[20]), "+f"(d[21]), "+f"(d[22]), "+f"(d[23]),
          "+f"(d[24]), "+f"(d[25]), "+f"(d[26]), "+f"(d[27]), "+f"(d[28]), "+f"(d[29]), "+f"(d[30]), "+f"(d[31]),
          "+f"(d[32]), "+f"(d[33]), "+f"(d[34]), "+f"(d[35]), "+f"(d[36]), "+f"(d[37]), "+f"(d[38]), "+f"(d[39]),
          "+f"(d[40]), "+f"(d[41]), "+f"(d[42]), "+f"(d[43]), "+f"(d[44]), "+f"(d[45]), "+f"(d[46]), "+f"(d[47]),
          "+f"(d[48]), "+f"(d[49]), "+f"(d[50]), "+f"(d[51]), "+f"(d[52]), "+f"(d[53]), "+f"(d[54]), "+f"(d[55]),
          "+f"(d[56]), "+f"(d[57]), "+f"(d[58]), "+f"(d[59]), "+f"(d[60]), "+f"(d[61]), "+f"(d[62]), "+f"(d[63]),
          "+f"(d[64]), "+f"(d[65]), "+f"(d[66]), "+f"(d[67]), "+f"(d[68]), "+f"(d[69]), "+f"(d[70]), "+f"(d[71]),
          "+f"(d[72]), "+f"(d[73]), "+f"(d[74]), "+f"(d[75]), "+f"(d[76]), "+f"(d[77]), "+f"(d[78]), "+f"(d[79]),
          "+f"(d[80]), "+f"(d[81]), "+f"(d[82]), "+f"(d[83]), "+f"(d[84]), "+f"(d[85]), "+f"(d[86]), "+f"(d[87]),
          "+f"(d[88]), "+f"(d[89]), "+f"(d[90]), "+f"(d[91]), "+f"(d[92]), "+f"(d[93]), "+f"(d[94]), "+f"(d[95]),
          "+f"(d[96]), "+f"(d[97]), "+f"(d[98]), "+f"(d[99]), "+f"(d[100]), "+f"(d[101]), "+f"(d[102]), "+f"(d[103]),
          "+f"(d[104]), "+f"(d[105]), "+f"(d[106]), "+f"(d[107]), "+f"(d[108]), "+f"(d[109]), "+f"(d[110]), "+f"(d[111])
        : "r"(da), "r"(db), "r"(scale_d), "n"(TB), "n"(SA), "n"(HA));
}
template<int TB, int SA = 1>
__device__ __forceinline__ void wgmma_rs_n32(float (&d)[16], const uint32_t (&a)[4], uint32_t db, int scale_d) {
    asm volatile("{\n.reg .pred p;\n.reg .b32 hi;\n.reg .b64 db;\nmov.b32 hi, 0x40000040;\nmov.b64 db, {%20, hi};\nsetp.ne.b32 p, %21, 0;\n"
        "wgmma.mma_async.sync.aligned.m64n32k16.f32.bf16.bf16 "
        "{%0, %1, %2, %3, %4, %5, %6, %7, %8, %9, %10, %11, %12, %13, %14, %15}, "
        "{%16, %17, %18, %19}, db, p, %23, 1, %22;\n}\n"
        : "+f"(d[0]), "+f"(d[1]), "+f"(d[2]), "+f"(d[3]), "+f"(d[4]), "+f"(d[5]), "+f"(d[6]), "+f"(d[7]),
          "+f"(d[8]), "+f"(d[9]), "+f"(d[10]), "+f"(d[11]), "+f"(d[12]), "+f"(d[13]), "+f"(d[14]), "+f"(d[15])
        : "r"(a[0]), "r"(a[1]), "r"(a[2]), "r"(a[3]), "r"(db), "r"(scale_d), "n"(TB), "n"(SA));
}
template<int TB, int SA = 1>
__device__ __forceinline__ void wgmma_rs_n56(float (&d)[28], const uint32_t (&a)[4], uint32_t db, int scale_d) {
    asm volatile("{\n.reg .pred p;\n.reg .b32 hi;\n.reg .b64 db;\nmov.b32 hi, 0x40000040;\nmov.b64 db, {%32, hi};\nsetp.ne.b32 p, %33, 0;\n"
        "wgmma.mma_async.sync.aligned.m64n56k16.f32.bf16.bf16 "
        "{%0, %1, %2, %3, %4, %5, %6, %7, %8, %9, %10, %11, %12, %13, %14, %15, "
        "%16, %17, %18, %19, %20, %21, %22, %23, %24, %25, %26, %27}, "
        "{%28, %29, %30, %31}, db, p, %35, 1, %34;\n}\n"
        : "+f"(d[0]), "+f"(d[1]), "+f"(d[2]), "+f"(d[3]), "+f"(d[4]), "+f"(d[5]), "+f"(d[6]), "+f"(d[7]),
          "+f"(d[8]), "+f"(d[9]), "+f"(d[10]), "+f"(d[11]), "+f"(d[12]), "+f"(d[13]), "+f"(d[14]), "+f"(d[15]),
          "+f"(d[16]), "+f"(d[17]), "+f"(d[18]), "+f"(d[19]), "+f"(d[20]), "+f"(d[21]), "+f"(d[22]), "+f"(d[23]),
          "+f"(d[24]), "+f"(d[25]), "+f"(d[26]), "+f"(d[27])
        : "r"(a[0]), "r"(a[1]), "r"(a[2]), "r"(a[3]), "r"(db), "r"(scale_d), "n"(TB), "n"(SA));
}
template<int TB, int SA = 1>
__device__ __forceinline__ void wgmma_rs_n64(float (&d)[32], const uint32_t (&a)[4], uint32_t db, int scale_d) {
    asm volatile("{\n.reg .pred p;\n.reg .b32 hi;\n.reg .b64 db;\nmov.b32 hi, 0x40000040;\nmov.b64 db, {%36, hi};\nsetp.ne.b32 p, %37, 0;\n"
        "wgmma.mma_async.sync.aligned.m64n64k16.f32.bf16.bf16 "
        "{%0, %1, %2, %3, %4, %5, %6, %7, %8, %9, %10, %11, %12, %13, %14, %15, "
        "%16, %17, %18, %19, %20, %21, %22, %23, %24, %25, %26, %27, %28, %29, %30, %31}, "
        "{%32, %33, %34, %35}, db, p, %39, 1, %38;\n}\n"
        : "+f"(d[0]), "+f"(d[1]), "+f"(d[2]), "+f"(d[3]), "+f"(d[4]), "+f"(d[5]), "+f"(d[6]), "+f"(d[7]),
          "+f"(d[8]), "+f"(d[9]), "+f"(d[10]), "+f"(d[11]), "+f"(d[12]), "+f"(d[13]), "+f"(d[14]), "+f"(d[15]),
          "+f"(d[16]), "+f"(d[17]), "+f"(d[18]), "+f"(d[19]), "+f"(d[20]), "+f"(d[21]), "+f"(d[22]), "+f"(d[23]),
          "+f"(d[24]), "+f"(d[25]), "+f"(d[26]), "+f"(d[27]), "+f"(d[28]), "+f"(d[29]), "+f"(d[30]), "+f"(d[31])
        : "r"(a[0]), "r"(a[1]), "r"(a[2]), "r"(a[3]), "r"(db), "r"(scale_d), "n"(TB), "n"(SA));
}
template<int TB, int SA = 1>
__device__ __forceinline__ void wgmma_rs_n96(float (&d)[48], const uint32_t (&a)[4], uint32_t db, int scale_d) {
    asm volatile("{\n.reg .pred p;\n.reg .b32 hi;\n.reg .b64 db;\nmov.b32 hi, 0x40000040;\nmov.b64 db, {%52, hi};\nsetp.ne.b32 p, %53, 0;\n"
        "wgmma.mma_async.sync.aligned.m64n96k16.f32.bf16.bf16 "
        "{%0, %1, %2, %3, %4, %5, %6, %7, %8, %9, %10, %11, %12, %13, %14, %15, "
        "%16, %17, %18, %19, %20, %21, %22, %23, %24, %25, %26, %27, %28, %29, %30, %31, "
        "%32, %33, %34, %35, %36, %37, %38, %39, %40, %41, %42, %43, %44, %45, %46, %47}, "
        "{%48, %49, %50, %51}, db, p, %55, 1, %54;\n}\n"
        : "+f"(d[0]), "+f"(d[1]), "+f"(d[2]), "+f"(d[3]), "+f"(d[4]), "+f"(d[5]), "+f"(d[6]), "+f"(d[7]),
          "+f"(d[8]), "+f"(d[9]), "+f"(d[10]), "+f"(d[11]), "+f"(d[12]), "+f"(d[13]), "+f"(d[14]), "+f"(d[15]),
          "+f"(d[16]), "+f"(d[17]), "+f"(d[18]), "+f"(d[19]), "+f"(d[20]), "+f"(d[21]), "+f"(d[22]), "+f"(d[23]),
          "+f"(d[24]), "+f"(d[25]), "+f"(d[26]), "+f"(d[27]), "+f"(d[28]), "+f"(d[29]), "+f"(d[30]), "+f"(d[31]),
          "+f"(d[32]), "+f"(d[33]), "+f"(d[34]), "+f"(d[35]), "+f"(d[36]), "+f"(d[37]), "+f"(d[38]), "+f"(d[39]),
          "+f"(d[40]), "+f"(d[41]), "+f"(d[42]), "+f"(d[43]), "+f"(d[44]), "+f"(d[45]), "+f"(d[46]), "+f"(d[47])
        : "r"(a[0]), "r"(a[1]), "r"(a[2]), "r"(a[3]), "r"(db), "r"(scale_d), "n"(TB), "n"(SA));
}
template<int TB, int SA = 1>
__device__ __forceinline__ void wgmma_rs_n112(float (&d)[56], const uint32_t (&a)[4], uint32_t db, int scale_d) {
    asm volatile("{\n.reg .pred p;\n.reg .b32 hi;\n.reg .b64 db;\nmov.b32 hi, 0x40000040;\nmov.b64 db, {%60, hi};\nsetp.ne.b32 p, %61, 0;\n"
        "wgmma.mma_async.sync.aligned.m64n112k16.f32.bf16.bf16 "
        "{%0, %1, %2, %3, %4, %5, %6, %7, %8, %9, %10, %11, %12, %13, %14, %15, "
        "%16, %17, %18, %19, %20, %21, %22, %23, %24, %25, %26, %27, %28, %29, %30, %31, "
        "%32, %33, %34, %35, %36, %37, %38, %39, %40, %41, %42, %43, %44, %45, %46, %47, "
        "%48, %49, %50, %51, %52, %53, %54, %55}, "
        "{%56, %57, %58, %59}, db, p, %63, 1, %62;\n}\n"
        : "+f"(d[0]), "+f"(d[1]), "+f"(d[2]), "+f"(d[3]), "+f"(d[4]), "+f"(d[5]), "+f"(d[6]), "+f"(d[7]),
          "+f"(d[8]), "+f"(d[9]), "+f"(d[10]), "+f"(d[11]), "+f"(d[12]), "+f"(d[13]), "+f"(d[14]), "+f"(d[15]),
          "+f"(d[16]), "+f"(d[17]), "+f"(d[18]), "+f"(d[19]), "+f"(d[20]), "+f"(d[21]), "+f"(d[22]), "+f"(d[23]),
          "+f"(d[24]), "+f"(d[25]), "+f"(d[26]), "+f"(d[27]), "+f"(d[28]), "+f"(d[29]), "+f"(d[30]), "+f"(d[31]),
          "+f"(d[32]), "+f"(d[33]), "+f"(d[34]), "+f"(d[35]), "+f"(d[36]), "+f"(d[37]), "+f"(d[38]), "+f"(d[39]),
          "+f"(d[40]), "+f"(d[41]), "+f"(d[42]), "+f"(d[43]), "+f"(d[44]), "+f"(d[45]), "+f"(d[46]), "+f"(d[47]),
          "+f"(d[48]), "+f"(d[49]), "+f"(d[50]), "+f"(d[51]), "+f"(d[52]), "+f"(d[53]), "+f"(d[54]), "+f"(d[55])
        : "r"(a[0]), "r"(a[1]), "r"(a[2]), "r"(a[3]), "r"(db), "r"(scale_d), "n"(TB), "n"(SA));
}
template<int TB, int SA = 1>
__device__ __forceinline__ void wgmma_rs_n224(float (&d)[112], const uint32_t (&a)[4], uint32_t db, int scale_d) {
    asm volatile("{\n.reg .pred p;\n.reg .b32 hi;\n.reg .b64 db;\nmov.b32 hi, 0x40000040;\nmov.b64 db, {%116, hi};\nsetp.ne.b32 p, %117, 0;\n"
        "wgmma.mma_async.sync.aligned.m64n224k16.f32.bf16.bf16 "
        "{%0, %1, %2, %3, %4, %5, %6, %7, %8, %9, %10, %11, %12, %13, %14, %15, "
        "%16, %17, %18, %19, %20, %21, %22, %23, %24, %25, %26, %27, %28, %29, %30, %31, "
        "%32, %33, %34, %35, %36, %37, %38, %39, %40, %41, %42, %43, %44, %45, %46, %47, "
        "%48, %49, %50, %51, %52, %53, %54, %55, %56, %57, %58, %59, %60, %61, %62, %63, "
        "%64, %65, %66, %67, %68, %69, %70, %71, %72, %73, %74, %75, %76, %77, %78, %79, "
        "%80, %81, %82, %83, %84, %85, %86, %87, %88, %89, %90, %91, %92, %93, %94, %95, "
        "%96, %97, %98, %99, %100, %101, %102, %103, %104, %105, %106, %107, %108, %109, %110, %111}, "
        "{%112, %113, %114, %115}, db, p, %119, 1, %118;\n}\n"
        : "+f"(d[0]), "+f"(d[1]), "+f"(d[2]), "+f"(d[3]), "+f"(d[4]), "+f"(d[5]), "+f"(d[6]), "+f"(d[7]),
          "+f"(d[8]), "+f"(d[9]), "+f"(d[10]), "+f"(d[11]), "+f"(d[12]), "+f"(d[13]), "+f"(d[14]), "+f"(d[15]),
          "+f"(d[16]), "+f"(d[17]), "+f"(d[18]), "+f"(d[19]), "+f"(d[20]), "+f"(d[21]), "+f"(d[22]), "+f"(d[23]),
          "+f"(d[24]), "+f"(d[25]), "+f"(d[26]), "+f"(d[27]), "+f"(d[28]), "+f"(d[29]), "+f"(d[30]), "+f"(d[31]),
          "+f"(d[32]), "+f"(d[33]), "+f"(d[34]), "+f"(d[35]), "+f"(d[36]), "+f"(d[37]), "+f"(d[38]), "+f"(d[39]),
          "+f"(d[40]), "+f"(d[41]), "+f"(d[42]), "+f"(d[43]), "+f"(d[44]), "+f"(d[45]), "+f"(d[46]), "+f"(d[47]),
          "+f"(d[48]), "+f"(d[49]), "+f"(d[50]), "+f"(d[51]), "+f"(d[52]), "+f"(d[53]), "+f"(d[54]), "+f"(d[55]),
          "+f"(d[56]), "+f"(d[57]), "+f"(d[58]), "+f"(d[59]), "+f"(d[60]), "+f"(d[61]), "+f"(d[62]), "+f"(d[63]),
          "+f"(d[64]), "+f"(d[65]), "+f"(d[66]), "+f"(d[67]), "+f"(d[68]), "+f"(d[69]), "+f"(d[70]), "+f"(d[71]),
          "+f"(d[72]), "+f"(d[73]), "+f"(d[74]), "+f"(d[75]), "+f"(d[76]), "+f"(d[77]), "+f"(d[78]), "+f"(d[79]),
          "+f"(d[80]), "+f"(d[81]), "+f"(d[82]), "+f"(d[83]), "+f"(d[84]), "+f"(d[85]), "+f"(d[86]), "+f"(d[87]),
          "+f"(d[88]), "+f"(d[89]), "+f"(d[90]), "+f"(d[91]), "+f"(d[92]), "+f"(d[93]), "+f"(d[94]), "+f"(d[95]),
          "+f"(d[96]), "+f"(d[97]), "+f"(d[98]), "+f"(d[99]), "+f"(d[100]), "+f"(d[101]), "+f"(d[102]), "+f"(d[103]),
          "+f"(d[104]), "+f"(d[105]), "+f"(d[106]), "+f"(d[107]), "+f"(d[108]), "+f"(d[109]), "+f"(d[110]), "+f"(d[111])
        : "r"(a[0]), "r"(a[1]), "r"(a[2]), "r"(a[3]), "r"(db), "r"(scale_d), "n"(TB), "n"(SA));
}

#define TR(idx) do {} while (0)
#define TRL(idx) do {} while (0)
#define TRX(idx) do {} while (0)
#define TRG(idx) do {} while (0)
#define TR_END() do {} while (0)

template<int V> struct Int { static constexpr int value = V; };
constexpr float ATT_SCALE = 0.18898223650461361f;
constexpr float LOG2E = 1.4426950408889634f;
constexpr uint32_t MASKED = 0xce6ece6eu;

__global__ void __cluster_dims__(2, 1, 1) __launch_bounds__(384, 1)
fused_kernel(__nv_bfloat16* __restrict__ out,
    const __grid_constant__ TMaps tm) {
    extern __shared__ __align__(1024) uint8_t smem_raw[];
    const uint32_t sb = smem_u32(smem_raw);
    const uint32_t bars = sb + BAR_OFF;
    const uint32_t bar_full = bars, bar_empty = bars + 32, bar_abf = bars + 64  , bar_ab6 = bars + 120, bar_ab = bars + 128  , bar_free = bars + 296  , bar_halo = bars + 152;
    const uint32_t bar_o = bars + 160, bar_qkv = bars + 176  , bar_sf = bars + 200, bar_se = bar_sf + 32  ;
    const uint32_t bar_fl = bars + 256  , bar_go = bars + 240  , bar_end = bars + 192, bar_af = bars + 312;
    const uint32_t stg = sb + STG_OFF;
    const int cta = blockIdx.x, r = cta & 1, cl = cta >> 1;
    const int place = pick3(cta, 32 + 8 * cl, cl - 4, cl - 3 + ((cl * 37 - 36 * 37) >> 8));
    const int mt = (place & 7) * 2 + r;
    const int sub = place >> 3;
    const CUtensorMap* tmWd = sub < 4 ? &tm.wdre : &tm.wdim;
    uint32_t t_first = 0;
    if (threadIdx.x < 32 + (((uint32_t)(uintptr_t)tmWd | (ODD2 ? sb >> 20 : sb) | (mt << 6)) & 32) && elect_one()) {
        prefetch_tmap(tmWd); prefetch_tmap(&tm.xB);
        #pragma unroll
        for (int kb = 0; kb < START_N; kb++) {
            mbar_init(bar_abf + 8 * kb, 1);
            mbar_expect_tx(bar_abf + 8 * kb, AB_BYTES);
            tma_load(sb + kb * AB_BYTES + SLOT_A, tmWd, bar_abf + 8 * kb, kb * 64, (sub & 3) * 112);
            tma_load(sb + kb * AB_BYTES, &tm.xB, bar_abf + 8 * kb, kb * 64, mt * 128);
        }
        t_first = clk32();
    }
    const int tid = threadIdx.x, warp = __shfl_sync(0xffffffffu, tid >> 5, 0), lane = tid & 31;
    const bool late = sub < 4;
    const int nh = sub & 1, part = (sub >> 1) & 1;
    const int nj = late ? 32 - KB_EARLY : KB_EARLY;
    static_assert(KB_EARLY == 14, "order of the k-blocks");
    const uint32_t t0 = clk32();
    auto clear_out = [&]() {
        while ((int)(clk32() - t0) < TP(ZERO_AT)) { }
        uint4* zp = reinterpret_cast<uint4*>(out + (size_t)(mt * 128 + sub * 16 + (warp - 2) * 8) * NOUT + DM) + lane;
        #pragma unroll 1
        for (int j = 0; j < (ABL & 8 ? 0 : 8); j++) {
            while ((int)(clk32() - t0) < TP(ZERO_AT) + j * TP(ZERO_GAP)) { }
            zp[j * (NOUT / 8)] = make_uint4(0, 0, 0, 0);
            if (lane < 24) zp[j * (NOUT / 8) + 32] = make_uint4(0, 0, 0, 0);
        }
    };
    if (warp == 0) {
        if (elect_one()) {
            #pragma unroll
            for (int s = START_N; s < 7; s++) mbar_init(bar_abf + 8 * s, 1);
            #pragma unroll
            for (int s = 0; s < NSLOT; s++) { mbar_init(bar_full + 8 * s, 1); mbar_init(bar_empty + 8 * s, 4); }
            asm volatile("fence.mbarrier_init.release.cluster;" ::: "memory");
        }
        __syncwarp();
        cluster_arrive();
        if (elect_one()) {
            #pragma unroll 1
            for (int kb = START_N; kb < 7; kb++) {
                while ((int)(clk32() - t_first) < TP(START_GAP1) + (kb - START_N) * TP(START_GAP)) { }
                const uint32_t a = sb + kb * AB_BYTES, fb = bar_abf + 8 * kb;
                mbar_expect_tx(fb, AB_BYTES);
                tma_load(a, &tm.xB, fb, kb * 64, mt * 128);
                tma_load(a + SLOT_A, tmWd, fb, kb * 64, (sub & 3) * 112);
            }
            TR(2);
            prefetch_tmap(&tm.xA3); prefetch_tmap(&tm.wqkv3);
            if (TP(PF0_N) > 0) {
                while ((int)(clk32() - t_first) < TP(PF0_AT)) { }
                #pragma unroll 1
                for (int it = 0; it < TP(PF0_N); it++) {
                    if (PF0_ALL || (sub & 3) == it) tma_prefetch3(&tm.xA3, it * 64, mt * 64);
                    if (PF0_ALL || (mt >> 1) == it) tma_prefetch3(&tm.wqkv3, sub * 56 - (sub & 1) * 8, it * 64 + r * 32);
                }
            }
        }
        __syncwarp();
    } else if (warp < 4) {
        cluster_arrive();
        if (warp >= 2) clear_out();
    }
    if (warp < 4) {
      reg_set<REG_AUX>();
      const CUtensorMap* tmB = r ? &tm.abP3 : &tm.abP4;
      const uint32_t boff = SLOT_A + r * 16384;
      const int bgrp = part * 14 + nh * 7 + r * 4;
      if (warp == 0) {
        cluster_wait();
        if (elect_one()) {
        uint32_t slot = sb, fb = bar_full, par = 0;
        auto advance = [&]() { if (fb == bar_full + 24) { fb = bar_full; slot = sb; par ^= 1; } else { fb += 8; slot += SLOT_BYTES; } };
        const CUtensorMap* tmW = part ? &tm.wim : &tm.wre;
        const CUtensorMap* tmH = part ? &tm.wimH : &tm.wreH;
        const int qc = sub * 56 - (sub & 1) * 8;
        auto next_kc = [&](int kc, int wi) { return wi == 3 ? (late ? 14 * 64 : 2 * 64) : wi == nj / 2 - 1 ? (late ? 15 * 64 : 64) : kc + (FLIP && wi == 1 ? -768 : wi < nj / 2 ? 256 : 128); };
        #pragma unroll 1
        for (int it = 0; it < 7; it++) {
            mbar_wait_p(fb + 32, par);
            mbar_expect_tx(fb, SLOT_A + 3 * 8192);
            tma_load3(slot, &tm.xA3, fb, it * 64, mt * 64);
            tma_load3_mc(slot + SLOT_A + r * 12288, &tm.wqkv3, fb, qc, it * 64 + r * 32, 0);
            TRL(64 + it);
            if (r && it == 2) {
                const int c = (7 - sub) * 8 + (mt >> 1), c7 = (c * 37) >> 8;
                tma_prefetch3(&tm.xA3, (3 + (sub >> 1)) * 64, (mt - (sub & 1)) * 64);
                if (c7 < 8) tma_prefetch3(&tm.wqkv3, (c - 7 * c7) * 64, 192 + c7 * 32);
            }
            if (it == 1) { prefetch_tmap(tmW); prefetch_tmap(tmB); prefetch_tmap(tmH); }
            advance();
        }
        int kc = (late ? 1024 : 0) + 512 * FLIP;
        #pragma unroll 1
        for (int wi = 0; wi < nj - late; wi++) {
            mbar_wait_p(fb + 32, par);
            if (TP(W_GAP) && wi > 0 && wi < 4) { const uint32_t t1 = clk32() + TP(W_GAP); while ((int)(clk32() - t1) < 0) { } }
            mbar_expect_tx(fb, SLOT_BYTES);
            tma_load(slot, tmW, fb, kc, mt * 128);
            TR(224 + 7 + wi);
            if (wi >= 4) {
                if (wi == 4 || wi == nj / 2) mbar_wait(bar_fl + (wi == 4 ? 16 : 24), 0);
                tma_load5_mc(slot + boff, tmB, fb, kc, bgrp);
                TR(64 + 7 + wi);
            } else mbar_arrive(bar_go + 8 * wi);
            advance();
            kc = next_kc(kc, wi);
            if (wi == (late ? TP(PF_L) : TP(PF_E))) tma_prefetch(tmH, (late ? 29 : 13) * 64, mt * 128 + nh * 64);
            if (late) {
                if (wi == TP(L_XAT) - 1) {
                    mbar_wait(bar_se, 0);
                    mbar_expect_tx(bar_sf, SLOT_BYTES);
                    tma_load5_mc(stg + boff, tmB, bar_sf, 31 * 64, bgrp);
                }
                if (wi == TP(L_XAT)) tma_load(stg, tmW, bar_sf, 31 * 64, mt * 128);
            } else if (wi == TP(WB_AT)) {
                mbar_wait(bar_se, 0);
                #pragma unroll
                for (int j = OUT_L2; j < 6 + OUT_L2; j += 2) tma_load_mc(sb + OUT_B(j) + r * 8192, &tm.wo64, bar_abf, 256 + 48 * (sub & 3), (j + r) * 64);
            } else if (wi == TP(WO_AT) - 1) {
                const int c = mt * 4 + (sub & 3), c7 = (c * 37) >> 8;
                if (c < 49) tma_prefetch(&tm.wo64, (c - 7 * c7) * 64, c7 * 64); else prefetch_tmap(&tm.wo64);
            }
        }
        if (!late) {
            const uint4* const po = g_o + mt * 7168;
            const int ca = 64 * (sub & 3), cb = 256 + 48 * (sub & 3);
            auto load_w = [&](int d0, int c0, int j0, int d1, int c1, int j1, int g) { tma_load_mc(sb + (r ? d1 : d0), &tm.wo64, bar_abf + 8 * g, r ? c1 : c0, (r ? j1 : j0) * 64); };
            auto load_o = [&](int p, int j, int n, int g) { bulk_load(sb + OUT_O(p, j), po + p * 3584 + j * 512, n * 8192, bar_abf + 8 * g); };
            #pragma unroll
            for (int g = 0; g < 5; g++) mbar_expect_tx(bar_abf + 8 * g, (g == 0 ? 11 : g == 2 ? 5 : 4) * 8192);
            mbar_wait_p(bar_empty + 8, 1);
            load_w(OUT_A(0), ca, 0, OUT_A(1), ca, 1, 0);
            if (r == 0) load_w(OUT_B(0), cb, 0, 0, 0, 0, 0);
            TR(64 + 7 + KB_EARLY);
            mbar_wait_p(bar_fl + 32, 0);
            TR(3);
            load_o(0, 0, 2, 0);
            mbar_wait_p(bar_af, 0);
            load_w(OUT_A(2), ca, 2, OUT_A(3), ca, 3, 1); load_o(0, 2, 2, 1);
            if (r) load_w(0, 0, 0, OUT_A(4), ca, 4, 2);
            TR(64 + 7 + KB_EARLY + 1);
            mbar_wait_p(bar_empty + 16, 1);
            load_o(0, 4, 2, 2); load_w(OUT_A(5), ca, 5, OUT_A(6), ca, 6, 2);
            TR(64 + 7 + KB_EARLY + 2);
            mbar_wait_p(bar_empty + 24, 1);
            load_o(0, 6, 4, 3);
            TR(64 + 7 + KB_EARLY + 3);
            mbar_wait_p(bar_empty, 0);
            load_o(1, 3, 4, 4);
            TR(64 + 7 + KB_EARLY + 4);
        }
        mbar_arrive(bar_end);
        }
      } else {
        const unsigned epoch = ld_relaxed(&g_epoch[cta * 8]) + 1;
        cluster_wait();
        auto forward = [&](const unsigned* fl, unsigned target, auto first, uint32_t bar, uint32_t again) {
            for (int spin = 0; !__all_sync(0xffffffffu, (int)(ld_acquire(fl) - target) >= 0);) {
                if ((int)(clk32() - again) < 0) { while ((int)(clk32() - again) < 0) { } } else __nanosleep(target != epoch ? TP(OPOLL_NS) : TP(POLL_NS));
                if (++spin > SPIN_LIMIT) give_up();
            }
            if (elect_one()) {
                fence_async_global();
                if constexpr (decltype(first)::value == 2) { if (atomicExch(reinterpret_cast<unsigned*>(smem_raw + BAR_OFF + 144), 1u) == 0) mbar_arrive(bar); }
                else if constexpr (!decltype(first)::value) mbar_arrive(bar);
                else {
                    #pragma unroll
                    for (int i = 0; i < 2; i++) {
                        const int wi = 2 * (warp - 2) + i, sl = (wi + 3) & 3;
                        mbar_wait_limit(bar_go + 8 * wi, 0);
                        tma_load5_mc(sb + sl * SLOT_BYTES + boff, tmB, bar_full + 8 * sl, (late ? 1024 : 0) + 256 * (wi ^ 2 * FLIP), bgrp);
                        TR(64 + 7 + wi);
                        if (i == 0) { const uint32_t t1 = clk32() + TP(BIG_GAP); while ((int)(clk32() - t1) < 0) { } }
                    }
                }
            }
            __syncwarp();
        };
        const int frow = part * 4 + nh * 2 + (lane & 1), st0 = late ? 8 : 0;
        const int ft = late ? min(7 + (lane >> 1), 15) : min(lane >> 1, 6);
        const unsigned* const fl2 = &g_flag_ab[(32 + frow) * 32 + (late ? min(7 + (lane & 14), 15) : min(1 + (lane & 14), 5))];
        const unsigned* const fl3 = &g_flag_ab[(16 + 8 * (ft & 1) + frow) * 32 + ft];
        if (warp == 1) {
            if (elect_one()) {
                prefetch_tmap(&tm.abH); if (BIG_ST) { prefetch_tmap(&tm.ab80); prefetch_tmap(&tm.ab32); }
                const int e0 = pin(sub * 112 - (sub & 2) * 16), e1 = pin((sub & 3) == 2 ? 224 : 0);
                #pragma unroll 1
                for (int hf = 0; hf < 2; hf++) {
                    const int gap = pin(hf ? (r ? TP(ABS_GAP3) : TP(ABS_GAP2)) : (r ? TP(ABS_GAP) : 0)), sc = pin(mt * 128 + hf * 64);
                    const uint32_t src = pin(hf ? stg : sb + 7 * AB_BYTES);
                    unsigned* const fl = pin(&g_flag_ab[((hf ? 2 + r : r ? 4 : URG(mt)) * 8 + sub) * 32 + mt]);
                    mbar_wait(bar_ab + 8 * hf, 0);
                    fence_async_smem();
                    uint32_t t1 = clk32() + (hf ? 0 : r ? TP(ABS_AT) : URG(mt) * TP(ABS_AT1));
                    if (BIG_ST && (hf | r) == 0) {
                        if (URG(mt)) { while ((int)(clk32() - t1) < 0) { } }
                        TR(4);
                        tma_store(&tm.ab80, src + 4096, sc, e0 + 32);
                        tma_store(&tm.ab32, src, sc, e0 + e1);
                    } else
                    #pragma unroll
                    for (int i = 0; i < 7; i++) {
                        if (i == 0 || gap) { while ((int)(clk32() - t1) < 0) { } }
                        t1 += gap;
                        if (i == 0 && hf == 0) TR(4);
                        if (hf > r && i % 3 == 0 && i / 3 < TP(PF_N)) tma_prefetch(part ? &tm.wim : &tm.wre, (late ? 1024 : 0) + ((i / 3) ^ 2 * FLIP) * 256, (mt + nh) * 128);
                        tma_store(&tm.abH, src + i * 2048, sc, e0 + i * 16 + (i < 2 ? e1 : 0));
                    }
                    bulk_commit();
                    bulk_wait_all();
                    if (hf) TR(5);
                    mbar_arrive(bar_free + 8 * hf);
                    st_release(fl, epoch);
                    TR(hf ? 6 : 38);
                }
                uint4* const po = pin(g_o + mt * 7168 + sub * 448);
                mbar_wait(bar_o, 0);
                fence_async_smem();
                TR(9);
                {
                    uint32_t t2 = clk32();
                    #pragma unroll 1
                    for (int i = 0; i < 2 * O_N; i++) {
                        while ((int)(clk32() - t2) < 0) { }
                        t2 += TP(O_GAP);
                        bulk_store(po + (i >= O_N ? 3584 - 448 : 0) + i * (448 / O_N), stg + i * (7168 / O_N), 7168 / O_N);
                    }
                }
                bulk_commit();
                TR(62);
                bulk_wait_all();
                TR(111);
                mbar_arrive(bar_se); mbar_arrive_remote(bar_se, r ^ 1);
                red_release(&g_flag_o[mt * 32], 1);
                TR(17); TRG(102);
                if (!late) {
                    prefetch_tmap(&tm.outA); prefetch_tmap(&tm.outB);
                    #pragma unroll
                    for (int c = 0; c < 2; c++) {
                        mbar_wait(bar_qkv + 8 * c, 1);
                        fence_async_smem();
                        tma_store3(c ? &tm.outB : &tm.outA, sb + OUT_ST + c * 8192, mt * 64, sub & 3);
                    }
                    bulk_commit();
                    asm volatile("cp.async.bulk.wait_group.read 0;" ::: "memory");
                    TR(19);
                }
            }
            __syncwarp();
        } else {
            asm volatile("st.shared.u32 [%0], %1;" :: "r"(bars + 168), "r"(epoch) : "memory");
            if (OPOLL2_ON) asm volatile("st.shared.u32 [%0], %1;" :: "r"(bars + 144), "r"(0) : "memory");
            __syncwarp();
            if (lane == 0) mbar_arrive(bar_ab + 8);
            mbar_wait_limit(bar_ab, 0);
            const uint32_t ta = clk32();
            if (tid == 96) TRG(98);
            const bool rest = warp == 3 && __all_sync(0xffffffffu, (int)(ld_acquire(lane >= 22 ? fl2 : fl3) - epoch) >= 0);
            forward(&g_flag_ab[((warp - 2) * 8 + frow) * 32 + st0 + 4 * ((warp - 2) ^ FLIP) + (lane & 2)], epoch, Int<1>(), 0, ta + (warp == 2 ? TP(POLL_AT) : TP(POLL_AT1)));
            if (warp == 2) {
                const uint4* const hp = pin(g_halo + (max(mt - 1, 0) * 8 + sub) * 320 + lane);
                const uint32_t ha = pin(stg + KV_OFF + (lane & 7) * KV_PITCH + (lane >> 3) * 16);
                mbar_wait(mt > 0 ? bar_go + 24 : bar_qkv, 0);
                uint4 v[10];
                if (mt > 0) {
                    const uint32_t tq = clk32();
                    while ((int)(clk32() - tq) < TP(HALO_WAIT)) { }
                    #pragma unroll 1
                    for (;;) {
                        uint32_t bad = 0;
                        #pragma unroll
                        for (int j = 0; j < 10; j++) v[j] = ld_b128_relaxed(hp + j * 32);
                        #pragma unroll
                        for (int j = 0; j < 10; j++) bad |= v[j].w ^ epoch;
                        if (__all_sync(0xffffffffu, bad == 0) || (ABL & 1)) break;
                        __nanosleep(200);
                    }
                } else {
                    const uint32_t r0 = stg + KV_OFF + 8 * KV_PITCH + 112 + (lane & 3) * 4;
                    v[0].x = v[0].y = v[0].z = v[1].x = v[1].y = v[1].z = v[2].x = 0;
                    v[2].y = lds32(r0); v[2].z = lds32(r0 + 16); v[3].x = lds32(r0 + 32); v[3].y = lds32(r0 + 48); v[3].z = lds32(r0 + 64); v[4].x = lds32(r0 + 80); v[4].y = lds32(r0 + 96);
                    #pragma unroll
                    for (int j = 0; j < 5; j++) v[5 + j] = v[j];
                }
                mbar_wait(bar_free, 0);
                #pragma unroll
                for (int p = 0; p < 2; p++) {
                    const uint4* u = v + 5 * p;
                    stsm_x4(ha + p * KV_PAR, u[0].x, u[0].y, u[0].z, u[1].x);
                    stsm_x4(ha + p * KV_PAR + 64, u[1].y, u[1].z, u[2].x, u[2].y);
                    stsm_x4(ha + p * KV_PAR + 128, u[2].z, u[3].x, u[3].y, u[3].z);
                    stsm_x2(ha + p * KV_PAR + 192, u[4].x, u[4].y);
                }
                __syncwarp();
                if (lane == 0) { mbar_arrive(bar_halo); TR(10); TRG(100); }
                if (OPOLL2_ON && !late) {
                    mbar_wait(bar_ab + 8, 0);
                    const uint32_t at = ta + TP(OPOLL_AT) + TP(OPOLL2);
                    while ((int)(clk32() - at) < 0) { }
                    forward(&g_flag_o[mt * 32], epoch * 8, Int<2>(), bar_fl + 32, at);
                }
            } else {
                #pragma unroll 1
                for (int j = 2; j < (late ? 4 : 5); j++) {
                    const unsigned* const fl = j == 2 ? fl2 : j == 4 ? &g_flag_o[mt * 32] : lane < 24 ? fl3 : &g_flag_ab[(16 + 8 * r + (lane & 7)) * 32 + mt];
                    const uint32_t at = ta + (j == 2 ? TP(POLL_AT2) : j == 3 ? TP(POLL_AT3) : TP(OPOLL_AT));
                    if (!rest) { while ((int)(clk32() - at) < 0) { } }
                    if (OPOLL2_ON && j == 4) { mbar_wait(bar_ab + 8, 0); forward(fl, epoch * 8, Int<2>(), bar_fl + 32, at); } else
                    forward(fl, j == 4 ? epoch * 8 : epoch, Int<0>(), bar_fl + 8 * j, at);
                    if (lane == 0) TR(j == 3 ? 39 : j == 4 ? 13 : 35 + j);
                }
                mbar_wait_limit(bar_end, 0);
            }
            __syncwarp();
        }
      }
      TR_END();
    } else {
        if (tid == 128) {
            mbar_init(bar_ab6, 1); mbar_init(bar_ab, 4); mbar_init(bar_ab + 8, 6); mbar_init(bar_free, 1); mbar_init(bar_free + 8, 1); mbar_init(bar_qkv, 4); mbar_init(bar_qkv + 8, 4); mbar_init(bar_o, 8);
            mbar_init(bar_halo, 1); mbar_init(bar_end, 3);
            #pragma unroll
            for (int j = 0; j < 7; j++) mbar_init(bar_go + 8 * j, 1);
            mbar_init(bar_sf, 1); mbar_init(bar_se, 2); mbar_init(bar_af, 4);
            asm volatile("fence.mbarrier_init.release.cluster;" ::: "memory");
        }
        __syncwarp();
        cluster_arrive();
        if (warp >= 8) {
            float d[4];
            #pragma unroll 1
            for (int i = 0; i < TP(WARM_N); i++) {
                const uint32_t t1 = clk32();
                wgmma_fence();
                wgmma_n8<1, 0>(d, desc_k(sb + 7 * AB_BYTES), desc_k(sb + 7 * AB_BYTES), 0);
                wgmma_commit();
                wgmma_wait<0>();
                while ((int)(clk32() - t1) < TP(WARM_GAP)) { }
                __syncwarp();
            }
        }
        cluster_wait();
        const int wg = warp >> 3, w = warp & 3, cw = warp - 4;

        const bool sig_local = (tid & 127) == 0;
        const int i8 = lane & 7, m = lane >> 3;
        const bool sig = (tid & 95) == 0;
        uint32_t rel;
        asm("mapa.shared::cluster.u32 %0, %1, %2;" : "=r"(rel) : "r"(bar_empty), "r"(r ^ (w & 1)));
        auto done = [&](int it) { (void)it; if ((tid & 127) == 64) TRL(160 + it); };
        auto release = [&](int s) { if (sig) asm volatile("mbarrier.arrive.shared::cluster.b64 _, [%0];" :: "r"(rel + 8 * s) : "memory"); };
        const uint32_t dA = desc_k(sb + wg * 8192), dB = desc_k(sb + SLOT_A), dBt = desc_mn(sb + SLOT_A);
        const uint32_t a_frag = sb + wg * 8192 + (w * 16 + (lane & 15)) * 128 + (((lane >> 4) ^ i8) << 4);
        auto wait_full = [&](int it) { mbar_wait(bar_full + 8 * (it & 3), (it >> 2) & 1); if (sig_local) TR(128 + wg * 64 + it); };
        uint32_t kq[4][4], vq[14], qb[2][8];
        {
            float aq[28], ak[28], av[28];
            uint32_t mh0 = 0;
            uint32_t af[2][4][4];
            auto load_af = [&](int it) {
                wait_full(it);
                #pragma unroll
                for (int k = 0; k < 4; k++) ldsm_x4((a_frag ^ (k << 5)) + (it & 3) * SLOT_BYTES, af[it & 1][k][0], af[it & 1][k][1], af[it & 1][k][2], af[it & 1][k][3]);
            };
            uint32_t abw[28], base;
            auto stage_ab = [&](int j0, int j1) {
                #pragma unroll
                for (int j = j0; j < j1; j++) {
                    if (j < 7) stsm_x4_t(base + j * 2048, abw[4 * j], abw[4 * j + 1], abw[4 * j + 2], abw[4 * j + 3]);
                    else { __syncwarp(); if (lane == 0) mbar_arrive(bar_ab + 8 * wg); }
                }
            };
            {
                float bacc[56];
                base = pin((wg ? stg : sb + 7 * AB_BYTES) + (((2 * w + (m & 1)) ^ i8) << 4) + ((m >> 1) * 8 + i8) * 128);
                auto ab_loop = [&](auto sign) {
                auto ab_issue = [&](int kb) {
                    mbar_wait_p(bar_abf + 8 * kb, 0);
                    if (kb == 0 && wg == 1) asm volatile("bar.sync 3, 256;" ::: "memory");
                    if (sig_local) TR(112 + wg * 8 + kb);
                    wgmma_fence();
                    #pragma unroll
                    for (int k = 0; k < 4; k++) wgmma_n112<decltype(sign)::value, 0>(bacc, dA + kb * (AB_BYTES >> 4) + 2 * k, dB + kb * (AB_BYTES >> 4) + 2 * k, (kb | k) != 0);
                    wgmma_commit();
                    if (kb == 0 && wg == 0) asm volatile("bar.arrive 3, 256;" ::: "memory");
                };
                #pragma unroll
                for (int kb = 0; kb < 5; kb++) {
                    ab_issue(kb);
                    if (kb > 0) wgmma_wait<1>();
                    if (kb == 2 || kb == 3) release(kb - 2);
                }
                if (wg == 0) {
                    ab_issue(5);
                    ab_issue(6);
                    asm volatile("bar.arrive 4, 256;" ::: "memory");
                    wgmma_wait<2>();
                    release(2);
                } else {
                    uint32_t xf[8][4];
                    #pragma unroll
                    for (int j = 0; j < 8; j++) {
                        if ((j & 3) == 0) mbar_wait(bar_abf + 8 * (5 + (j >> 2)), 0);
                        ldsm_x4((a_frag ^ ((j & 3) << 5)) + (5 + (j >> 2)) * AB_BYTES, xf[j][0], xf[j][1], xf[j][2], xf[j][3]);
                    }
                    wgmma_wait<0>();
                    release(2);
                    asm volatile("bar.sync 4, 256;" ::: "memory");
                    wgmma_fence();
                    #pragma unroll
                    for (int j = 0; j < 8; j++) {
                        wgmma_rs_n112<0, decltype(sign)::value>(bacc, xf[j], dB + (5 + (j >> 2)) * (AB_BYTES >> 4) + 2 * (j & 3), 1);
                        if ((j & 3) == 3) wgmma_commit();
                    }
                }
                };
                if (sub >> 2) ab_loop(Int<-1>()); else ab_loop(Int<1>());
                wgmma_wait<1>();
                release(3);
                reg_set<REG_CONS>();
                if (wg == 1) load_af(0);
                wgmma_wait<0>();
                if (sig_local) TRX(21 + wg);
                if (AB_ST) { if (wg == 0) asm volatile("bar.arrive 3, 256;" ::: "memory"); else asm volatile("bar.sync 3, 256;" ::: "memory"); }
                #pragma unroll
                for (int j = 0; j < 28; j++) abw[j] = pack_bf16(bacc[2 * j], bacc[2 * j + 1]);
                stage_ab(0, AB_ST);
                if (wg == 0 || AB_ST == 7) stage_ab(AB_ST, 8);
            }
            const uint32_t dQ = dBt + (sub & 1);
            #pragma unroll
            for (int it = 0; it < 7; it++) {
                const uint32_t o = (it & 3) * (SLOT_BYTES >> 4);
                if (it > 0 || wg == 0) load_af(it);
                if (it == 5) mh0 = pin((lane & 3) < 2 ? 0xffffffffu : 0u);
                if (AB_ST < 7 && wg == 1) { if (it == 1) stage_ab(AB_ST, AB_ST2); if (it == 2) stage_ab(AB_ST2, 8); }
                wgmma_wait<0>();
                if (it > 0) { release((it - 1) & 3); done(it - 1); }
                if (it == 0 && sig_local) TRL(60 + wg);
                if (wg == 0) { if (it > 0) asm volatile("bar.sync 6, 256;" ::: "memory"); } else asm volatile("bar.sync 8, 256;" ::: "memory");
                wgmma_fence();
                #pragma unroll
                for (int j = 0; j < 12; j++) {
                    const int k = it < 6 || !KV_FIRST ? j / 3 : j < 8 ? j >> 1 : j - 8, x = it < 6 || !KV_FIRST ? j % 3 : j < 8 ? j & 1 : 2;
                    const uint32_t d = dQ + o + (k >> 1) * 768 + (k & 1) * 128;
                    if (j == Q_ARR) { if (wg == 0) asm volatile("bar.arrive 8, 256;" ::: "memory"); else asm volatile("bar.arrive 6, 256;" ::: "memory"); }
                    if (x == 0) wgmma_rs_n56<1>(ak, af[it & 1][k], d + 256, (it | k) != 0);
                    if (x == 1) wgmma_rs_n56<1>(av, af[it & 1][k], d + 512, (it | k) != 0);
                    if (x == 2) wgmma_rs_n56<1>(aq, af[it & 1][k], d, (it | k) != 0);
                    if (KV_FIRST && it == 6 && j == 7) wgmma_commit();
                }
                wgmma_commit();
            }
            uint4* const hp = pin(g_halo + (mt * 8 + sub) * 320 + wg * 160 + lane);
            mbar_wait(bar_ab + 8, 0);
            const uint32_t epoch = lds32(bars + 168);
            wgmma_wait<KV_FIRST>();
            #pragma unroll
            for (int j = 0; j < 16; j++) kq[j >> 2][j & 3] = pin(pack_bf16(ak[2 * (j - 2 * (j > 7))], ak[1 + 2 * (j - 2 * (j > 7))]));
            #pragma unroll
            for (int j = 0; j < 14; j++) vq[j] = pin(pack_bf16(av[2 * j], av[2 * j + 1]));
            if (w == 3 && !(ABL & 1)) {
                st_b128_relaxed(hp, kq[0][1], kq[0][3], kq[1][1], epoch);
                st_b128_relaxed(hp + 32, kq[1][3], kq[2][3], kq[3][1], epoch);
                st_b128_relaxed(hp + 64, kq[3][3], vq[1], vq[3], epoch);
                st_b128_relaxed(hp + 96, vq[5], vq[7], vq[9], epoch);
                st_b128_relaxed(hp + 128, vq[11], vq[13], 0u, epoch);
                if (lane == 0) TR(8);
            }
            wgmma_wait<0>();
            release(6 & 3);
            if (sig_local) TRX(23 + wg);
            #pragma unroll
            for (int j = 0; j < 14; j++) qb[j & 1][(j >> 1) + (j > 7)] = pin(pack_bf16(aq[2 * j], aq[2 * j + 1]));
            #pragma unroll
            for (int j = 0; j < 2; j++) { qb[j][4] = qb[j][3] & ~mh0; qb[j][3] &= mh0; }
        }
        float acc[112];
        const int it1 = 7 + nj;
        auto big_issue = [&](int slot, bool first) {
            wgmma_fence();
            #pragma unroll
            for (int k = 0; k < 4; k++) wgmma_n224<1, 0>(acc, dA + slot * (SLOT_BYTES >> 4) + 2 * k, dB + slot * (SLOT_BYTES >> 4) + 2 * k, !first || k != 0);
            wgmma_commit();
        };
        if (wg == 1) {
            asm volatile("bar.sync 7, 256;" ::: "memory");
            big_issue(3, true);
        } else {
            wait_full(7);
            asm volatile("bar.sync 6, 256;" ::: "memory");
            big_issue(3, true);
            asm volatile("bar.arrive 7, 256;" ::: "memory");
            if (sig_local) TR(20);
        }
        {
            auto plain = [&](int it) {
                wait_full(it); wgmma_wait<0>(); release((it - 1) & 3); done(it - 1); big_issue(it & 3, false);
                mbar_wait(bar_free, 0);
            };
            auto before_mma = [&](int it, int last) {
                if (wg == last) {
                    mbar_wait_limit(bar_full + 8 * (it & 3), (it >> 2) & 1);
                    if (sig_local) TR(128 + last * 64 + it);
                    asm volatile("bar.sync 2, 256;" ::: "memory");
                    wgmma_wait<0>();
                    release((it - 1) & 3);
                    done(it - 1);
                } else {
                    if (GAP_FLIP) { wgmma_wait<0>(); release((it - 1) & 3); }
                    asm volatile("bar.arrive 2, 256;" ::: "memory");
                }
            };
            auto after_mma = [&](int it, int last) {
                if (wg == (last ^ 1)) {
                    if (!GAP_FLIP) { wgmma_wait<0>(); release((it - 1) & 3); }
                    asm volatile("bar.sync 7, 256;" ::: "memory");
                    big_issue(it & 3, false);
                } else {
                    big_issue(it & 3, false);
                    asm volatile("bar.arrive 7, 256;" ::: "memory");
                }
            };
            const uint32_t kvw = stg + KV_OFF + wg * KV_PAR + (w * 16 + i8) * KV_PITCH;
            const uint32_t a_k = kvw + (m & 1) * 8 * KV_PITCH + (m >> 1) * 16, a_v = kvw + (m >> 1) * 8 * KV_PITCH + 112 + (m & 1) * 16;
            mbar_wait(bar_free, 0);
            #pragma unroll
            for (int u = 0; u < (ABL & 64 ? 0 : 3); u++) stsm_x4(a_k + 8 * KV_PITCH + 112 + u * 32, vq[4 * u], vq[4 * u + 1], vq[4 * u + 2], vq[4 * u + 3]);
            if (!(ABL & 64)) stsm_x2(a_k + 8 * KV_PITCH + 112 + 96, vq[12], vq[13]);
            plain(8);
            #pragma unroll
            for (int u = 0; u < (ABL & 64 ? 1 : 4); u++) stsm_x4(a_k + 8 * KV_PITCH + (2 * u - (u > 1)) * 16, kq[u][0], kq[u][1], kq[u][2], kq[u][3]);
            __syncwarp();
            if (lane == 0) mbar_arrive(bar_qkv + 8 * wg);
            if (sig_local) TR(25 + wg);
            uint32_t kp[4][4], vt[8][4], pb[4][2];
            auto load_v = [&](int n) {
                #pragma unroll
                for (int u = 0; u < 4; u++) {
                    if ((ABL & 64) && u > 0) { vt[2 * u + n][0] = vq[u]; vt[2 * u + n][1] = vq[u + 4]; vt[2 * u + n][2] = vq[u + 8]; vt[2 * u + n][3] = vq[u + n]; } else
                    ldsm_x4_t(a_v + n * 8 * KV_PITCH + (2 * u - (u > 1)) * 16, vt[2 * u + n][0], vt[2 * u + n][1], vt[2 * u + n][2], vt[2 * u + n][3]);
                }
            };
            load_v(1);
            plain(9);
            if (QK_AT > 10) plain(10);
            mbar_wait(w == 0 && !(ABL & 2) ? bar_halo : bar_qkv + 8 * wg, 0);
            #pragma unroll
            for (int u = 0; u < 4; u++) {
                if ((ABL & 64) && u > 0) { kp[u][0] = kq[u][1]; kp[u][1] = kq[u][0]; kp[u][2] = kq[u][3]; kp[u][3] = kq[u][2]; } else
                ldsm_x4(a_k + (2 * u - (u > 1)) * 16, kp[u][0], kp[u][1], kp[u][2], kp[u][3]);
            }
            if (sig_local) TR(54 + wg);
            before_mma(QK_AT, GAP_FLIP);
            float s[4][4];
            #pragma unroll
            for (int i = 0; i < 16; i++) s[i >> 2][i & 3] = 0.f;
            #pragma unroll
            for (int i = 0; i < (ABL & 4 ? 0 : 8); i++) {
                const int n = i & 1, h = (i >> 1) & 1, ks = 2 * h + (i >> 2);
                if (n) mma16816(s[i & 3], kq[ks][0], kq[ks][1], kq[ks][2], kq[ks][3], qb[1][2 * ks], qb[1][2 * ks + 1]);
                else mma16816(s[i & 3], kp[ks][0], kp[ks][1], kp[ks][2], kp[ks][3], qb[0][2 * ks], qb[0][2 * ks + 1]);
            }
            #pragma unroll
            for (int i = 0; i < 16; i++) asm volatile("" : "+f"(s[i >> 2][i & 3]) :: "memory");
            after_mma(QK_AT, GAP_FLIP);
            if (sig_local) TR(48 + wg);
            const int g = lane >> 2, t2 = 2 * (lane & 3);
            const uint32_t mlo = (t2 > g ? 0xffffu : 0u) | (t2 + 1 > g ? 0xffff0000u : 0u), before = (mt | w) == 0 ? mlo : 0u;
            uint32_t y[4], mx[2];
            #pragma unroll
            for (int i = 0; i < 4; i++) {
                const uint32_t x = pack_bf16(g > t2 ? s[i][0] : s[i][2], g > t2 + 1 ? s[i][1] : s[i][3]);
                y[i] = movm_t(pack_bf16(bf_lo(x) * ATT_SCALE, bf_hi(x) * ATT_SCALE));
                if (!(i & 1)) y[i] = (y[i] & ~before) | (MASKED & before);
            }
            #pragma unroll
            for (int h = 0; h < 2; h++) {
                mx[h] = max_bf16x2(__byte_perm(y[2 * h], y[2 * h + 1], 0x5410), __byte_perm(y[2 * h], y[2 * h + 1], 0x7632));
                mx[h] = pin(max_bf16x2(mx[h], __shfl_xor_sync(0xffffffffu, mx[h], 1)));
            }
            load_v(0);
            if (sig_local) TR(50 + wg);
            plain(QK_AT + 1);
            #pragma unroll
            for (int h = 0; h < 2; h++) mx[h] = max_bf16x2(mx[h], __shfl_xor_sync(0xffffffffu, mx[h], 2));
            #pragma unroll
            for (int i = 0; i < 4; i++) {
                const float mi = i & 1 ? bf_hi(mx[i >> 1]) : bf_lo(mx[i >> 1]);
                const float e0 = ex2_approx((bf_lo(y[i]) - mi) * LOG2E), e1 = ex2_approx((bf_hi(y[i]) - mi) * LOG2E);
                float sum = e0 + e1;
                sum += __shfl_xor_sync(0xffffffffu, sum, 1);
                sum += __shfl_xor_sync(0xffffffffu, sum, 2);
                const float inv = rcp_approx(sum);
                const uint32_t p = pack_bf16(e0 * inv, e1 * inv);
                pb[i][0] = pin(p & mlo); pb[i][1] = pin(p & ~mlo);
            }
            if (sig_local) TR(52 + wg);
            before_mma(QK_AT + 2, 0);
            float ao[8][4];
            #pragma unroll
            for (int i = 0; i < 8; i++) {
                ao[i][0] = ao[i][1] = ao[i][2] = ao[i][3] = 0.f;
                if (!(ABL & 4)) mma16816(ao[i], vt[i][0], vt[i][1], vt[i][2], vt[i][3], pb[(i >> 2) * 2 + (i & 1)][0], pb[(i >> 2) * 2 + (i & 1)][1]);
            }
            #pragma unroll
            for (int i = 0; i < 32; i++) asm volatile("" : "+f"(ao[i >> 2][i & 3]) :: "memory");
            after_mma(QK_AT + 2, 0);
            if (sig_local) TRX(11 + wg);
            if (g >= 4) { ao[2][2] = ao[4][0]; ao[2][3] = ao[4][1]; ao[3][2] = ao[5][0]; ao[3][3] = ao[5][1]; }
            mbar_wait(bar_free + 8, 0);
            const uint32_t orow = stg + wg * 7168 + (m >> 1) * 1024 + (w * 16 + (lane & 15)) * 16;
            stsm_x4_t(orow, pack_bf16(ao[0][0], ao[0][1]), pack_bf16(ao[1][0], ao[1][1]), pack_bf16(ao[0][2], ao[0][3]), pack_bf16(ao[1][2], ao[1][3]));
            stsm_x4_t(orow + 2048, pack_bf16(ao[2][0], ao[2][1]), pack_bf16(ao[3][0], ao[3][1]), pack_bf16(ao[2][2], ao[2][3]), pack_bf16(ao[3][2], ao[3][3]));
            stsm_x4_t(orow + 4096, pack_bf16(ao[4][2], ao[4][3]), pack_bf16(ao[5][2], ao[5][3]), pack_bf16(ao[6][0], ao[6][1]), pack_bf16(ao[7][0], ao[7][1]));
            stsm_x2_t(orow + 6144, pack_bf16(ao[6][2], ao[6][3]), pack_bf16(ao[7][2], ao[7][3]));
            __syncwarp();
            if (lane == 0) mbar_arrive(bar_o);
        }
        uint32_t af[4 * L_NB][4];
        #pragma unroll 1
        for (int it = QK_AT + 3; it < it1 - (late ? L_NB : 3); it++) {
            wait_full(it);
            wgmma_wait<0>();
            if (it != 7 + 32 - KB_EARLY - 4) release((it - 1) & 3);
            done(it - 1);
            big_issue(it & 3, false);
            if (L_PRE && it == 7 + 32 - KB_EARLY - L_NB - 2) {
                mbar_wait(bar_sf, 0);
                #pragma unroll
                for (int k = 0; k < 4; k++) ldsm_x4((a_frag ^ (k << 5)) + NSLOT * SLOT_BYTES, af[k][0], af[k][1], af[k][2], af[k][3]);
            }
        }
        mbar_wait(bar_fl + 24, 0);
        if (tid == 128) atomicAdd(&g_epoch[cta * 8], 1);
        __nv_bfloat16* const yp = pin(out + (size_t)(mt * 128 + cw * 16 + (lane >> 2)) * NOUT + DM + nh * 256 + (lane & 3) * 8);
        const int y6 = 192 - nh * 224;
        #define Y_WORD(A, i, jj) pack_bf16(A[16 * ((i) >> 1) + 4 * (jj) + 2 * ((i) & 1)], A[16 * ((i) >> 1) + 4 * (jj) + 2 * ((i) & 1) + 1])
        #define Y_ADDR(i) (yp + ((i) & 1) * 8 * NOUT + ((i) < 12 ? ((i) >> 1) * 32 : y6))
        const bool odd = lane & 4;
        __nv_bfloat16* const yq = pin(odd ? yp - NOUT + 32 : yp);
        #define Y_PAIR(A, i, B, j, rh, C, PAUSE) do { \
            uint32_t x_[4], y_[4]; \
            _Pragma("unroll") \
            for (int jj = 0; jj < 4; jj++) { \
                const uint32_t u_ = Y_WORD(A, 2 * (i) + (rh), jj), v_ = Y_WORD(B, 2 * (j) + (rh), jj), o_ = __shfl_xor_sync(0xffffffffu, odd ? u_ : v_, 4); \
                x_[jj] = odd ? o_ : u_; y_[jj] = odd ? v_ : o_; \
            } \
            red_add_bf16x8(yq + (rh) * 8 * NOUT + (C), x_[0], x_[1], x_[2], x_[3]); \
            PAUSE; \
            red_add_bf16x8(yq + ((rh) * 8 + 1) * NOUT + (C), y_[0], y_[1], y_[2], y_[3]); \
        } while (0)
        if (late) {
            constexpr int IT = 7 + 32 - KB_EARLY - L_NB;
            #define L_SLOT(j) ((j) == 0 ? NSLOT : (IT + (j) - 1) & 3)
            auto load_af = [&](int j) {
                if (j == 0) mbar_wait(bar_sf, 0); else wait_full(IT + j - 1);
                #pragma unroll
                for (int k = 0; k < 4; k++) ldsm_x4((a_frag ^ (k << 5)) + L_SLOT(j) * SLOT_BYTES, af[4 * j + k][0], af[4 * j + k][1], af[4 * j + k][2], af[4 * j + k][3]);
            };
            if (!L_PRE) load_af(0);
            load_af(1);
            if (L_UP) load_af(2);
            wgmma_wait<0>();
            done(IT - 1);
            if (!L_UP && wg == 1) load_af(2);
            if (L_NB == 4 && wg == 1) load_af(L_NB - 1);
            auto issue = [&](auto& p, auto c0, int j0, int j1, bool first, bool last) {
                constexpr int W = sizeof(p) / 2, C0 = decltype(c0)::value;
                if (wg == 0) { if (!first) asm volatile("bar.sync 9, 256;" ::: "memory"); } else asm volatile("bar.sync 5, 256;" ::: "memory");
                wgmma_fence();
                #pragma unroll
                for (int j = j0; j < j1; j++) {
                    if (!L_UP && first && j == 8) { if (wg == 0) load_af(2); wgmma_fence(); }
                    if (L_NB == 4 && first && j == 12) { if (wg == 0) load_af(L_NB - 1); wgmma_fence(); }
                    if (j == j1 - 12 + L_ARR) { if (wg == 0) asm volatile("bar.arrive 5, 256;" ::: "memory"); else if (!last) asm volatile("bar.arrive 9, 256;" ::: "memory"); }
                    const uint32_t d = dB + L_SLOT(j >> 2) * (SLOT_BYTES >> 4) + C0 * 8 + 2 * (j & 3);
                    if constexpr (W == 96) wgmma_rs_n96<0>(p, af[j], d, 1); else if constexpr (W == 64) wgmma_rs_n64<0>(p, af[j], d, 1); else wgmma_rs_n32<0>(p, af[j], d, 1);
                }
                wgmma_commit();
            };
            float pa[48], p0[32], p1[32];
            #pragma unroll
            for (int i = 0; i < 48; i++) asm volatile("mov.b32 %0, %1;" : "=f"(pa[i]) : "f"(acc[64 + i]));
            #pragma unroll
            for (int i = 0; i < 32; i++) asm volatile("mov.b32 %0, %1;" : "=f"(p1[i]) : "f"(acc[32 + i]));
            #pragma unroll
            for (int i = 0; i < 32; i++) asm volatile("mov.b32 %0, %1;" : "=f"(p0[i]) : "f"(acc[i]));
            issue(pa, Int<128>(), 0, 4 * L_NB, true, false);
            wgmma_wait<0>();
            if (sig_local) TRL(14 + wg);
            Y_PAIR(pa, 0, pa, 1, 0, 128, ); Y_PAIR(pa, 0, pa, 1, 1, 128, );
            #pragma unroll
            for (int i = 0; i < 2; i++) red_add_bf16x8(Y_ADDR(12 + i), Y_WORD(pa, 4 + i, 0), Y_WORD(pa, 4 + i, 1), Y_WORD(pa, 4 + i, 2), Y_WORD(pa, 4 + i, 3));
            issue(p0, Int<0>(), 0, 4 * L_NB, false, false);
            wgmma_wait<0>();
            Y_PAIR(p0, 0, p0, 1, 0, 0, ); Y_PAIR(p0, 0, p0, 1, 1, 0, );
            issue(p1, Int<64>(), 0, 4 * L_NB, false, true);
            if (sig_local) mbar_arrive(bar_end);
            wgmma_wait<0>();
            if (sig_local) TRX(27 + wg);
            Y_PAIR(p1, 0, p1, 1, 0, 64, ); Y_PAIR(p1, 0, p1, 1, 1, 64, );
            if (sig_local) TR(29 + wg);
        } else {
        constexpr int IT0 = 7 + KB_EARLY;
        auto load_af = [&](int j) {
            wait_full(IT0 - 3 + j);
            #pragma unroll
            for (int k = 0; k < 4; k++) ldsm_x4((a_frag ^ (k << 5)) + ((IT0 - 3 + j) & 3) * SLOT_BYTES, af[4 * j + k][0], af[4 * j + k][1], af[4 * j + k][2], af[4 * j + k][3]);
        };
        wait_full(IT0 - 3);
        wgmma_wait<0>();
        release((IT0 - 4) & 3);
        done(IT0 - 4);
        if (wg == 1) {
            load_af(0); load_af(1); load_af(2);
            asm volatile("bar.sync 5, 256;" ::: "memory");
            release((bar_af - bar_empty) / 8);
            #pragma unroll
            for (int it = IT0 - 3; it < IT0; it++) {
                if (it == IT0 - 1) { wgmma_wait<1>(); release((it - 2) & 3); }
                wgmma_fence();
                #pragma unroll
                for (int k = 0; k < 4; k++) wgmma_rs_n224<0>(acc, af[4 * (it - IT0 + 3) + k], dB + (it & 3) * (SLOT_BYTES >> 4) + 2 * k, 1);
                wgmma_commit();
            }
            asm volatile("bar.arrive 9, 256;" ::: "memory");
            wgmma_wait<1>();
            release((IT0 - 2) & 3);
            wgmma_wait<0>();
            release((IT0 - 1) & 3);
            if (sig_local) { mbar_arrive(bar_end); TRL(28); }
            const uint32_t t1 = clk32() + TP(RED_AT1);
            auto pause = [&](int i) { while ((int)(clk32() - t1) < i * TP(RED_GAP1)) { } };
            #pragma unroll
            for (int i = 0; i < 2; i++) { pause(i); red_add_bf16x8(Y_ADDR(12 + i), Y_WORD(acc, 12 + i, 0), Y_WORD(acc, 12 + i, 1), Y_WORD(acc, 12 + i, 2), Y_WORD(acc, 12 + i, 3)); }
            #pragma unroll
            for (int i = 0; i < 6; i++) { pause(2 + 2 * i); Y_PAIR(acc, i & 6, acc, (i & 6) + 1, i & 1, 32 * (i & 6), pause(3 + 2 * i)); }
            if (sig_local) TRX(30);
        } else {
            float lo[64], hi[48];
            #pragma unroll
            for (int i = 0; i < 48; i++) asm volatile("mov.b32 %0, %1;" : "=f"(hi[i]) : "f"(acc[64 + i]));
            #pragma unroll
            for (int i = 0; i < 64; i++) asm volatile("mov.b32 %0, %1;" : "=f"(lo[i]) : "f"(acc[i]));
            #pragma unroll
            for (int it = IT0 - 3; it < IT0; it++) {
                if (it == IT0 - 1) {
                    #pragma unroll
                    for (int k = 0; k < E_FILL; k++) wgmma_n96<1, 0>(hi, dA + ((IT0 - 3 + (k >> 2)) & 3) * (SLOT_BYTES >> 4) + 2 * (k & 3), dB + ((IT0 - 3 + (k >> 2)) & 3) * (SLOT_BYTES >> 4) + 1024 + 2 * (k & 3), 1);
                }
                if (it > IT0 - 3) wait_full(it);
                wgmma_fence();
                #pragma unroll
                for (int k = 0; k < 4; k++) wgmma_n128<1, 0>(lo, dA + (it & 3) * (SLOT_BYTES >> 4) + 2 * k, dB + (it & 3) * (SLOT_BYTES >> 4) + 2 * k, 1);
            }
            wgmma_commit();
            #define E_RED(i) do { if ((i) < 8) red_add_bf16x8(Y_ADDR(i), Y_WORD(lo, (i) & 7, 0), Y_WORD(lo, (i) & 7, 1), Y_WORD(lo, (i) & 7, 2), Y_WORD(lo, (i) & 7, 3)); \
                                  else red_add_bf16x8(Y_ADDR(i), Y_WORD(hi, (i) & 7, 0), Y_WORD(hi, (i) & 7, 1), Y_WORD(hi, (i) & 7, 2), Y_WORD(hi, (i) & 7, 3)); } while (0)
            #pragma unroll
            for (int j = E_FILL; j < 12; j++) {
                const int it = IT0 - 3 + (j >> 2), k = j & 3;
                if (j == E_FILL + E_SPLIT) {
                    wgmma_commit();
                    wgmma_wait<1>();
                    if (sig_local) TR(14);
                    #pragma unroll
                    for (int i = 0; i < RED_A; i++) E_RED(i);
                    wgmma_fence();
                }
                wgmma_n96<1, 0>(hi, dA + (it & 3) * (SLOT_BYTES >> 4) + 2 * k, dB + (it & 3) * (SLOT_BYTES >> 4) + 1024 + 2 * k, 1);
            }
            wgmma_commit();
            asm volatile("bar.arrive 5, 256;" ::: "memory");
            #pragma unroll
            for (int i = RED_A; i < RED_FAST; i++) E_RED(i);
            wgmma_wait<0>();
            release((bar_af - bar_empty) / 8); release((IT0 - 3) & 3); release((IT0 - 2) & 3); release((IT0 - 1) & 3);
            if (sig_local) TRL(27);
            const uint32_t t1 = clk32();
            #pragma unroll
            for (int i = RED_FAST; i < 14 - E_LATE; i++) {
                while ((int)(clk32() - t1) < (i - RED_FAST) * TP(RED_GAP)) { }
                E_RED(i);
            }
            if (sig_local) TR(29);
            float o0[56], o1[56];
            auto out_issue = [&](float (&oa)[56], int p, int j) {
                wgmma_fence();
                #pragma unroll
                for (int k = 0; k < (ABL & 32 ? 0 : 4); k++) wgmma_n112<1, 1, 8>(oa, dB + (63 << 16) + ((OUT_O(p, j) - SLOT_A) >> 4) + 128 * k, dB + ((((OUT_B(j) - OUT_A(j)) >> 4) - 1) << 16) + ((OUT_A(j) - SLOT_A) >> 4) + 128 * k, (j | k) != 0);
                wgmma_commit();
            };
            const uint32_t wa = pin(sb + w * 2048 + ((m & 1) * 8 + i8) * 128 + (((m >> 1) ^ i8) << 4)), ra = pin(sb + w * 2048 + m * 128 + ((i8 ^ m) << 4));
            auto stage = [&](float (&oa)[56], int buf, int u) {
                stsm_x4((wa ^ ((u & 3) << 5)) + buf + (u >> 2) * 8192, pack_bf16(oa[8 * u], oa[8 * u + 1]), pack_bf16(oa[8 * u + 2], oa[8 * u + 3]),
                        pack_bf16(oa[8 * u + 4], oa[8 * u + 5]), pack_bf16(oa[8 * u + 6], oa[8 * u + 7]));
            };
            __nv_bfloat16* const op = pin(out + (size_t)(mt * 128 + 1 + w * 32 + 2 * m) * NOUT + (sub & 3) * 64 + i8 * 8);
            const int c1 = 256 - (sub & 3) * 16;
            asm volatile("bar.sync 9, 256;" ::: "memory");
            #pragma unroll
            for (int j = 0; j < 7; j++) {
                if (j == 0 || j == 2 || j == 4 || (OUT_L2 && j == 6)) { mbar_wait(bar_abf + 4 * j, 1); if (sig_local) TR(128 + IT0 + j); }
                out_issue(o0, 0, j);
                if (j < E_LATE) E_RED(14 - E_LATE + j);
                if (!OUT_L2 && j == 2) { wgmma_wait<2>(); if (sig_local) mbar_arrive(bar_ab6); }
            }
            #undef E_RED
            #pragma unroll
            for (int j = 0; j < 7; j++) {
                if (OUT_L2 ? j == 3 : j % 3 == 0) { mbar_wait(bar_abf + 24 + 8 * (j / 3), 1); if (sig_local) TR(192 + IT0 + j); }
                out_issue(o1, 1, j);
                if (j == 1) { wgmma_wait<2>(); if (sig_local) TR(31); }
                if (j >= 1 && j < 5) {
                    stage(o0, OUT_ST, 2 * j - 2);
                    if (j < 4) stage(o0, OUT_ST, 2 * j - 1);
                    if (j == 2 || j == 4) { __syncwarp(); if (lane == 0) mbar_arrive(bar_qkv + 4 * j - 8); }
                }
            }
            if (sig_local) mbar_arrive(bar_end);
            wgmma_wait<0>();
            if (sig_local) TRL(32);
            #pragma unroll
            for (int c = 0; c < 2; c++) {
                #pragma unroll
                for (int u = 4 * c; u < (c ? 7 : 4); u++) stage(o1, 0, u);
                __syncwarp();
                #pragma unroll
                for (int q = 0; q < 4; q++) {
                    uint4 v;
                    asm volatile("ld.shared.v4.u32 {%0, %1, %2, %3}, [%4];" : "=r"(v.x), "=r"(v.y), "=r"(v.z), "=r"(v.w) : "r"((ra ^ ((q & 1) << 6)) + c * 8192 + q * 512) : "memory");
                    if (c == 0 || i8 < 6) *reinterpret_cast<uint4*>(op + q * 8 * NOUT + (c ? c1 : 0)) = v;
                }
            }
        }
        }
        #undef Y_PAIR
        #undef Y_WORD
        #undef Y_ADDR
        if (sig_local) { TRX(33 + wg); if (wg == (late ? 1 : 0)) TRG(104); }
        TR_END();
    }
}

typedef CUresult (*EncodeFn)(CUtensorMap*, CUtensorMapDataType, cuuint32_t, void*, const cuuint64_t*, const cuuint64_t*,
                             const cuuint32_t*, const cuuint32_t*, CUtensorMapInterleave, CUtensorMapSwizzle,
                             CUtensorMapL2promotion, CUtensorMapFloatOOBfill);

void make_map(EncodeFn fn, CUtensorMap* tm, const void* ptr, uint64_t inner, uint64_t outer, uint32_t box_inner, uint32_t box_outer,
              CUtensorMapSwizzle sw = CU_TENSOR_MAP_SWIZZLE_128B, uint64_t clip = 0) {
    cuuint64_t gd[2] = {clip ? clip : inner, outer};
    cuuint64_t gs[1] = {inner * 2};
    cuuint32_t bd[2] = {box_inner, box_outer};
    cuuint32_t es[2] = {1, 1};
    fn(tm, CU_TENSOR_MAP_DATA_TYPE_BFLOAT16, 2, const_cast<void*>(ptr), gd, gs, bd, es, CU_TENSOR_MAP_INTERLEAVE_NONE,
       sw, CU_TENSOR_MAP_L2_PROMOTION_L2_128B, CU_TENSOR_MAP_FLOAT_OOB_FILL_NONE);
}
void make_map3(EncodeFn fn, CUtensorMap* tm, const void* ptr, uint64_t n0, uint64_t n1, uint64_t s1, uint64_t n2, uint64_t s2, uint32_t b1, uint32_t b2) {
    cuuint64_t gd[3] = {n0, n1, n2};
    cuuint64_t gs[2] = {s1 * 2, s2 * 2};
    cuuint32_t bd[3] = {64, b1, b2};
    cuuint32_t es[3] = {1, 1, 1};
    fn(tm, CU_TENSOR_MAP_DATA_TYPE_BFLOAT16, 3, const_cast<void*>(ptr), gd, gs, bd, es, CU_TENSOR_MAP_INTERLEAVE_NONE,
       CU_TENSOR_MAP_SWIZZLE_128B, CU_TENSOR_MAP_L2_PROMOTION_L2_128B, CU_TENSOR_MAP_FLOAT_OOB_FILL_NONE);
}
void make_map_perm(EncodeFn fn, CUtensorMap* tm, void* ptr, uint32_t n) {
    cuuint64_t gd[5] = {SEQ, 2, 4, 4, 28};
    cuuint64_t gs[4] = {SEQ * 2, 8 * SEQ * 2, 2 * SEQ * 2, 32 * SEQ * 2};
    cuuint32_t bd[5] = {64, 2, 4, 4, n};
    cuuint32_t es[5] = {1, 1, 1, 1, 1};
    fn(tm, CU_TENSOR_MAP_DATA_TYPE_BFLOAT16, 5, ptr, gd, gs, bd, es, CU_TENSOR_MAP_INTERLEAVE_NONE,
       CU_TENSOR_MAP_SWIZZLE_128B, CU_TENSOR_MAP_L2_PROMOTION_L2_128B, CU_TENSOR_MAP_FLOAT_OOB_FILL_NONE);
}

}

extern "C" void kernel_launch(void* const* d_in, const int* in_sizes, int n_in, void* d_out, int out_size) {
    (void)in_sizes; (void)n_in; (void)out_size;
    static EncodeFn fn = nullptr;
    static void* p_abT = nullptr;
    if (!fn) {
        void* p = nullptr; cudaDriverEntryPointQueryResult qr;
        cudaGetDriverEntryPoint("cuTensorMapEncodeTiled", &p, cudaEnableDefault, &qr);
        fn = (EncodeFn)p;
        cudaGetSymbolAddress(&p_abT, g_abT);
        cudaFuncSetAttribute(fused_kernel, cudaFuncAttributeMaxDynamicSharedMemorySize, SMEM_BYTES);
    }
    TMaps tm;
    make_map3(fn, &tm.xA3, d_in[0], DM, SEQ / 2, 2 * DM, 2, DM, 64, 2);
    make_map3(fn, &tm.wqkv3, d_in[1], DM, DM, 3 * DM, 3, DM, 32, 3);
    make_map(fn, &tm.wo64, d_in[2], DM, DM, 64, 64);
    make_map3(fn, &tm.outA, d_out, 64, SEQ / 2, 2 * NOUT, 4, 64, 64, 1);
    make_map3(fn, &tm.outB, (const __nv_bfloat16*)d_out + 256, 48, SEQ / 2, 2 * NOUT, 4, 48, 64, 1);
    make_map(fn, &tm.xB, d_in[3], DM, SEQ, 64, 128);
    make_map(fn, &tm.wre, d_in[4], SEQ, SEQ, 64, 128);
    make_map(fn, &tm.wim, d_in[5], SEQ, SEQ, 64, 128);
    make_map(fn, &tm.wreH, d_in[4], SEQ, SEQ, 64, 64);
    make_map(fn, &tm.wimH, d_in[5], SEQ, SEQ, 64, 64);
    make_map(fn, &tm.wdre, d_in[6], DM, DM, 64, 112);
    make_map(fn, &tm.wdim, d_in[7], DM, DM, 64, 112);
    make_map_perm(fn, &tm.abP4, p_abT, 4);
    make_map_perm(fn, &tm.abP3, p_abT, 3);
    make_map(fn, &tm.abH, p_abT, SEQ, 896, 64, 16);
    make_map(fn, &tm.ab32, p_abT, SEQ, 896, 64, 32);
    make_map(fn, &tm.ab80, p_abT, SEQ, 896, 64, 80);
    fused_kernel<<<NCTA, 384, SMEM_BYTES, cudaStreamPerThread>>>((__nv_bfloat16*)d_out,
        tm);
}
```

```cpp
#include <cuda_runtime.h>
#include <cuda_bf16.h>
#include <cuda.h>
#include <stdint.h>

namespace {

constexpr int SEQ = 2048, DM = 448, NOUT = 896;
constexpr int NCTA = 128;
constexpr int SLOT_A = 16384, SLOT_B = 28672, SLOT_BYTES = SLOT_A + SLOT_B, NSLOT = 4;
constexpr int AB_BYTES = SLOT_A + 112 * 128;
constexpr int STG_OFF = NSLOT * SLOT_BYTES;
constexpr int STG_BYTES = 7 * 7168;
constexpr int KV_PITCH = 240;
constexpr int KV_OFF = 2 * 7168, KV_PAR = 72 * KV_PITCH;
#define OUT_A(j) (((j) < 2 ? 48 + 8 * (j) : (j) < 4 ? 8 * (j) - 16 : (j) == 4 ? 136 : 80 + 8 * (j)) * 1024)
#define OUT_B(j) (((j) == 0 ? 80 : 168 + 8 * (j)) * 1024)
#define OUT_O(p, j) (((p) ? ((j) < 3 ? 152 + 8 * (j) : 8 * (j) - 8) : ((j) < 2 ? 64 + 8 * (j) : (j) < 6 ? 72 + 8 * (j) : 144)) * 1024)
#define OUT_ST OUT_O(0, 0)
constexpr int BAR_OFF = STG_OFF + STG_BYTES;
constexpr int TR_OFF = BAR_OFF + 512;
constexpr int SMEM_BYTES = TR_OFF + 1024;
constexpr int SPIN_LIMIT = 1 << 24;
#define TUNE_LIST(X) \
    X(START_GAP1, 400, 50, 0, 900)   \
    X(START_GAP, 280, 30, 0, 500)   \
    X(WARM_N, 3, 1, 0, 6)   \
    X(WARM_GAP, 150, 50, 50, 500)   \
    X(ZERO_GAP, 100, 50, 0, 300)   \
    X(ZERO_AT, 900, 200, 0, 2400)   \
    X(ABS_AT1, 500, 100, 0, 1000)   \
    X(ABS_AT, 1500, 150, 300, 3000)   \
    X(ABS_GAP, 60, 40, 0, 400)   \
    X(ABS_GAP2, 230, 40, 0, 400)   \
    X(ABS_GAP3, 100, 40, 0, 400)   \
    X(POLL_AT, 3100, 100, 2000, 4000)   \
    X(POLL_AT1, 3600, 150, 2000, 5000)   \
    X(POLL_AT2, 6300, 200, 4000, 8000)   \
    X(POLL_AT3, 9200, 200, 6000, 11000)   \
    X(OPOLL_AT, 15100, 200, 13000, 17500)   \
    X(OPOLL2, 500, 100, -1000, 1500)   \
    X(POLL_NS, 50, 100, 0, 800)   \
    X(OPOLL_NS, 100, 60, 0, 600)   \
    X(BIG_GAP, 250, 100, 0, 1000)   \
    X(W_GAP, 180, 100, 0, 900)   \
    X(HALO_WAIT, 350, 100, 0, 1500)   \
    X(O_GAP, 130, 60, 10, 600)   \
    X(PF_N, 0, 1, 0, 3)   \
    X(PF_E, 6, 1, 4, 13)   \
    X(PF_L, 14, 1, 4, 17)   \
    X(WO_AT, 7, 1, 5, 10)   \
    X(WB_AT, 10, 1, 10, 13)   \
    X(L_XAT, 13, 1, 10, 13)   \
    X(RED_GAP, 185, 30, 0, 300)   \
    X(RED_AT1, 0, 100, 0, 1000)   \
    X(RED_GAP1, 80, 30, 0, 300)   \

#define X(n, d, s, lo, hi) constexpr int n = d;
TUNE_LIST(X)
#undef X
#define TP(n) n
#define L_UP 1
#define ABL 0
#define BIG_ST 1
#define FLIP 1
#define URG(mt) ((((mt) >> 2) & 1) ^ FLIP)
#define AB_ST 7
#define AB_ST2 8
#define GAP_FLIP 1
#define L_PRE 1
#define E_FILL 2
#define KB_EARLY 14
#define O_N 2
#define QK_AT 10
#define WAIT_KIND 1
#define KV_FIRST 1
#define Q_ARR 11
#define E_SPLIT 7
#define RED_A 4
#define RED_FAST 6
#define L_ARR 11
#define OPOLL2_ON 1
#define E_LATE 2
#define L_NB 4
#define START_N 2
#define REG_CONS 208
#define REG_AUX 88

struct __align__(64) TMaps { CUtensorMap xB, wdre, wdim, wre, wim, abP4, abP3, abH, ab32, ab80, wreH, wimH, wo64, xA3, wqkv3, outA, outB; };

__device__ __nv_bfloat16 g_abT[896 * SEQ];
__device__ uint4 g_o[SEQ * DM / 8];
__device__ uint4 g_halo[16 * 8 * 2 * 160];
__device__ unsigned g_flag_ab[40 * 32];
__device__ unsigned g_flag_o[16 * 32];
__device__ unsigned g_epoch[NCTA * 8];

__device__ __forceinline__ uint32_t smem_u32(const void* p) { return (uint32_t)__cvta_generic_to_shared(p); }
__device__ __forceinline__ uint32_t clk32() { uint32_t c; asm volatile("mov.u32 %0, %%clock;" : "=r"(c) :: "memory"); return c; }
__device__ __forceinline__ void give_up() { asm volatile("st.global.u32 [%0], 0;" :: "l"(0ull) : "memory"); }
__device__ __forceinline__ void mbar_init(uint32_t bar, uint32_t count) { asm volatile("mbarrier.init.shared::cta.b64 [%0], %1;" :: "r"(bar), "r"(count) : "memory"); }
__device__ __forceinline__ void mbar_expect_tx(uint32_t bar, uint32_t bytes) { asm volatile("mbarrier.arrive.expect_tx.shared::cta.b64 _, [%0], %1;" :: "r"(bar), "r"(bytes) : "memory"); }
__device__ __forceinline__ void mbar_arrive(uint32_t bar) { asm volatile("mbarrier.arrive.shared::cta.b64 _, [%0];" :: "r"(bar) : "memory"); }
__device__ __forceinline__ void mbar_arrive_remote(uint32_t bar, uint32_t cta) {
    asm volatile("{\n.reg .b32 ra;\nmapa.shared::cluster.u32 ra, %0, %1;\nmbarrier.arrive.shared::cluster.b64 _, [ra];\n}" :: "r"(bar), "r"(cta) : "memory");
}
__device__ __forceinline__ bool mbar_try_wait(uint32_t bar, uint32_t parity) {
    uint32_t ok;
    asm volatile("{\n.reg .pred p;\nmbarrier.try_wait.parity.shared::cta.b64 p, [%1], %2;\nselp.u32 %0, 1, 0, p;\n}" : "=r"(ok) : "r"(bar), "r"(parity) : "memory");
    return ok;
}
__device__ __forceinline__ bool mbar_test_wait(uint32_t bar, uint32_t parity) {
    uint32_t ok;
    asm volatile("{\n.reg .pred p;\nmbarrier.test_wait.parity.shared::cta.b64 p, [%1], %2;\nselp.u32 %0, 1, 0, p;\n}" : "=r"(ok) : "r"(bar), "r"(parity) : "memory");
    return ok;
}
#define WAIT_OP "pmevent 0;\nmbarrier.try_wait.parity.shared::cta.b64 p, [%0], %1;\n"
__device__ __forceinline__ void mbar_wait(uint32_t bar, uint32_t parity) {
    asm volatile("{\n.reg .pred p;\nWAIT:\n" WAIT_OP "@!p bra WAIT;\n}" :: "r"(bar), "r"(parity) : "memory");
}
__device__ __forceinline__ void mbar_wait_p(uint32_t bar, uint32_t parity) {
    asm volatile("{\n.reg .pred p;\nWAIT:\nmbarrier.try_wait.parity.shared::cta.b64 p, [%0], %1;\n@!p bra WAIT;\n}" :: "r"(bar), "r"(parity) : "memory");
}
__device__ __forceinline__ void mbar_wait_limit(uint32_t bar, uint32_t parity) {
    int it = 0;
    while (!mbar_try_wait(bar, parity)) { if (++it > SPIN_LIMIT) give_up(); }
}
__device__ __forceinline__ void tma_load(uint32_t dst, const CUtensorMap* tm, uint32_t bar, int c0, int c1) {
    asm volatile("cp.async.bulk.tensor.2d.shared::cluster.global.mbarrier::complete_tx::bytes [%0], [%1, {%3, %4}], [%2];"
        :: "r"(dst), "l"(tm), "r"(bar), "r"(c0), "r"(c1) : "memory");
}
__device__ __forceinline__ void tma_load_mc(uint32_t dst, const CUtensorMap* tm, uint32_t bar, int c0, int c1) {
    asm volatile("cp.async.bulk.tensor.2d.shared::cluster.global.mbarrier::complete_tx::bytes.multicast::cluster [%0], [%1, {%3, %4}], [%2], %5;"
        :: "r"(dst), "l"(tm), "r"(bar), "r"(c0), "r"(c1), "h"((uint16_t)3) : "memory");
}
__device__ __forceinline__ void tma_load3(uint32_t dst, const CUtensorMap* tm, uint32_t bar, int c0, int c1) {
    asm volatile("cp.async.bulk.tensor.3d.shared::cluster.global.mbarrier::complete_tx::bytes [%0], [%1, {%3, %4, %5}], [%2];"
        :: "r"(dst), "l"(tm), "r"(bar), "r"(c0), "r"(c1), "r"(0) : "memory");
}
__device__ __forceinline__ void tma_load3_mc(uint32_t dst, const CUtensorMap* tm, uint32_t bar, int c0, int c1, int c2) {
    asm volatile("cp.async.bulk.tensor.3d.shared::cluster.global.mbarrier::complete_tx::bytes.multicast::cluster [%0], [%1, {%3, %4, %6}], [%2], %5;"
        :: "r"(dst), "l"(tm), "r"(bar), "r"(c0), "r"(c1), "h"((uint16_t)3), "r"(c2) : "memory");
}
__device__ __forceinline__ void tma_prefetch(const CUtensorMap* tm, int c0, int c1) {
    asm volatile("cp.async.bulk.prefetch.tensor.2d.L2.global [%0, {%1, %2}];" :: "l"(tm), "r"(c0), "r"(c1) : "memory");
}
__device__ __forceinline__ void tma_prefetch3(const CUtensorMap* tm, int c0, int c1) {
    asm volatile("cp.async.bulk.prefetch.tensor.3d.L2.global [%0, {%1, %2, %3}];" :: "l"(tm), "r"(c0), "r"(c1), "r"(0) : "memory");
}
__device__ __forceinline__ void tma_store(const CUtensorMap* tm, uint32_t src, int c0, int c1) {
    asm volatile("cp.async.bulk.tensor.2d.global.shared::cta.bulk_group [%0, {%2, %3}], [%1];" :: "l"(tm), "r"(src), "r"(c0), "r"(c1) : "memory");
}
__device__ __forceinline__ void tma_store3(const CUtensorMap* tm, uint32_t src, int c1, int c2) {
    asm volatile("cp.async.bulk.tensor.3d.global.shared::cta.bulk_group [%0, {%2, %3, %4}], [%1];" :: "l"(tm), "r"(src), "r"(0), "r"(c1), "r"(c2) : "memory");
}
__device__ __forceinline__ void bulk_load(uint32_t dst, const void* src, uint32_t bytes, uint32_t bar) {
    asm volatile("cp.async.bulk.shared::cluster.global.mbarrier::complete_tx::bytes [%0], [%1], %2, [%3];" :: "r"(dst), "l"(src), "r"(bytes), "r"(bar) : "memory");
}
__device__ __forceinline__ void bulk_store(void* dst, uint32_t src, uint32_t bytes) {
    asm volatile("cp.async.bulk.global.shared::cta.bulk_group [%0], [%1], %2;" :: "l"(dst), "r"(src), "r"(bytes) : "memory");
}
__device__ __forceinline__ void tma_load5_mc(uint32_t dst, const CUtensorMap* tm, uint32_t bar, int c0, int c4) {
    asm volatile("cp.async.bulk.tensor.5d.shared::cluster.global.mbarrier::complete_tx::bytes.multicast::cluster [%0], [%1, {%3, %6, %6, %6, %4}], [%2], %5;"
        :: "r"(dst), "l"(tm), "r"(bar), "r"(c0), "r"(c4), "h"((uint16_t)3), "r"(0) : "memory");
}
__device__ __forceinline__ void red_add_bf16x8(__nv_bfloat16* p, uint32_t w0, uint32_t w1, uint32_t w2, uint32_t w3) {
    asm volatile("red.relaxed.gpu.global.add.noftz.v4.bf16x2 [%0], {%1, %2, %3, %4};" :: "l"(p), "r"(w0), "r"(w1), "r"(w2), "r"(w3) : "memory");
}
__device__ __forceinline__ void prefetch_tmap(const CUtensorMap* tm) { asm volatile("prefetch.tensormap [%0];" :: "l"(tm) : "memory"); }
__device__ __forceinline__ void cluster_arrive() { asm volatile("barrier.cluster.arrive.relaxed.aligned;" ::: "memory"); }
__device__ __forceinline__ void cluster_wait() { asm volatile("barrier.cluster.wait.aligned;" ::: "memory"); }
__device__ __forceinline__ void wgmma_fence() { asm volatile("wgmma.fence.sync.aligned;" ::: "memory"); }
__device__ __forceinline__ void wgmma_commit() { asm volatile("wgmma.commit_group.sync.aligned;" ::: "memory"); }
template<int N> __device__ __forceinline__ void wgmma_wait() { asm volatile("wgmma.wait_group.sync.aligned %0;" :: "n"(N) : "memory"); }
__device__ __forceinline__ void fence_async_smem() { asm volatile("fence.proxy.async.shared::cta;" ::: "memory"); }
__device__ __forceinline__ void fence_async_global() { asm volatile("fence.proxy.async.global;" ::: "memory"); }
__device__ __forceinline__ uint32_t desc_k(uint32_t addr) { return ((addr & 0x3FFFF) >> 4) | (1u << 16); }
__device__ __forceinline__ uint32_t desc_mn(uint32_t addr) { return ((addr & 0x3FFFF) >> 4) | ((8192u >> 4) << 16); }
template<int R> __device__ __forceinline__ void reg_set() {
    if (R > 168) asm volatile("setmaxnreg.inc.sync.aligned.u32 %0;" :: "n"(R));
    if (R < 168) asm volatile("setmaxnreg.dec.sync.aligned.u32 %0;" :: "n"(R));
}
__device__ __forceinline__ unsigned ld_acquire(const unsigned* p) { unsigned v; asm volatile("ld.acquire.gpu.global.u32 %0, [%1];" : "=r"(v) : "l"(p) : "memory"); return v; }
__device__ __forceinline__ unsigned ld_relaxed(const unsigned* p) { unsigned v; asm volatile("ld.relaxed.gpu.global.u32 %0, [%1];" : "=r"(v) : "l"(p) : "memory"); return v; }
__device__ __forceinline__ void st_release(unsigned* p, unsigned v) { asm volatile("fence.proxy.async.global;\nst.release.gpu.global.u32 [%0], %1;" :: "l"(p), "r"(v) : "memory"); }
__device__ __forceinline__ void red_release(unsigned* p, unsigned v) { asm volatile("fence.proxy.async.global;\nred.release.gpu.global.add.u32 [%0], %1;" :: "l"(p), "r"(v) : "memory"); }
__device__ __forceinline__ bool elect_one() {
    uint32_t pred;
    asm volatile("{\n.reg .pred p;\nelect.sync _|p, 0xffffffff;\nselp.u32 %0, 1, 0, p;\n}" : "=r"(pred));
    return pred;
}
__device__ __forceinline__ int pick3(int cta, int a, int b, int c) {
    int v;
    asm("{\n.reg .pred p, q;\nsetp.lt.s32 p, %1, 8;\nsetp.lt.s32 q, %1, 72;\nselp.b32 %0, %3, %4, q;\nselp.b32 %0, %2, %0, p;\n}" : "=&r"(v) : "r"(cta), "r"(a), "r"(b), "r"(c));
    return v;
}
template<typename T> __device__ __forceinline__ T pin(T v) {
    if constexpr (sizeof(T) == 8) asm volatile("" : "+l"(v) :: "memory"); else asm volatile("" : "+r"(v) :: "memory");
    return v;
}
__device__ __forceinline__ void bulk_commit() { asm volatile("cp.async.bulk.commit_group;" ::: "memory"); }
__device__ __forceinline__ void bulk_wait_all() { asm volatile("cp.async.bulk.wait_group 0;" ::: "memory"); }
__device__ __forceinline__ uint32_t pack_bf16(float lo, float hi) { uint32_t r; asm("cvt.rn.bf16x2.f32 %0, %1, %2;" : "=r"(r) : "f"(hi), "f"(lo)); return r; }
__device__ __forceinline__ float bf_lo(uint32_t w) { return __uint_as_float(w << 16); }
__device__ __forceinline__ float bf_hi(uint32_t w) { return __uint_as_float(w & 0xffff0000u); }
__device__ __forceinline__ void stsm_x4(uint32_t addr, uint32_t r0, uint32_t r1, uint32_t r2, uint32_t r3) {
    asm volatile("stmatrix.sync.aligned.m8n8.x4.shared.b16 [%0], {%1, %2, %3, %4};" :: "r"(addr), "r"(r0), "r"(r1), "r"(r2), "r"(r3) : "memory");
}
__device__ __forceinline__ void stsm_x2(uint32_t addr, uint32_t r0, uint32_t r1) {
    asm volatile("stmatrix.sync.aligned.m8n8.x2.shared.b16 [%0], {%1, %2};" :: "r"(addr), "r"(r0), "r"(r1) : "memory");
}
__device__ __forceinline__ void stsm_x4_t(uint32_t addr, uint32_t r0, uint32_t r1, uint32_t r2, uint32_t r3) {
    asm volatile("stmatrix.sync.aligned.m8n8.x4.trans.shared.b16 [%0], {%1, %2, %3, %4};" :: "r"(addr), "r"(r0), "r"(r1), "r"(r2), "r"(r3) : "memory");
}
__device__ __forceinline__ void stsm_x2_t(uint32_t addr, uint32_t r0, uint32_t r1) {
    asm volatile("stmatrix.sync.aligned.m8n8.x2.trans.shared.b16 [%0], {%1, %2};" :: "r"(addr), "r"(r0), "r"(r1) : "memory");
}
__device__ __forceinline__ uint32_t movm_t(uint32_t x) { uint32_t r; asm volatile("movmatrix.sync.aligned.m8n8.trans.b16 %0, %1;" : "=r"(r) : "r"(x)); return r; }
__device__ __forceinline__ void ldsm_x4(uint32_t addr, uint32_t& r0, uint32_t& r1, uint32_t& r2, uint32_t& r3) {
    asm volatile("ldmatrix.sync.aligned.m8n8.x4.shared.b16 {%0, %1, %2, %3}, [%4];" : "=r"(r0), "=r"(r1), "=r"(r2), "=r"(r3) : "r"(addr) : "memory");
}
__device__ __forceinline__ void ldsm_x4_t(uint32_t addr, uint32_t& r0, uint32_t& r1, uint32_t& r2, uint32_t& r3) {
    asm volatile("ldmatrix.sync.aligned.m8n8.x4.trans.shared.b16 {%0, %1, %2, %3}, [%4];" : "=r"(r0), "=r"(r1), "=r"(r2), "=r"(r3) : "r"(addr) : "memory");
}
__device__ __forceinline__ void mma16816(float (&d)[4], uint32_t a0, uint32_t a1, uint32_t a2, uint32_t a3, uint32_t b0, uint32_t b1) {
    asm("mma.sync.aligned.m16n8k16.row.col.f32.bf16.bf16.f32 {%0, %1, %2, %3}, {%4, %5, %6, %7}, {%8, %9}, {%0, %1, %2, %3};"
        : "+f"(d[0]), "+f"(d[1]), "+f"(d[2]), "+f"(d[3]) : "r"(a0), "r"(a1), "r"(a2), "r"(a3), "r"(b0), "r"(b1));
}
__device__ __forceinline__ void mma1688(float (&d)[4], uint32_t a0, uint32_t a1, uint32_t b0) {
    asm("mma.sync.aligned.m16n8k8.row.col.f32.bf16.bf16.f32 {%0, %1, %2, %3}, {%4, %5}, {%6}, {%0, %1, %2, %3};"
        : "+f"(d[0]), "+f"(d[1]), "+f"(d[2]), "+f"(d[3]) : "r"(a0), "r"(a1), "r"(b0));
}
__device__ __forceinline__ uint32_t max_bf16x2(uint32_t a, uint32_t b) { uint32_t r; asm("max.bf16x2 %0, %1, %2;" : "=r"(r) : "r"(a), "r"(b)); return r; }
__device__ __forceinline__ float bf16_round(float x) { return __bfloat162float(__float2bfloat16_rn(x)); }
__device__ __forceinline__ uint32_t lds32(uint32_t addr) { uint32_t v; asm volatile("ld.shared.u32 %0, [%1];" : "=r"(v) : "r"(addr)); return v; }
__device__ __forceinline__ float ex2_approx(float x) { float y; asm("ex2.approx.ftz.f32 %0, %1;" : "=f"(y) : "f"(x)); return y; }
__device__ __forceinline__ float rcp_approx(float x) { float y; asm("rcp.approx.ftz.f32 %0, %1;" : "=f"(y) : "f"(x)); return y; }
__device__ __forceinline__ void st_b128_relaxed(uint4* p, uint32_t w0, uint32_t w1, uint32_t w2, uint32_t w3) {
    asm volatile("{\n.reg .b128 t;\n.reg .b64 lo, hi;\nmov.b64 lo, {%1, %2};\nmov.b64 hi, {%3, %4};\nmov.b128 t, {lo, hi};\nst.relaxed.gpu.global.b128 [%0], t;\n}"
        :: "l"(p), "r"(w0), "r"(w1), "r"(w2), "r"(w3) : "memory");
}
__device__ __forceinline__ uint4 ld_b128_relaxed(const uint4* p) {
    uint4 v;
    asm volatile("{\n.reg .b128 t;\n.reg .b64 lo, hi;\nld.relaxed.gpu.global.b128 t, [%4];\nmov.b128 {lo, hi}, t;\nmov.b64 {%0, %1}, lo;\nmov.b64 {%2, %3}, hi;\n}"
        : "=r"(v.x), "=r"(v.y), "=r"(v.z), "=r"(v.w) : "l"(p) : "memory");
    return v;
}

template<int SA, int TB, int HA = 0x40000040, int M>
__device__ __forceinline__ void wgmma_n8(float (&d)[M], uint32_t da, uint32_t db, int scale_d) {
    asm volatile("{\n.reg .pred p;\n.reg .b32 hi, ha;\n.reg .b64 da, db;\nmov.b32 hi, 0x40000040;\nmov.b32 ha, %9;\nmov.b64 da, {%4, ha};\nmov.b64 db, {%5, hi};\nsetp.ne.b32 p, %6, 0;\n"
        "wgmma.mma_async.sync.aligned.m64n8k16.f32.bf16.bf16 "
        "{%0, %1, %2, %3}, "
        "da, db, p, %8, 1, 0, %7;\n}\n"
        : "+f"(d[0]), "+f"(d[1]), "+f"(d[2]), "+f"(d[3])
        : "r"(da), "r"(db), "r"(scale_d), "n"(TB), "n"(SA), "n"(HA));
}
template<int SA, int TB, int HA = 0x40000040, int M>
__device__ __forceinline__ void wgmma_n96(float (&d)[M], uint32_t da, uint32_t db, int scale_d) {
    asm volatile("{\n.reg .pred p;\n.reg .b32 hi, ha;\n.reg .b64 da, db;\nmov.b32 hi, 0x40000040;\nmov.b32 ha, %53;\nmov.b64 da, {%48, ha};\nmov.b64 db, {%49, hi};\nsetp.ne.b32 p, %50, 0;\n"
        "wgmma.mma_async.sync.aligned.m64n96k16.f32.bf16.bf16 "
        "{%0, %1, %2, %3, %4, %5, %6, %7, %8, %9, %10, %11, %12, %13, %14, %15, "
        "%16, %17, %18, %19, %20, %21, %22, %23, %24, %25, %26, %27, %28, %29, %30, %31, "
        "%32, %33, %34, %35, %36, %37, %38, %39, %40, %41, %42, %43, %44, %45, %46, %47}, "
        "da, db, p, %52, 1, 0, %51;\n}\n"
        : "+f"(d[0]), "+f"(d[1]), "+f"(d[2]), "+f"(d[3]), "+f"(d[4]), "+f"(d[5]), "+f"(d[6]), "+f"(d[7]),
          "+f"(d[8]), "+f"(d[9]), "+f"(d[10]), "+f"(d[11]), "+f"(d[12]), "+f"(d[13]), "+f"(d[14]), "+f"(d[15]),
          "+f"(d[16]), "+f"(d[17]), "+f"(d[18]), "+f"(d[19]), "+f"(d[20]), "+f"(d[21]), "+f"(d[22]), "+f"(d[23]),
          "+f"(d[24]), "+f"(d[25]), "+f"(d[26]), "+f"(d[27]), "+f"(d[28]), "+f"(d[29]), "+f"(d[30]), "+f"(d[31]),
          "+f"(d[32]), "+f"(d[33]), "+f"(d[34]), "+f"(d[35]), "+f"(d[36]), "+f"(d[37]), "+f"(d[38]), "+f"(d[39]),
          "+f"(d[40]), "+f"(d[41]), "+f"(d[42]), "+f"(d[43]), "+f"(d[44]), "+f"(d[45]), "+f"(d[46]), "+f"(d[47])
        : "r"(da), "r"(db), "r"(scale_d), "n"(TB), "n"(SA), "n"(HA));
}
template<int SA, int TB, int HA = 0x40000040, int M>
__device__ __forceinline__ void wgmma_n112(float (&d)[M], uint32_t da, uint32_t db, int scale_d) {
    asm volatile("{\n.reg .pred p;\n.reg .b32 hi, ha;\n.reg .b64 da, db;\nmov.b32 hi, 0x40000040;\nmov.b32 ha, %61;\nmov.b64 da, {%56, ha};\nmov.b64 db, {%57, hi};\nsetp.ne.b32 p, %58, 0;\n"
        "wgmma.mma_async.sync.aligned.m64n112k16.f32.bf16.bf16 "
        "{%0, %1, %2, %3, %4, %5, %6, %7, %8, %9, %10, %11, %12, %13, %14, %15, "
        "%16, %17, %18, %19, %20, %21, %22, %23, %24, %25, %26, %27, %28, %29, %30, %31, "
        "%32, %33, %34, %35, %36, %37, %38, %39, %40, %41, %42, %43, %44, %45, %46, %47, "
        "%48, %49, %50, %51, %52, %53, %54, %55}, "
        "da, db, p, %60, 1, 0, %59;\n}\n"
        : "+f"(d[0]), "+f"(d[1]), "+f"(d[2]), "+f"(d[3]), "+f"(d[4]), "+f"(d[5]), "+f"(d[6]), "+f"(d[7]),
          "+f"(d[8]), "+f"(d[9]), "+f"(d[10]), "+f"(d[11]), "+f"(d[12]), "+f"(d[13]), "+f"(d[14]), "+f"(d[15]),
          "+f"(d[16]), "+f"(d[17]), "+f"(d[18]), "+f"(d[19]), "+f"(d[20]), "+f"(d[21]), "+f"(d[22]), "+f"(d[23]),
          "+f"(d[24]), "+f"(d[25]), "+f"(d[26]), "+f"(d[27]), "+f"(d[28]), "+f"(d[29]), "+f"(d[30]), "+f"(d[31]),
          "+f"(d[32]), "+f"(d[33]), "+f"(d[34]), "+f"(d[35]), "+f"(d[36]), "+f"(d[37]), "+f"(d[38]), "+f"(d[39]),
          "+f"(d[40]), "+f"(d[41]), "+f"(d[42]), "+f"(d[43]), "+f"(d[44]), "+f"(d[45]), "+f"(d[46]), "+f"(d[47]),
          "+f"(d[48]), "+f"(d[49]), "+f"(d[50]), "+f"(d[51]), "+f"(d[52]), "+f"(d[53]), "+f"(d[54]), "+f"(d[55])
        : "r"(da), "r"(db), "r"(scale_d), "n"(TB), "n"(SA), "n"(HA));
}
template<int SA, int TB, int HA = 0x40000040, int M>
__device__ __forceinline__ void wgmma_n128(float (&d)[M], uint32_t da, uint32_t db, int scale_d) {
    asm volatile("{\n.reg .pred p;\n.reg .b32 hi, ha;\n.reg .b64 da, db;\nmov.b32 hi, 0x40000040;\nmov.b32 ha, %69;\nmov.b64 da, {%64, ha};\nmov.b64 db, {%65, hi};\nsetp.ne.b32 p, %66, 0;\n"
        "wgmma.mma_async.sync.aligned.m64n128k16.f32.bf16.bf16 "
        "{%0, %1, %2, %3, %4, %5, %6, %7, %8, %9, %10, %11, %12, %13, %14, %15, "
        "%16, %17, %18, %19, %20, %21, %22, %23, %24, %25, %26, %27, %28, %29, %30, %31, "
        "%32, %33, %34, %35, %36, %37, %38, %39, %40, %41, %42, %43, %44, %45, %46, %47, "
        "%48, %49, %50, %51, %52, %53, %54, %55, %56, %57, %58, %59, %60, %61, %62, %63}, "
        "da, db, p, %68, 1, 0, %67;\n}\n"
        : "+f"(d[0]), "+f"(d[1]), "+f"(d[2]), "+f"(d[3]), "+f"(d[4]), "+f"(d[5]), "+f"(d[6]), "+f"(d[7]),
          "+f"(d[8]), "+f"(d[9]), "+f"(d[10]), "+f"(d[11]), "+f"(d[12]), "+f"(d[13]), "+f"(d[14]), "+f"(d[15]),
          "+f"(d[16]), "+f"(d[17]), "+f"(d[18]), "+f"(d[19]), "+f"(d[20]), "+f"(d[21]), "+f"(d[22]), "+f"(d[23]),
          "+f"(d[24]), "+f"(d[25]), "+f"(d[26]), "+f"(d[27]), "+f"(d[28]), "+f"(d[29]), "+f"(d[30]), "+f"(d[31]),
          "+f"(d[32]), "+f"(d[33]), "+f"(d[34]), "+f"(d[35]), "+f"(d[36]), "+f"(d[37]), "+f"(d[38]), "+f"(d[39]),
          "+f"(d[40]), "+f"(d[41]), "+f"(d[42]), "+f"(d[43]), "+f"(d[44]), "+f"(d[45]), "+f"(d[46]), "+f"(d[47]),
          "+f"(d[48]), "+f"(d[49]), "+f"(d[50]), "+f"(d[51]), "+f"(d[52]), "+f"(d[53]), "+f"(d[54]), "+f"(d[55]),
          "+f"(d[56]), "+f"(d[57]), "+f"(d[58]), "+f"(d[59]), "+f"(d[60]), "+f"(d[61]), "+f"(d[62]), "+f"(d[63])
        : "r"(da), "r"(db), "r"(scale_d), "n"(TB), "n"(SA), "n"(HA));
}
template<int SA, int TB, int HA = 0x40000040, int M>
__device__ __forceinline__ void wgmma_n224(float (&d)[M], uint32_t da, uint32_t db, int scale_d) {
    asm volatile("{\n.reg .pred p;\n.reg .b32 hi, ha;\n.reg .b64 da, db;\nmov.b32 hi, 0x40000040;\nmov.b32 ha, %117;\nmov.b64 da, {%112, ha};\nmov.b64 db, {%113, hi};\nsetp.ne.b32 p, %114, 0;\n"
        "wgmma.mma_async.sync.aligned.m64n224k16.f32.bf16.bf16 "
        "{%0, %1, %2, %3, %4, %5, %6, %7, %8, %9, %10, %11, %12, %13, %14, %15, "
        "%16, %17, %18, %19, %20, %21, %22, %23, %24, %25, %26, %27, %28, %29, %30, %31, "
        "%32, %33, %34, %35, %36, %37, %38, %39, %40, %41, %42, %43, %44, %45, %46, %47, "
        "%48, %49, %50, %51, %52, %53, %54, %55, %56, %57, %58, %59, %60, %61, %62, %63, "
        "%64, %65, %66, %67, %68, %69, %70, %71, %72, %73, %74, %75, %76, %77, %78, %79, "
        "%80, %81, %82, %83, %84, %85, %86, %87, %88, %89, %90, %91, %92, %93, %94, %95, "
        "%96, %97, %98, %99, %100, %101, %102, %103, %104, %105, %106, %107, %108, %109, %110, %111}, "
        "da, db, p, %116, 1, 0, %115;\n}\n"
        : "+f"(d[0]), "+f"(d[1]), "+f"(d[2]), "+f"(d[3]), "+f"(d[4]), "+f"(d[5]), "+f"(d[6]), "+f"(d[7]),
          "+f"(d[8]), "+f"(d[9]), "+f"(d[10]), "+f"(d[11]), "+f"(d[12]), "+f"(d[13]), "+f"(d[14]), "+f"(d[15]),
          "+f"(d[16]), "+f"(d[17]), "+f"(d[18]), "+f"(d[19]), "+f"(d[20]), "+f"(d[21]), "+f"(d[22]), "+f"(d[23]),
          "+f"(d[24]), "+f"(d[25]), "+f"(d[26]), "+f"(d[27]), "+f"(d[28]), "+f"(d[29]), "+f"(d[30]), "+f"(d[31]),
          "+f"(d[32]), "+f"(d[33]), "+f"(d[34]), "+f"(d[35]), "+f"(d[36]), "+f"(d[37]), "+f"(d[38]), "+f"(d[39]),
          "+f"(d[40]), "+f"(d[41]), "+f"(d[42]), "+f"(d[43]), "+f"(d[44]), "+f"(d[45]), "+f"(d[46]), "+f"(d[47]),
          "+f"(d[48]), "+f"(d[49]), "+f"(d[50]), "+f"(d[51]), "+f"(d[52]), "+f"(d[53]), "+f"(d[54]), "+f"(d[55]),
          "+f"(d[56]), "+f"(d[57]), "+f"(d[58]), "+f"(d[59]), "+f"(d[60]), "+f"(d[61]), "+f"(d[62]), "+f"(d[63]),
          "+f"(d[64]), "+f"(d[65]), "+f"(d[66]), "+f"(d[67]), "+f"(d[68]), "+f"(d[69]), "+f"(d[70]), "+f"(d[71]),
          "+f"(d[72]), "+f"(d[73]), "+f"(d[74]), "+f"(d[75]), "+f"(d[76]), "+f"(d[77]), "+f"(d[78]), "+f"(d[79]),
          "+f"(d[80]), "+f"(d[81]), "+f"(d[82]), "+f"(d[83]), "+f"(d[84]), "+f"(d[85]), "+f"(d[86]), "+f"(d[87]),
          "+f"(d[88]), "+f"(d[89]), "+f"(d[90]), "+f"(d[91]), "+f"(d[92]), "+f"(d[93]), "+f"(d[94]), "+f"(d[95]),
          "+f"(d[96]), "+f"(d[97]), "+f"(d[98]), "+f"(d[99]), "+f"(d[100]), "+f"(d[101]), "+f"(d[102]), "+f"(d[103]),
          "+f"(d[104]), "+f"(d[105]), "+f"(d[106]), "+f"(d[107]), "+f"(d[108]), "+f"(d[109]), "+f"(d[110]), "+f"(d[111])
        : "r"(da), "r"(db), "r"(scale_d), "n"(TB), "n"(SA), "n"(HA));
}
template<int TB, int SA = 1>
__device__ __forceinline__ void wgmma_rs_n32(float (&d)[16], const uint32_t (&a)[4], uint32_t db, int scale_d) {
    asm volatile("{\n.reg .pred p;\n.reg .b32 hi;\n.reg .b64 db;\nmov.b32 hi, 0x40000040;\nmov.b64 db, {%20, hi};\nsetp.ne.b32 p, %21, 0;\n"
        "wgmma.mma_async.sync.aligned.m64n32k16.f32.bf16.bf16 "
        "{%0, %1, %2, %3, %4, %5, %6, %7, %8, %9, %10, %11, %12, %13, %14, %15}, "
        "{%16, %17, %18, %19}, db, p, %23, 1, %22;\n}\n"
        : "+f"(d[0]), "+f"(d[1]), "+f"(d[2]), "+f"(d[3]), "+f"(d[4]), "+f"(d[5]), "+f"(d[6]), "+f"(d[7]),
          "+f"(d[8]), "+f"(d[9]), "+f"(d[10]), "+f"(d[11]), "+f"(d[12]), "+f"(d[13]), "+f"(d[14]), "+f"(d[15])
        : "r"(a[0]), "r"(a[1]), "r"(a[2]), "r"(a[3]), "r"(db), "r"(scale_d), "n"(TB), "n"(SA));
}
template<int TB, int SA = 1>
__device__ __forceinline__ void wgmma_rs_n56(float (&d)[28], const uint32_t (&a)[4], uint32_t db, int scale_d) {
    asm volatile("{\n.reg .pred p;\n.reg .b32 hi;\n.reg .b64 db;\nmov.b32 hi, 0x40000040;\nmov.b64 db, {%32, hi};\nsetp.ne.b32 p, %33, 0;\n"
        "wgmma.mma_async.sync.aligned.m64n56k16.f32.bf16.bf16 "
        "{%0, %1, %2, %3, %4, %5, %6, %7, %8, %9, %10, %11, %12, %13, %14, %15, "
        "%16, %17, %18, %19, %20, %21, %22, %23, %24, %25, %26, %27}, "
        "{%28, %29, %30, %31}, db, p, %35, 1, %34;\n}\n"
        : "+f"(d[0]), "+f"(d[1]), "+f"(d[2]), "+f"(d[3]), "+f"(d[4]), "+f"(d[5]), "+f"(d[6]), "+f"(d[7]),
          "+f"(d[8]), "+f"(d[9]), "+f"(d[10]), "+f"(d[11]), "+f"(d[12]), "+f"(d[13]), "+f"(d[14]), "+f"(d[15]),
          "+f"(d[16]), "+f"(d[17]), "+f"(d[18]), "+f"(d[19]), "+f"(d[20]), "+f"(d[21]), "+f"(d[22]), "+f"(d[23]),
          "+f"(d[24]), "+f"(d[25]), "+f"(d[26]), "+f"(d[27])
        : "r"(a[0]), "r"(a[1]), "r"(a[2]), "r"(a[3]), "r"(db), "r"(scale_d), "n"(TB), "n"(SA));
}
template<int TB, int SA = 1>
__device__ __forceinline__ void wgmma_rs_n64(float (&d)[32], const uint32_t (&a)[4], uint32_t db, int scale_d) {
    asm volatile("{\n.reg .pred p;\n.reg .b32 hi;\n.reg .b64 db;\nmov.b32 hi, 0x40000040;\nmov.b64 db, {%36, hi};\nsetp.ne.b32 p, %37, 0;\n"
        "wgmma.mma_async.sync.aligned.m64n64k16.f32.bf16.bf16 "
        "{%0, %1, %2, %3, %4, %5, %6, %7, %8, %9, %10, %11, %12, %13, %14, %15, "
        "%16, %17, %18, %19, %20, %21, %22, %23, %24, %25, %26, %27, %28, %29, %30, %31}, "
        "{%32, %33, %34, %35}, db, p, %39, 1, %38;\n}\n"
        : "+f"(d[0]), "+f"(d[1]), "+f"(d[2]), "+f"(d[3]), "+f"(d[4]), "+f"(d[5]), "+f"(d[6]), "+f"(d[7]),
          "+f"(d[8]), "+f"(d[9]), "+f"(d[10]), "+f"(d[11]), "+f"(d[12]), "+f"(d[13]), "+f"(d[14]), "+f"(d[15]),
          "+f"(d[16]), "+f"(d[17]), "+f"(d[18]), "+f"(d[19]), "+f"(d[20]), "+f"(d[21]), "+f"(d[22]), "+f"(d[23]),
          "+f"(d[24]), "+f"(d[25]), "+f"(d[26]), "+f"(d[27]), "+f"(d[28]), "+f"(d[29]), "+f"(d[30]), "+f"(d[31])
        : "r"(a[0]), "r"(a[1]), "r"(a[2]), "r"(a[3]), "r"(db), "r"(scale_d), "n"(TB), "n"(SA));
}
template<int TB, int SA = 1>
__device__ __forceinline__ void wgmma_rs_n96(float (&d)[48], const uint32_t (&a)[4], uint32_t db, int scale_d) {
    asm volatile("{\n.reg .pred p;\n.reg .b32 hi;\n.reg .b64 db;\nmov.b32 hi, 0x40000040;\nmov.b64 db, {%52, hi};\nsetp.ne.b32 p, %53, 0;\n"
        "wgmma.mma_async.sync.aligned.m64n96k16.f32.bf16.bf16 "
        "{%0, %1, %2, %3, %4, %5, %6, %7, %8, %9, %10, %11, %12, %13, %14, %15, "
        "%16, %17, %18, %19, %20, %21, %22, %23, %24, %25, %26, %27, %28, %29, %30, %31, "
        "%32, %33, %34, %35, %36, %37, %38, %39, %40, %41, %42, %43, %44, %45, %46, %47}, "
        "{%48, %49, %50, %51}, db, p, %55, 1, %54;\n}\n"
        : "+f"(d[0]), "+f"(d[1]), "+f"(d[2]), "+f"(d[3]), "+f"(d[4]), "+f"(d[5]), "+f"(d[6]), "+f"(d[7]),
          "+f"(d[8]), "+f"(d[9]), "+f"(d[10]), "+f"(d[11]), "+f"(d[12]), "+f"(d[13]), "+f"(d[14]), "+f"(d[15]),
          "+f"(d[16]), "+f"(d[17]), "+f"(d[18]), "+f"(d[19]), "+f"(d[20]), "+f"(d[21]), "+f"(d[22]), "+f"(d[23]),
          "+f"(d[24]), "+f"(d[25]), "+f"(d[26]), "+f"(d[27]), "+f"(d[28]), "+f"(d[29]), "+f"(d[30]), "+f"(d[31]),
          "+f"(d[32]), "+f"(d[33]), "+f"(d[34]), "+f"(d[35]), "+f"(d[36]), "+f"(d[37]), "+f"(d[38]), "+f"(d[39]),
          "+f"(d[40]), "+f"(d[41]), "+f"(d[42]), "+f"(d[43]), "+f"(d[44]), "+f"(d[45]), "+f"(d[46]), "+f"(d[47])
        : "r"(a[0]), "r"(a[1]), "r"(a[2]), "r"(a[3]), "r"(db), "r"(scale_d), "n"(TB), "n"(SA));
}
template<int TB, int SA = 1>
__device__ __forceinline__ void wgmma_rs_n112(float (&d)[56], const uint32_t (&a)[4], uint32_t db, int scale_d) {
    asm volatile("{\n.reg .pred p;\n.reg .b32 hi;\n.reg .b64 db;\nmov.b32 hi, 0x40000040;\nmov.b64 db, {%60, hi};\nsetp.ne.b32 p, %61, 0;\n"
        "wgmma.mma_async.sync.aligned.m64n112k16.f32.bf16.bf16 "
        "{%0, %1, %2, %3, %4, %5, %6, %7, %8, %9, %10, %11, %12, %13, %14, %15, "
        "%16, %17, %18, %19, %20, %21, %22, %23, %24, %25, %26, %27, %28, %29, %30, %31, "
        "%32, %33, %34, %35, %36, %37, %38, %39, %40, %41, %42, %43, %44, %45, %46, %47, "
        "%48, %49, %50, %51, %52, %53, %54, %55}, "
        "{%56, %57, %58, %59}, db, p, %63, 1, %62;\n}\n"
        : "+f"(d[0]), "+f"(d[1]), "+f"(d[2]), "+f"(d[3]), "+f"(d[4]), "+f"(d[5]), "+f"(d[6]), "+f"(d[7]),
          "+f"(d[8]), "+f"(d[9]), "+f"(d[10]), "+f"(d[11]), "+f"(d[12]), "+f"(d[13]), "+f"(d[14]), "+f"(d[15]),
          "+f"(d[16]), "+f"(d[17]), "+f"(d[18]), "+f"(d[19]), "+f"(d[20]), "+f"(d[21]), "+f"(d[22]), "+f"(d[23]),
          "+f"(d[24]), "+f"(d[25]), "+f"(d[26]), "+f"(d[27]), "+f"(d[28]), "+f"(d[29]), "+f"(d[30]), "+f"(d[31]),
          "+f"(d[32]), "+f"(d[33]), "+f"(d[34]), "+f"(d[35]), "+f"(d[36]), "+f"(d[37]), "+f"(d[38]), "+f"(d[39]),
          "+f"(d[40]), "+f"(d[41]), "+f"(d[42]), "+f"(d[43]), "+f"(d[44]), "+f"(d[45]), "+f"(d[46]), "+f"(d[47]),
          "+f"(d[48]), "+f"(d[49]), "+f"(d[50]), "+f"(d[51]), "+f"(d[52]), "+f"(d[53]), "+f"(d[54]), "+f"(d[55])
        : "r"(a[0]), "r"(a[1]), "r"(a[2]), "r"(a[3]), "r"(db), "r"(scale_d), "n"(TB), "n"(SA));
}
template<int TB, int SA = 1>
__device__ __forceinline__ void wgmma_rs_n224(float (&d)[112], const uint32_t (&a)[4], uint32_t db, int scale_d) {
    asm volatile("{\n.reg .pred p;\n.reg .b32 hi;\n.reg .b64 db;\nmov.b32 hi, 0x40000040;\nmov.b64 db, {%116, hi};\nsetp.ne.b32 p, %117, 0;\n"
        "wgmma.mma_async.sync.aligned.m64n224k16.f32.bf16.bf16 "
        "{%0, %1, %2, %3, %4, %5, %6, %7, %8, %9, %10, %11, %12, %13, %14, %15, "
        "%16, %17, %18, %19, %20, %21, %22, %23, %24, %25, %26, %27, %28, %29, %30, %31, "
        "%32, %33, %34, %35, %36, %37, %38, %39, %40, %41, %42, %43, %44, %45, %46, %47, "
        "%48, %49, %50, %51, %52, %53, %54, %55, %56, %57, %58, %59, %60, %61, %62, %63, "
        "%64, %65, %66, %67, %68, %69, %70, %71, %72, %73, %74, %75, %76, %77, %78, %79, "
        "%80, %81, %82, %83, %84, %85, %86, %87, %88, %89, %90, %91, %92, %93, %94, %95, "
        "%96, %97, %98, %99, %100, %101, %102, %103, %104, %105, %106, %107, %108, %109, %110, %111}, "
        "{%112, %113, %114, %115}, db, p, %119, 1, %118;\n}\n"
        : "+f"(d[0]), "+f"(d[1]), "+f"(d[2]), "+f"(d[3]), "+f"(d[4]), "+f"(d[5]), "+f"(d[6]), "+f"(d[7]),
          "+f"(d[8]), "+f"(d[9]), "+f"(d[10]), "+f"(d[11]), "+f"(d[12]), "+f"(d[13]), "+f"(d[14]), "+f"(d[15]),
          "+f"(d[16]), "+f"(d[17]), "+f"(d[18]), "+f"(d[19]), "+f"(d[20]), "+f"(d[21]), "+f"(d[22]), "+f"(d[23]),
          "+f"(d[24]), "+f"(d[25]), "+f"(d[26]), "+f"(d[27]), "+f"(d[28]), "+f"(d[29]), "+f"(d[30]), "+f"(d[31]),
          "+f"(d[32]), "+f"(d[33]), "+f"(d[34]), "+f"(d[35]), "+f"(d[36]), "+f"(d[37]), "+f"(d[38]), "+f"(d[39]),
          "+f"(d[40]), "+f"(d[41]), "+f"(d[42]), "+f"(d[43]), "+f"(d[44]), "+f"(d[45]), "+f"(d[46]), "+f"(d[47]),
          "+f"(d[48]), "+f"(d[49]), "+f"(d[50]), "+f"(d[51]), "+f"(d[52]), "+f"(d[53]), "+f"(d[54]), "+f"(d[55]),
          "+f"(d[56]), "+f"(d[57]), "+f"(d[58]), "+f"(d[59]), "+f"(d[60]), "+f"(d[61]), "+f"(d[62]), "+f"(d[63]),
          "+f"(d[64]), "+f"(d[65]), "+f"(d[66]), "+f"(d[67]), "+f"(d[68]), "+f"(d[69]), "+f"(d[70]), "+f"(d[71]),
          "+f"(d[72]), "+f"(d[73]), "+f"(d[74]), "+f"(d[75]), "+f"(d[76]), "+f"(d[77]), "+f"(d[78]), "+f"(d[79]),
          "+f"(d[80]), "+f"(d[81]), "+f"(d[82]), "+f"(d[83]), "+f"(d[84]), "+f"(d[85]), "+f"(d[86]), "+f"(d[87]),
          "+f"(d[88]), "+f"(d[89]), "+f"(d[90]), "+f"(d[91]), "+f"(d[92]), "+f"(d[93]), "+f"(d[94]), "+f"(d[95]),
          "+f"(d[96]), "+f"(d[97]), "+f"(d[98]), "+f"(d[99]), "+f"(d[100]), "+f"(d[101]), "+f"(d[102]), "+f"(d[103]),
          "+f"(d[104]), "+f"(d[105]), "+f"(d[106]), "+f"(d[107]), "+f"(d[108]), "+f"(d[109]), "+f"(d[110]), "+f"(d[111])
        : "r"(a[0]), "r"(a[1]), "r"(a[2]), "r"(a[3]), "r"(db), "r"(scale_d), "n"(TB), "n"(SA));
}

#define TR(idx) do {} while (0)
#define TRL(idx) do {} while (0)
#define TRX(idx) do {} while (0)
#define TRG(idx) do {} while (0)
#define TR_END() do {} while (0)

template<int V> struct Int { static constexpr int value = V; };
constexpr float ATT_SCALE = 0.18898223650461361f;
constexpr float LOG2E = 1.4426950408889634f;
constexpr uint32_t MASKED = 0xce6ece6eu;

__global__ void __cluster_dims__(2, 1, 1) __launch_bounds__(384, 1)
fused_kernel(__nv_bfloat16* __restrict__ out,
    const __grid_constant__ TMaps tm) {
    extern __shared__ __align__(1024) uint8_t smem_raw[];
    const uint32_t sb = smem_u32(smem_raw);
    const uint32_t bars = sb + BAR_OFF;
    const uint32_t bar_full = bars, bar_empty = bars + 32, bar_abf = bars + 64  , bar_ab = bars + 128  , bar_free = bars + 296  , bar_halo = bars + 152;
    const uint32_t bar_o = bars + 160, bar_qkv = bars + 176  , bar_sf = bars + 200, bar_se = bar_sf + 32  ;
    const uint32_t bar_fl = bars + 256  , bar_go = bars + 240  , bar_end = bars + 192, bar_af = bars + 312;
    const uint32_t stg = sb + STG_OFF;
    const int cta = blockIdx.x, r = cta & 1, cl = cta >> 1;
    const int place = pick3(cta, 32 + 8 * cl, cl - 4, cl - 3 + ((cl * 37 - 36 * 37) >> 8));
    const int mt = (place & 7) * 2 + r;
    const int sub = place >> 3;
    const CUtensorMap* tmWd = sub < 4 ? &tm.wdre : &tm.wdim;
    uint32_t t_first = 0;
    if (threadIdx.x < 32 + (((uint32_t)(uintptr_t)tmWd | sb | (mt << 6)) & 32) && elect_one()) {
        prefetch_tmap(tmWd); prefetch_tmap(&tm.xB);
        #pragma unroll
        for (int kb = 0; kb < START_N; kb++) {
            mbar_init(bar_abf + 8 * kb, 1);
            mbar_expect_tx(bar_abf + 8 * kb, AB_BYTES);
            tma_load(sb + kb * AB_BYTES + SLOT_A, tmWd, bar_abf + 8 * kb, kb * 64, (sub & 3) * 112);
            tma_load(sb + kb * AB_BYTES, &tm.xB, bar_abf + 8 * kb, kb * 64, mt * 128);
        }
        t_first = clk32();
    }
    const int tid = threadIdx.x, warp = __shfl_sync(0xffffffffu, tid >> 5, 0), lane = tid & 31;
    const bool late = sub < 4;
    const int nh = sub & 1, part = (sub >> 1) & 1;
    const int nj = late ? 32 - KB_EARLY : KB_EARLY;
    static_assert(KB_EARLY == 14, "order of the k-blocks");
    const uint32_t t0 = clk32();
    auto clear_out = [&]() {
        while ((int)(clk32() - t0) < TP(ZERO_AT)) { }
        uint4* zp = reinterpret_cast<uint4*>(out + (size_t)(mt * 128 + sub * 16 + (warp - 2) * 8) * NOUT + DM) + lane;
        #pragma unroll 1
        for (int j = 0; j < (ABL & 8 ? 0 : 8); j++) {
            while ((int)(clk32() - t0) < TP(ZERO_AT) + j * TP(ZERO_GAP)) { }
            zp[j * (NOUT / 8)] = make_uint4(0, 0, 0, 0);
            if (lane < 24) zp[j * (NOUT / 8) + 32] = make_uint4(0, 0, 0, 0);
        }
    };
    if (warp == 0) {
        if (elect_one()) {
            #pragma unroll
            for (int s = START_N; s < 7; s++) mbar_init(bar_abf + 8 * s, 1);
            #pragma unroll
            for (int s = 0; s < NSLOT; s++) { mbar_init(bar_full + 8 * s, 1); mbar_init(bar_empty + 8 * s, 4); }
            asm volatile("fence.mbarrier_init.release.cluster;" ::: "memory");
        }
        __syncwarp();
        cluster_arrive();
        if (elect_one()) {
            #pragma unroll 1
            for (int kb = START_N; kb < 7; kb++) {
                while ((int)(clk32() - t_first) < TP(START_GAP1) + (kb - START_N) * TP(START_GAP)) { }
                const uint32_t a = sb + kb * AB_BYTES, fb = bar_abf + 8 * kb;
                mbar_expect_tx(fb, AB_BYTES);
                tma_load(a, &tm.xB, fb, kb * 64, mt * 128);
                tma_load(a + SLOT_A, tmWd, fb, kb * 64, (sub & 3) * 112);
            }
            TR(2);
            prefetch_tmap(&tm.xA3); prefetch_tmap(&tm.wqkv3);
        }
        __syncwarp();
    } else if (warp < 4) {
        cluster_arrive();
        if (warp >= 2) clear_out();
    }
    if (warp < 4) {
      reg_set<REG_AUX>();
      const CUtensorMap* tmB = r ? &tm.abP3 : &tm.abP4;
      const uint32_t boff = SLOT_A + r * 16384;
      const int bgrp = part * 14 + nh * 7 + r * 4;
      if (warp == 0) {
        cluster_wait();
        if (elect_one()) {
        uint32_t slot = sb, fb = bar_full, par = 0;
        auto advance = [&]() { if (fb == bar_full + 24) { fb = bar_full; slot = sb; par ^= 1; } else { fb += 8; slot += SLOT_BYTES; } };
        const CUtensorMap* tmW = part ? &tm.wim : &tm.wre;
        const CUtensorMap* tmH = part ? &tm.wimH : &tm.wreH;
        const int qc = sub * 56 - (sub & 1) * 8;
        auto next_kc = [&](int kc, int wi) { return wi == 3 ? (late ? 14 * 64 : 2 * 64) : wi == nj / 2 - 1 ? (late ? 15 * 64 : 64) : kc + (FLIP && wi == 1 ? -768 : wi < nj / 2 ? 256 : 128); };
        #pragma unroll 1
        for (int it = 0; it < 7; it++) {
            mbar_wait_p(fb + 32, par);
            mbar_expect_tx(fb, SLOT_A + 3 * 8192);
            tma_load3(slot, &tm.xA3, fb, it * 64, mt * 64);
            tma_load3_mc(slot + SLOT_A + r * 12288, &tm.wqkv3, fb, qc, it * 64 + r * 32, 0);
            TRL(64 + it);
            if (r && it == 2) {
                const int c = (7 - sub) * 8 + (mt >> 1), c7 = (c * 37) >> 8;
                tma_prefetch3(&tm.xA3, (3 + (sub >> 1)) * 64, (mt - (sub & 1)) * 64);
                if (c7 < 8) tma_prefetch3(&tm.wqkv3, (c - 7 * c7) * 64, 192 + c7 * 32);
            }
            if (it == 1) { prefetch_tmap(tmW); prefetch_tmap(tmB); prefetch_tmap(tmH); }
            advance();
        }
        int kc = (late ? 1024 : 0) + 512 * FLIP;
        #pragma unroll 1
        for (int wi = 0; wi < nj - late; wi++) {
            mbar_wait_p(fb + 32, par);
            if (TP(W_GAP) && wi > 0 && wi < 4) { const uint32_t t1 = clk32() + TP(W_GAP); while ((int)(clk32() - t1) < 0) { } }
            mbar_expect_tx(fb, SLOT_BYTES);
            tma_load(slot, tmW, fb, kc, mt * 128);
            TR(224 + 7 + wi);
            if (wi >= 4) {
                if (wi == 4 || wi == nj / 2) mbar_wait(bar_fl + (wi == 4 ? 16 : 24), 0);
                tma_load5_mc(slot + boff, tmB, fb, kc, bgrp);
                TR(64 + 7 + wi);
            } else mbar_arrive(bar_go + 8 * wi);
            advance();
            kc = next_kc(kc, wi);
            if (wi == (late ? TP(PF_L) : TP(PF_E))) tma_prefetch(tmH, (late ? 29 : 13) * 64, mt * 128 + nh * 64);
            if (late) {
                if (wi == TP(L_XAT) - 1) {
                    mbar_wait(bar_se, 0);
                    mbar_expect_tx(bar_sf, SLOT_BYTES);
                    tma_load5_mc(stg + boff, tmB, bar_sf, 31 * 64, bgrp);
                }
                if (wi == TP(L_XAT)) tma_load(stg, tmW, bar_sf, 31 * 64, mt * 128);
            } else if (wi == TP(WB_AT)) {
                mbar_wait(bar_se, 0);
                #pragma unroll
                for (int j = 1; j < 7; j += 2) tma_load_mc(sb + OUT_B(j) + r * 8192, &tm.wo64, bar_abf, 256 + 48 * (sub & 3), (j + r) * 64);
            } else if (wi == TP(WO_AT) - 1) {
                const int c = mt * 4 + (sub & 3), c7 = (c * 37) >> 8;
                if (c < 49) tma_prefetch(&tm.wo64, (c - 7 * c7) * 64, c7 * 64); else prefetch_tmap(&tm.wo64);
            }
        }
        if (!late) {
            const uint4* const po = g_o + mt * 7168;
            const int ca = 64 * (sub & 3), cb = 256 + 48 * (sub & 3);
            auto load_w = [&](int d0, int c0, int j0, int d1, int c1, int j1, int g) { tma_load_mc(sb + (r ? d1 : d0), &tm.wo64, bar_abf + 8 * g, r ? c1 : c0, (r ? j1 : j0) * 64); };
            auto load_o = [&](int p, int j, int n, int g) { bulk_load(sb + OUT_O(p, j), po + p * 3584 + j * 512, n * 8192, bar_abf + 8 * g); };
            #pragma unroll
            for (int g = 0; g < 5; g++) mbar_expect_tx(bar_abf + 8 * g, (g == 0 ? 11 : g == 2 ? 5 : 4) * 8192);
            mbar_wait_p(bar_empty + 8, 1);
            load_w(OUT_A(0), ca, 0, OUT_A(1), ca, 1, 0);
            if (r == 0) load_w(OUT_B(0), cb, 0, 0, 0, 0, 0);
            TR(64 + 7 + KB_EARLY);
            mbar_wait_p(bar_fl + 32, 0);
            TR(3);
            load_o(0, 0, 2, 0);
            mbar_wait_p(bar_af, 0);
            load_w(OUT_A(2), ca, 2, OUT_A(3), ca, 3, 1); load_o(0, 2, 2, 1);
            if (r) load_w(0, 0, 0, OUT_A(4), ca, 4, 2);
            TR(64 + 7 + KB_EARLY + 1);
            mbar_wait_p(bar_empty + 16, 1);
            load_o(0, 4, 2, 2); load_w(OUT_A(5), ca, 5, OUT_A(6), ca, 6, 2);
            TR(64 + 7 + KB_EARLY + 2);
            mbar_wait_p(bar_empty + 24, 1);
            load_o(0, 6, 4, 3);
            TR(64 + 7 + KB_EARLY + 3);
            mbar_wait_p(bar_empty, 0);
            load_o(1, 3, 4, 4);
            TR(64 + 7 + KB_EARLY + 4);
        }
        mbar_arrive(bar_end);
        }
      } else {
        const unsigned epoch = ld_relaxed(&g_epoch[cta * 8]) + 1;
        cluster_wait();
        auto forward = [&](const unsigned* fl, unsigned target, auto first, uint32_t bar, uint32_t again) {
            for (int spin = 0; !__all_sync(0xffffffffu, (int)(ld_acquire(fl) - target) >= 0);) {
                if ((int)(clk32() - again) < 0) { while ((int)(clk32() - again) < 0) { } } else __nanosleep(target != epoch ? TP(OPOLL_NS) : TP(POLL_NS));
                if (++spin > SPIN_LIMIT) give_up();
            }
            if (elect_one()) {
                fence_async_global();
                if constexpr (decltype(first)::value == 2) { if (atomicExch(reinterpret_cast<unsigned*>(smem_raw + BAR_OFF + 144), 1u) == 0) mbar_arrive(bar); }
                else if constexpr (!decltype(first)::value) mbar_arrive(bar);
                else {
                    #pragma unroll
                    for (int i = 0; i < 2; i++) {
                        const int wi = 2 * (warp - 2) + i, sl = (wi + 3) & 3;
                        mbar_wait_limit(bar_go + 8 * wi, 0);
                        tma_load5_mc(sb + sl * SLOT_BYTES + boff, tmB, bar_full + 8 * sl, (late ? 1024 : 0) + 256 * (wi ^ 2 * FLIP), bgrp);
                        TR(64 + 7 + wi);
                        if (i == 0) { const uint32_t t1 = clk32() + TP(BIG_GAP); while ((int)(clk32() - t1) < 0) { } }
                    }
                }
            }
            __syncwarp();
        };
        const int frow = part * 4 + nh * 2 + (lane & 1), st0 = late ? 8 : 0;
        const int ft = late ? min(7 + (lane >> 1), 15) : min(lane >> 1, 6);
        const unsigned* const fl2 = &g_flag_ab[(32 + frow) * 32 + (late ? min(7 + (lane & 14), 15) : min(1 + (lane & 14), 5))];
        const unsigned* const fl3 = &g_flag_ab[(16 + 8 * (ft & 1) + frow) * 32 + ft];
        if (warp == 1) {
            if (elect_one()) {
                prefetch_tmap(&tm.abH); if (BIG_ST) { prefetch_tmap(&tm.ab80); prefetch_tmap(&tm.ab32); }
                const int e0 = pin(sub * 112 - (sub & 2) * 16), e1 = pin((sub & 3) == 2 ? 224 : 0);
                #pragma unroll 1
                for (int hf = 0; hf < 2; hf++) {
                    const int gap = pin(hf ? (r ? TP(ABS_GAP3) : TP(ABS_GAP2)) : (r ? TP(ABS_GAP) : 0)), sc = pin(mt * 128 + hf * 64);
                    const uint32_t src = pin(hf ? stg : sb + 7 * AB_BYTES);
                    unsigned* const fl = pin(&g_flag_ab[((hf ? 2 + r : r ? 4 : URG(mt)) * 8 + sub) * 32 + mt]);
                    mbar_wait(bar_ab + 8 * hf, 0);
                    fence_async_smem();
                    uint32_t t1 = clk32() + (hf ? 0 : r ? TP(ABS_AT) : URG(mt) * TP(ABS_AT1));
                    if (BIG_ST && (hf | r) == 0) {
                        if (URG(mt)) { while ((int)(clk32() - t1) < 0) { } }
                        TR(4);
                        tma_store(&tm.ab80, src + 4096, sc, e0 + 32);
                        tma_store(&tm.ab32, src, sc, e0 + e1);
                    } else
                    #pragma unroll
                    for (int i = 0; i < 7; i++) {
                        if (i == 0 || gap) { while ((int)(clk32() - t1) < 0) { } }
                        t1 += gap;
                        if (i == 0 && hf == 0) TR(4);
                        if (hf > r && i % 3 == 0 && i / 3 < TP(PF_N)) tma_prefetch(part ? &tm.wim : &tm.wre, (late ? 1024 : 0) + ((i / 3) ^ 2 * FLIP) * 256, (mt + nh) * 128);
                        tma_store(&tm.abH, src + i * 2048, sc, e0 + i * 16 + (i < 2 ? e1 : 0));
                    }
                    bulk_commit();
                    bulk_wait_all();
                    if (hf) TR(5);
                    mbar_arrive(bar_free + 8 * hf);
                    st_release(fl, epoch);
                    TR(hf ? 6 : 38);
                }
                uint4* const po = pin(g_o + mt * 7168 + sub * 448);
                mbar_wait(bar_o, 0);
                fence_async_smem();
                TR(9);
                {
                    uint32_t t2 = clk32();
                    #pragma unroll 1
                    for (int i = 0; i < 2 * O_N; i++) {
                        while ((int)(clk32() - t2) < 0) { }
                        t2 += TP(O_GAP);
                        bulk_store(po + (i >= O_N ? 3584 - 448 : 0) + i * (448 / O_N), stg + i * (7168 / O_N), 7168 / O_N);
                    }
                }
                bulk_commit();
                TR(62);
                bulk_wait_all();
                TR(111);
                mbar_arrive(bar_se); mbar_arrive_remote(bar_se, r ^ 1);
                red_release(&g_flag_o[mt * 32], 1);
                TR(17); TRG(102);
                if (!late) {
                    prefetch_tmap(&tm.outA); prefetch_tmap(&tm.outB);
                    #pragma unroll
                    for (int c = 0; c < 2; c++) {
                        mbar_wait(bar_qkv + 8 * c, 1);
                        fence_async_smem();
                        tma_store3(c ? &tm.outB : &tm.outA, sb + OUT_ST + c * 8192, mt * 64, sub & 3);
                    }
                    bulk_commit();
                    asm volatile("cp.async.bulk.wait_group.read 0;" ::: "memory");
                    TR(19);
                }
            }
            __syncwarp();
        } else {
            asm volatile("st.shared.u32 [%0], %1;" :: "r"(bars + 168), "r"(epoch) : "memory");
            if (OPOLL2_ON) asm volatile("st.shared.u32 [%0], %1;" :: "r"(bars + 144), "r"(0) : "memory");
            __syncwarp();
            if (lane == 0) mbar_arrive(bar_ab + 8);
            mbar_wait_limit(bar_ab, 0);
            const uint32_t ta = clk32();
            if (tid == 96) TRG(98);
            const bool rest = warp == 3 && __all_sync(0xffffffffu, (int)(ld_acquire(lane >= 22 ? fl2 : fl3) - epoch) >= 0);
            forward(&g_flag_ab[((warp - 2) * 8 + frow) * 32 + st0 + 4 * ((warp - 2) ^ FLIP) + (lane & 2)], epoch, Int<1>(), 0, ta + (warp == 2 ? TP(POLL_AT) : TP(POLL_AT1)));
            if (warp == 2) {
                const uint4* const hp = pin(g_halo + (max(mt - 1, 0) * 8 + sub) * 320 + lane);
                const uint32_t ha = pin(stg + KV_OFF + (lane & 7) * KV_PITCH + (lane >> 3) * 16);
                mbar_wait(mt > 0 ? bar_go + 24 : bar_qkv, 0);
                uint4 v[10];
                if (mt > 0) {
                    const uint32_t tq = clk32();
                    while ((int)(clk32() - tq) < TP(HALO_WAIT)) { }
                    #pragma unroll 1
                    for (;;) {
                        uint32_t bad = 0;
                        #pragma unroll
                        for (int j = 0; j < 10; j++) v[j] = ld_b128_relaxed(hp + j * 32);
                        #pragma unroll
                        for (int j = 0; j < 10; j++) bad |= v[j].w ^ epoch;
                        if (__all_sync(0xffffffffu, bad == 0) || (ABL & 1)) break;
                        __nanosleep(200);
                    }
                } else {
                    const uint32_t r0 = stg + KV_OFF + 8 * KV_PITCH + 112 + (lane & 3) * 4;
                    v[0].x = v[0].y = v[0].z = v[1].x = v[1].y = v[1].z = v[2].x = 0;
                    v[2].y = lds32(r0); v[2].z = lds32(r0 + 16); v[3].x = lds32(r0 + 32); v[3].y = lds32(r0 + 48); v[3].z = lds32(r0 + 64); v[4].x = lds32(r0 + 80); v[4].y = lds32(r0 + 96);
                    #pragma unroll
                    for (int j = 0; j < 5; j++) v[5 + j] = v[j];
                }
                mbar_wait(bar_free, 0);
                #pragma unroll
                for (int p = 0; p < 2; p++) {
                    const uint4* u = v + 5 * p;
                    stsm_x4(ha + p * KV_PAR, u[0].x, u[0].y, u[0].z, u[1].x);
                    stsm_x4(ha + p * KV_PAR + 64, u[1].y, u[1].z, u[2].x, u[2].y);
                    stsm_x4(ha + p * KV_PAR + 128, u[2].z, u[3].x, u[3].y, u[3].z);
                    stsm_x2(ha + p * KV_PAR + 192, u[4].x, u[4].y);
                }
                __syncwarp();
                if (lane == 0) { mbar_arrive(bar_halo); TR(10); TRG(100); }
                if (OPOLL2_ON && !late) {
                    mbar_wait(bar_ab + 8, 0);
                    const uint32_t at = ta + TP(OPOLL_AT) + TP(OPOLL2);
                    while ((int)(clk32() - at) < 0) { }
                    forward(&g_flag_o[mt * 32], epoch * 8, Int<2>(), bar_fl + 32, at);
                }
            } else {
                #pragma unroll 1
                for (int j = 2; j < (late ? 4 : 5); j++) {
                    const unsigned* const fl = j == 2 ? fl2 : j == 4 ? &g_flag_o[mt * 32] : lane < 24 ? fl3 : &g_flag_ab[(16 + 8 * r + (lane & 7)) * 32 + mt];
                    const uint32_t at = ta + (j == 2 ? TP(POLL_AT2) : j == 3 ? TP(POLL_AT3) : TP(OPOLL_AT));
                    if (!rest) { while ((int)(clk32() - at) < 0) { } }
                    if (OPOLL2_ON && j == 4) { mbar_wait(bar_ab + 8, 0); forward(fl, epoch * 8, Int<2>(), bar_fl + 32, at); } else
                    forward(fl, j == 4 ? epoch * 8 : epoch, Int<0>(), bar_fl + 8 * j, at);
                    if (lane == 0) TR(j == 3 ? 39 : j == 4 ? 13 : 35 + j);
                }
                mbar_wait_limit(bar_end, 0);
            }
            __syncwarp();
        }
      }
      TR_END();
    } else {
        if (tid == 128) {
            mbar_init(bar_ab, 4); mbar_init(bar_ab + 8, 6); mbar_init(bar_free, 1); mbar_init(bar_free + 8, 1); mbar_init(bar_qkv, 4); mbar_init(bar_qkv + 8, 4); mbar_init(bar_o, 8);
            mbar_init(bar_halo, 1); mbar_init(bar_end, 3);
            #pragma unroll
            for (int j = 0; j < 7; j++) mbar_init(bar_go + 8 * j, 1);
            mbar_init(bar_sf, 1); mbar_init(bar_se, 2); mbar_init(bar_af, 4);
            asm volatile("fence.mbarrier_init.release.cluster;" ::: "memory");
        }
        __syncwarp();
        cluster_arrive();
        if (warp >= 8) {
            float d[4];
            #pragma unroll 1
            for (int i = 0; i < TP(WARM_N); i++) {
                const uint32_t t1 = clk32();
                wgmma_fence();
                wgmma_n8<1, 0>(d, desc_k(sb + 7 * AB_BYTES), desc_k(sb + 7 * AB_BYTES), 0);
                wgmma_commit();
                wgmma_wait<0>();
                while ((int)(clk32() - t1) < TP(WARM_GAP)) { }
                __syncwarp();
            }
        }
        cluster_wait();
        const int wg = warp >> 3, w = warp & 3, cw = warp - 4;

        const bool sig_local = (tid & 127) == 0;
        const int i8 = lane & 7, m = lane >> 3;
        const bool sig = (tid & 95) == 0;
        uint32_t rel;
        asm("mapa.shared::cluster.u32 %0, %1, %2;" : "=r"(rel) : "r"(bar_empty), "r"(r ^ (w & 1)));
        auto done = [&](int it) { (void)it; if ((tid & 127) == 64) TRL(160 + it); };
        auto release = [&](int s) { if (sig) asm volatile("mbarrier.arrive.shared::cluster.b64 _, [%0];" :: "r"(rel + 8 * s) : "memory"); };
        const uint32_t dA = desc_k(sb + wg * 8192), dB = desc_k(sb + SLOT_A), dBt = desc_mn(sb + SLOT_A);
        const uint32_t a_frag = sb + wg * 8192 + (w * 16 + (lane & 15)) * 128 + (((lane >> 4) ^ i8) << 4);
        auto wait_full = [&](int it) { mbar_wait(bar_full + 8 * (it & 3), (it >> 2) & 1); if (sig_local) TR(128 + wg * 64 + it); };
        uint32_t kq[4][4], vq[14], qb[2][8];
        {
            float aq[28], ak[28], av[28];
            uint32_t mh0 = 0;
            uint32_t af[2][4][4];
            auto load_af = [&](int it) {
                wait_full(it);
                #pragma unroll
                for (int k = 0; k < 4; k++) ldsm_x4((a_frag ^ (k << 5)) + (it & 3) * SLOT_BYTES, af[it & 1][k][0], af[it & 1][k][1], af[it & 1][k][2], af[it & 1][k][3]);
            };
            uint32_t abw[28], base;
            auto stage_ab = [&](int j0, int j1) {
                #pragma unroll
                for (int j = j0; j < j1; j++) {
                    if (j < 7) stsm_x4_t(base + j * 2048, abw[4 * j], abw[4 * j + 1], abw[4 * j + 2], abw[4 * j + 3]);
                    else { __syncwarp(); if (lane == 0) mbar_arrive(bar_ab + 8 * wg); }
                }
            };
            {
                float bacc[56];
                base = pin((wg ? stg : sb + 7 * AB_BYTES) + (((2 * w + (m & 1)) ^ i8) << 4) + ((m >> 1) * 8 + i8) * 128);
                auto ab_loop = [&](auto sign) {
                auto ab_issue = [&](int kb) {
                    mbar_wait_p(bar_abf + 8 * kb, 0);
                    if (kb == 0 && wg == 1) asm volatile("bar.sync 3, 256;" ::: "memory");
                    if (sig_local) TR(112 + wg * 8 + kb);
                    wgmma_fence();
                    #pragma unroll
                    for (int k = 0; k < 4; k++) wgmma_n112<decltype(sign)::value, 0>(bacc, dA + kb * (AB_BYTES >> 4) + 2 * k, dB + kb * (AB_BYTES >> 4) + 2 * k, (kb | k) != 0);
                    wgmma_commit();
                    if (kb == 0 && wg == 0) asm volatile("bar.arrive 3, 256;" ::: "memory");
                };
                #pragma unroll
                for (int kb = 0; kb < 5; kb++) {
                    ab_issue(kb);
                    if (kb > 0) wgmma_wait<1>();
                    if (kb == 2 || kb == 3) release(kb - 2);
                }
                if (wg == 0) {
                    ab_issue(5);
                    ab_issue(6);
                    asm volatile("bar.arrive 4, 256;" ::: "memory");
                    wgmma_wait<2>();
                    release(2);
                } else {
                    uint32_t xf[8][4];
                    #pragma unroll
                    for (int j = 0; j < 8; j++) {
                        if ((j & 3) == 0) mbar_wait(bar_abf + 8 * (5 + (j >> 2)), 0);
                        ldsm_x4((a_frag ^ ((j & 3) << 5)) + (5 + (j >> 2)) * AB_BYTES, xf[j][0], xf[j][1], xf[j][2], xf[j][3]);
                    }
                    wgmma_wait<0>();
                    release(2);
                    asm volatile("bar.sync 4, 256;" ::: "memory");
                    wgmma_fence();
                    #pragma unroll
                    for (int j = 0; j < 8; j++) {
                        wgmma_rs_n112<0, decltype(sign)::value>(bacc, xf[j], dB + (5 + (j >> 2)) * (AB_BYTES >> 4) + 2 * (j & 3), 1);
                        if ((j & 3) == 3) wgmma_commit();
                    }
                }
                };
                if (sub >> 2) ab_loop(Int<-1>()); else ab_loop(Int<1>());
                wgmma_wait<1>();
                release(3);
                reg_set<REG_CONS>();
                if (wg == 1) load_af(0);
                wgmma_wait<0>();
                if (sig_local) TRX(21 + wg);
                if (AB_ST) { if (wg == 0) asm volatile("bar.arrive 3, 256;" ::: "memory"); else asm volatile("bar.sync 3, 256;" ::: "memory"); }
                #pragma unroll
                for (int j = 0; j < 28; j++) abw[j] = pack_bf16(bacc[2 * j], bacc[2 * j + 1]);
                stage_ab(0, AB_ST);
                if (wg == 0 || AB_ST == 7) stage_ab(AB_ST, 8);
            }
            const uint32_t dQ = dBt + (sub & 1);
            #pragma unroll
            for (int it = 0; it < 7; it++) {
                const uint32_t o = (it & 3) * (SLOT_BYTES >> 4);
                if (it > 0 || wg == 0) load_af(it);
                if (it == 5) mh0 = pin((lane & 3) < 2 ? 0xffffffffu : 0u);
                if (AB_ST < 7 && wg == 1) { if (it == 1) stage_ab(AB_ST, AB_ST2); if (it == 2) stage_ab(AB_ST2, 8); }
                wgmma_wait<0>();
                if (it > 0) { release((it - 1) & 3); done(it - 1); }
                if (it == 0 && sig_local) TRL(60 + wg);
                if (wg == 0) { if (it > 0) asm volatile("bar.sync 6, 256;" ::: "memory"); } else asm volatile("bar.sync 8, 256;" ::: "memory");
                wgmma_fence();
                #pragma unroll
                for (int j = 0; j < 12; j++) {
                    const int k = it < 6 || !KV_FIRST ? j / 3 : j < 8 ? j >> 1 : j - 8, x = it < 6 || !KV_FIRST ? j % 3 : j < 8 ? j & 1 : 2;
                    const uint32_t d = dQ + o + (k >> 1) * 768 + (k & 1) * 128;
                    if (j == Q_ARR) { if (wg == 0) asm volatile("bar.arrive 8, 256;" ::: "memory"); else asm volatile("bar.arrive 6, 256;" ::: "memory"); }
                    if (x == 0) wgmma_rs_n56<1>(ak, af[it & 1][k], d + 256, (it | k) != 0);
                    if (x == 1) wgmma_rs_n56<1>(av, af[it & 1][k], d + 512, (it | k) != 0);
                    if (x == 2) wgmma_rs_n56<1>(aq, af[it & 1][k], d, (it | k) != 0);
                    if (KV_FIRST && it == 6 && j == 7) wgmma_commit();
                }
                wgmma_commit();
            }
            uint4* const hp = pin(g_halo + (mt * 8 + sub) * 320 + wg * 160 + lane);
            mbar_wait(bar_ab + 8, 0);
            const uint32_t epoch = lds32(bars + 168);
            wgmma_wait<KV_FIRST>();
            #pragma unroll
            for (int j = 0; j < 16; j++) kq[j >> 2][j & 3] = pin(pack_bf16(ak[2 * (j - 2 * (j > 7))], ak[1 + 2 * (j - 2 * (j > 7))]));
            #pragma unroll
            for (int j = 0; j < 14; j++) vq[j] = pin(pack_bf16(av[2 * j], av[2 * j + 1]));
            if (w == 3 && !(ABL & 1)) {
                st_b128_relaxed(hp, kq[0][1], kq[0][3], kq[1][1], epoch);
                st_b128_relaxed(hp + 32, kq[1][3], kq[2][3], kq[3][1], epoch);
                st_b128_relaxed(hp + 64, kq[3][3], vq[1], vq[3], epoch);
                st_b128_relaxed(hp + 96, vq[5], vq[7], vq[9], epoch);
                st_b128_relaxed(hp + 128, vq[11], vq[13], 0u, epoch);
                if (lane == 0) TR(8);
            }
            wgmma_wait<0>();
            release(6 & 3);
            if (sig_local) TRX(23 + wg);
            #pragma unroll
            for (int j = 0; j < 14; j++) qb[j & 1][(j >> 1) + (j > 7)] = pin(pack_bf16(aq[2 * j], aq[2 * j + 1]));
            #pragma unroll
            for (int j = 0; j < 2; j++) { qb[j][4] = qb[j][3] & ~mh0; qb[j][3] &= mh0; }
        }
        float acc[112];
        const int it1 = 7 + nj;
        auto big_issue = [&](int slot, bool first) {
            wgmma_fence();
            #pragma unroll
            for (int k = 0; k < 4; k++) wgmma_n224<1, 0>(acc, dA + slot * (SLOT_BYTES >> 4) + 2 * k, dB + slot * (SLOT_BYTES >> 4) + 2 * k, !first || k != 0);
            wgmma_commit();
        };
        if (wg == 1) {
            asm volatile("bar.sync 7, 256;" ::: "memory");
            big_issue(3, true);
        } else {
            wait_full(7);
            asm volatile("bar.sync 6, 256;" ::: "memory");
            big_issue(3, true);
            asm volatile("bar.arrive 7, 256;" ::: "memory");
            if (sig_local) TR(20);
        }
        {
            auto plain = [&](int it) {
                wait_full(it); wgmma_wait<0>(); release((it - 1) & 3); done(it - 1); big_issue(it & 3, false);
                mbar_wait(bar_free, 0);
            };
            auto before_mma = [&](int it, int last) {
                if (wg == last) {
                    mbar_wait_limit(bar_full + 8 * (it & 3), (it >> 2) & 1);
                    if (sig_local) TR(128 + last * 64 + it);
                    asm volatile("bar.sync 2, 256;" ::: "memory");
                    wgmma_wait<0>();
                    release((it - 1) & 3);
                    done(it - 1);
                } else {
                    if (GAP_FLIP) { wgmma_wait<0>(); release((it - 1) & 3); }
                    asm volatile("bar.arrive 2, 256;" ::: "memory");
                }
            };
            auto after_mma = [&](int it, int last) {
                if (wg == (last ^ 1)) {
                    if (!GAP_FLIP) { wgmma_wait<0>(); release((it - 1) & 3); }
                    asm volatile("bar.sync 7, 256;" ::: "memory");
                    big_issue(it & 3, false);
                } else {
                    big_issue(it & 3, false);
                    asm volatile("bar.arrive 7, 256;" ::: "memory");
                }
            };
            const uint32_t kvw = stg + KV_OFF + wg * KV_PAR + (w * 16 + i8) * KV_PITCH;
            const uint32_t a_k = kvw + (m & 1) * 8 * KV_PITCH + (m >> 1) * 16, a_v = kvw + (m >> 1) * 8 * KV_PITCH + 112 + (m & 1) * 16;
            mbar_wait(bar_free, 0);
            #pragma unroll
            for (int u = 0; u < (ABL & 64 ? 0 : 3); u++) stsm_x4(a_k + 8 * KV_PITCH + 112 + u * 32, vq[4 * u], vq[4 * u + 1], vq[4 * u + 2], vq[4 * u + 3]);
            if (!(ABL & 64)) stsm_x2(a_k + 8 * KV_PITCH + 112 + 96, vq[12], vq[13]);
            plain(8);
            #pragma unroll
            for (int u = 0; u < (ABL & 64 ? 1 : 4); u++) stsm_x4(a_k + 8 * KV_PITCH + (2 * u - (u > 1)) * 16, kq[u][0], kq[u][1], kq[u][2], kq[u][3]);
            __syncwarp();
            if (lane == 0) mbar_arrive(bar_qkv + 8 * wg);
            if (sig_local) TR(25 + wg);
            uint32_t kp[4][4], vt[8][4], pb[4][2];
            auto load_v = [&](int n) {
                #pragma unroll
                for (int u = 0; u < 4; u++) {
                    if ((ABL & 64) && u > 0) { vt[2 * u + n][0] = vq[u]; vt[2 * u + n][1] = vq[u + 4]; vt[2 * u + n][2] = vq[u + 8]; vt[2 * u + n][3] = vq[u + n]; } else
                    ldsm_x4_t(a_v + n * 8 * KV_PITCH + (2 * u - (u > 1)) * 16, vt[2 * u + n][0], vt[2 * u + n][1], vt[2 * u + n][2], vt[2 * u + n][3]);
                }
            };
            load_v(1);
            plain(9);
            if (QK_AT > 10) plain(10);
            mbar_wait(w == 0 && !(ABL & 2) ? bar_halo : bar_qkv + 8 * wg, 0);
            #pragma unroll
            for (int u = 0; u < 4; u++) {
                if ((ABL & 64) && u > 0) { kp[u][0] = kq[u][1]; kp[u][1] = kq[u][0]; kp[u][2] = kq[u][3]; kp[u][3] = kq[u][2]; } else
                ldsm_x4(a_k + (2 * u - (u > 1)) * 16, kp[u][0], kp[u][1], kp[u][2], kp[u][3]);
            }
            if (sig_local) TR(54 + wg);
            before_mma(QK_AT, GAP_FLIP);
            float s[4][4];
            #pragma unroll
            for (int i = 0; i < 16; i++) s[i >> 2][i & 3] = 0.f;
            #pragma unroll
            for (int i = 0; i < (ABL & 4 ? 0 : 8); i++) {
                const int n = i & 1, h = (i >> 1) & 1, ks = 2 * h + (i >> 2);
                if (n) mma16816(s[i & 3], kq[ks][0], kq[ks][1], kq[ks][2], kq[ks][3], qb[1][2 * ks], qb[1][2 * ks + 1]);
                else mma16816(s[i & 3], kp[ks][0], kp[ks][1], kp[ks][2], kp[ks][3], qb[0][2 * ks], qb[0][2 * ks + 1]);
            }
            #pragma unroll
            for (int i = 0; i < 16; i++) asm volatile("" : "+f"(s[i >> 2][i & 3]) :: "memory");
            after_mma(QK_AT, GAP_FLIP);
            if (sig_local) TR(48 + wg);
            const int g = lane >> 2, t2 = 2 * (lane & 3);
            const uint32_t mlo = (t2 > g ? 0xffffu : 0u) | (t2 + 1 > g ? 0xffff0000u : 0u), before = (mt | w) == 0 ? mlo : 0u;
            uint32_t y[4], mx[2];
            #pragma unroll
            for (int i = 0; i < 4; i++) {
                const uint32_t x = pack_bf16(g > t2 ? s[i][0] : s[i][2], g > t2 + 1 ? s[i][1] : s[i][3]);
                y[i] = movm_t(pack_bf16(bf_lo(x) * ATT_SCALE, bf_hi(x) * ATT_SCALE));
                if (!(i & 1)) y[i] = (y[i] & ~before) | (MASKED & before);
            }
            #pragma unroll
            for (int h = 0; h < 2; h++) {
                mx[h] = max_bf16x2(__byte_perm(y[2 * h], y[2 * h + 1], 0x5410), __byte_perm(y[2 * h], y[2 * h + 1], 0x7632));
                mx[h] = pin(max_bf16x2(mx[h], __shfl_xor_sync(0xffffffffu, mx[h], 1)));
            }
            load_v(0);
            if (sig_local) TR(50 + wg);
            plain(QK_AT + 1);
            #pragma unroll
            for (int h = 0; h < 2; h++) mx[h] = max_bf16x2(mx[h], __shfl_xor_sync(0xffffffffu, mx[h], 2));
            #pragma unroll
            for (int i = 0; i < 4; i++) {
                const float mi = i & 1 ? bf_hi(mx[i >> 1]) : bf_lo(mx[i >> 1]);
                const float e0 = ex2_approx((bf_lo(y[i]) - mi) * LOG2E), e1 = ex2_approx((bf_hi(y[i]) - mi) * LOG2E);
                float sum = e0 + e1;
                sum += __shfl_xor_sync(0xffffffffu, sum, 1);
                sum += __shfl_xor_sync(0xffffffffu, sum, 2);
                const float inv = rcp_approx(sum);
                const uint32_t p = pack_bf16(e0 * inv, e1 * inv);
                pb[i][0] = pin(p & mlo); pb[i][1] = pin(p & ~mlo);
            }
            if (sig_local) TR(52 + wg);
            before_mma(QK_AT + 2, 0);
            float ao[8][4];
            #pragma unroll
            for (int i = 0; i < 8; i++) {
                ao[i][0] = ao[i][1] = ao[i][2] = ao[i][3] = 0.f;
                if (!(ABL & 4)) mma16816(ao[i], vt[i][0], vt[i][1], vt[i][2], vt[i][3], pb[(i >> 2) * 2 + (i & 1)][0], pb[(i >> 2) * 2 + (i & 1)][1]);
            }
            #pragma unroll
            for (int i = 0; i < 32; i++) asm volatile("" : "+f"(ao[i >> 2][i & 3]) :: "memory");
            after_mma(QK_AT + 2, 0);
            if (sig_local) TRX(11 + wg);
            if (g >= 4) { ao[2][2] = ao[4][0]; ao[2][3] = ao[4][1]; ao[3][2] = ao[5][0]; ao[3][3] = ao[5][1]; }
            mbar_wait(bar_free + 8, 0);
            const uint32_t orow = stg + wg * 7168 + (m >> 1) * 1024 + (w * 16 + (lane & 15)) * 16;
            stsm_x4_t(orow, pack_bf16(ao[0][0], ao[0][1]), pack_bf16(ao[1][0], ao[1][1]), pack_bf16(ao[0][2], ao[0][3]), pack_bf16(ao[1][2], ao[1][3]));
            stsm_x4_t(orow + 2048, pack_bf16(ao[2][0], ao[2][1]), pack_bf16(ao[3][0], ao[3][1]), pack_bf16(ao[2][2], ao[2][3]), pack_bf16(ao[3][2], ao[3][3]));
            stsm_x4_t(orow + 4096, pack_bf16(ao[4][2], ao[4][3]), pack_bf16(ao[5][2], ao[5][3]), pack_bf16(ao[6][0], ao[6][1]), pack_bf16(ao[7][0], ao[7][1]));
            stsm_x2_t(orow + 6144, pack_bf16(ao[6][2], ao[6][3]), pack_bf16(ao[7][2], ao[7][3]));
            __syncwarp();
            if (lane == 0) mbar_arrive(bar_o);
        }
        uint32_t af[4 * L_NB][4];
        #pragma unroll 1
        for (int it = QK_AT + 3; it < it1 - (late ? L_NB : 3); it++) {
            wait_full(it);
            wgmma_wait<0>();
            if (it != 7 + 32 - KB_EARLY - 4) release((it - 1) & 3);
            done(it - 1);
            big_issue(it & 3, false);
            if (L_PRE && it == 7 + 32 - KB_EARLY - L_NB - 2) {
                mbar_wait(bar_sf, 0);
                #pragma unroll
                for (int k = 0; k < 4; k++) ldsm_x4((a_frag ^ (k << 5)) + NSLOT * SLOT_BYTES, af[k][0], af[k][1], af[k][2], af[k][3]);
            }
        }
        mbar_wait(bar_fl + 24, 0);
        if (tid == 128) atomicAdd(&g_epoch[cta * 8], 1);
        __nv_bfloat16* const yp = pin(out + (size_t)(mt * 128 + cw * 16 + (lane >> 2)) * NOUT + DM + nh * 256 + (lane & 3) * 8);
        const int y6 = 192 - nh * 224;
        #define Y_WORD(A, i, jj) pack_bf16(A[16 * ((i) >> 1) + 4 * (jj) + 2 * ((i) & 1)], A[16 * ((i) >> 1) + 4 * (jj) + 2 * ((i) & 1) + 1])
        #define Y_ADDR(i) (yp + ((i) & 1) * 8 * NOUT + ((i) < 12 ? ((i) >> 1) * 32 : y6))
        const bool odd = lane & 4;
        __nv_bfloat16* const yq = pin(odd ? yp - NOUT + 32 : yp);
        #define Y_PAIR(A, i, B, j, rh, C, PAUSE) do { \
            uint32_t x_[4], y_[4]; \
            _Pragma("unroll") \
            for (int jj = 0; jj < 4; jj++) { \
                const uint32_t u_ = Y_WORD(A, 2 * (i) + (rh), jj), v_ = Y_WORD(B, 2 * (j) + (rh), jj), o_ = __shfl_xor_sync(0xffffffffu, odd ? u_ : v_, 4); \
                x_[jj] = odd ? o_ : u_; y_[jj] = odd ? v_ : o_; \
            } \
            red_add_bf16x8(yq + (rh) * 8 * NOUT + (C), x_[0], x_[1], x_[2], x_[3]); \
            PAUSE; \
            red_add_bf16x8(yq + ((rh) * 8 + 1) * NOUT + (C), y_[0], y_[1], y_[2], y_[3]); \
        } while (0)
        if (late) {
            constexpr int IT = 7 + 32 - KB_EARLY - L_NB;
            #define L_SLOT(j) ((j) == 0 ? NSLOT : (IT + (j) - 1) & 3)
            auto load_af = [&](int j) {
                if (j == 0) mbar_wait(bar_sf, 0); else wait_full(IT + j - 1);
                #pragma unroll
                for (int k = 0; k < 4; k++) ldsm_x4((a_frag ^ (k << 5)) + L_SLOT(j) * SLOT_BYTES, af[4 * j + k][0], af[4 * j + k][1], af[4 * j + k][2], af[4 * j + k][3]);
            };
            if (!L_PRE) load_af(0);
            load_af(1);
            if (L_UP) load_af(2);
            wgmma_wait<0>();
            done(IT - 1);
            if (!L_UP && wg == 1) load_af(2);
            if (L_NB == 4 && wg == 1) load_af(L_NB - 1);
            auto issue = [&](auto& p, auto c0, int j0, int j1, bool first, bool last) {
                constexpr int W = sizeof(p) / 2, C0 = decltype(c0)::value;
                if (wg == 0) { if (!first) asm volatile("bar.sync 9, 256;" ::: "memory"); } else asm volatile("bar.sync 5, 256;" ::: "memory");
                wgmma_fence();
                #pragma unroll
                for (int j = j0; j < j1; j++) {
                    if (!L_UP && first && j == 8) { if (wg == 0) load_af(2); wgmma_fence(); }
                    if (L_NB == 4 && first && j == 12) { if (wg == 0) load_af(L_NB - 1); wgmma_fence(); }
                    if (j == j1 - 12 + L_ARR) { if (wg == 0) asm volatile("bar.arrive 5, 256;" ::: "memory"); else if (!last) asm volatile("bar.arrive 9, 256;" ::: "memory"); }
                    const uint32_t d = dB + L_SLOT(j >> 2) * (SLOT_BYTES >> 4) + C0 * 8 + 2 * (j & 3);
                    if constexpr (W == 96) wgmma_rs_n96<0>(p, af[j], d, 1); else if constexpr (W == 64) wgmma_rs_n64<0>(p, af[j], d, 1); else wgmma_rs_n32<0>(p, af[j], d, 1);
                }
                wgmma_commit();
            };
            float pa[48], p0[32], p1[32];
            #pragma unroll
            for (int i = 0; i < 48; i++) asm volatile("mov.b32 %0, %1;" : "=f"(pa[i]) : "f"(acc[64 + i]));
            #pragma unroll
            for (int i = 0; i < 32; i++) asm volatile("mov.b32 %0, %1;" : "=f"(p1[i]) : "f"(acc[32 + i]));
            #pragma unroll
            for (int i = 0; i < 32; i++) asm volatile("mov.b32 %0, %1;" : "=f"(p0[i]) : "f"(acc[i]));
            issue(pa, Int<128>(), 0, 4 * L_NB, true, false);
            wgmma_wait<0>();
            if (sig_local) TRL(14 + wg);
            Y_PAIR(pa, 0, pa, 1, 0, 128, ); Y_PAIR(pa, 0, pa, 1, 1, 128, );
            #pragma unroll
            for (int i = 0; i < 2; i++) red_add_bf16x8(Y_ADDR(12 + i), Y_WORD(pa, 4 + i, 0), Y_WORD(pa, 4 + i, 1), Y_WORD(pa, 4 + i, 2), Y_WORD(pa, 4 + i, 3));
            issue(p0, Int<0>(), 0, 4 * L_NB, false, false);
            wgmma_wait<0>();
            Y_PAIR(p0, 0, p0, 1, 0, 0, ); Y_PAIR(p0, 0, p0, 1, 1, 0, );
            issue(p1, Int<64>(), 0, 4 * L_NB, false, true);
            if (sig_local) mbar_arrive(bar_end);
            wgmma_wait<0>();
            if (sig_local) TRX(27 + wg);
            Y_PAIR(p1, 0, p1, 1, 0, 64, ); Y_PAIR(p1, 0, p1, 1, 1, 64, );
            if (sig_local) TR(29 + wg);
        } else {
        constexpr int IT0 = 7 + KB_EARLY;
        auto load_af = [&](int j) {
            wait_full(IT0 - 3 + j);
            #pragma unroll
            for (int k = 0; k < 4; k++) ldsm_x4((a_frag ^ (k << 5)) + ((IT0 - 3 + j) & 3) * SLOT_BYTES, af[4 * j + k][0], af[4 * j + k][1], af[4 * j + k][2], af[4 * j + k][3]);
        };
        wait_full(IT0 - 3);
        wgmma_wait<0>();
        release((IT0 - 4) & 3);
        done(IT0 - 4);
        if (wg == 1) {
            load_af(0); load_af(1); load_af(2);
            asm volatile("bar.sync 5, 256;" ::: "memory");
            release((bar_af - bar_empty) / 8);
            #pragma unroll
            for (int it = IT0 - 3; it < IT0; it++) {
                if (it == IT0 - 1) { wgmma_wait<1>(); release((it - 2) & 3); }
                wgmma_fence();
                #pragma unroll
                for (int k = 0; k < 4; k++) wgmma_rs_n224<0>(acc, af[4 * (it - IT0 + 3) + k], dB + (it & 3) * (SLOT_BYTES >> 4) + 2 * k, 1);
                wgmma_commit();
            }
            asm volatile("bar.arrive 9, 256;" ::: "memory");
            wgmma_wait<1>();
            release((IT0 - 2) & 3);
            wgmma_wait<0>();
            release((IT0 - 1) & 3);
            if (sig_local) { mbar_arrive(bar_end); TRL(28); }
            const uint32_t t1 = clk32() + TP(RED_AT1);
            auto pause = [&](int i) { while ((int)(clk32() - t1) < i * TP(RED_GAP1)) { } };
            #pragma unroll
            for (int i = 0; i < 2; i++) { pause(i); red_add_bf16x8(Y_ADDR(12 + i), Y_WORD(acc, 12 + i, 0), Y_WORD(acc, 12 + i, 1), Y_WORD(acc, 12 + i, 2), Y_WORD(acc, 12 + i, 3)); }
            #pragma unroll
            for (int i = 0; i < 6; i++) { pause(2 + 2 * i); Y_PAIR(acc, i & 6, acc, (i & 6) + 1, i & 1, 32 * (i & 6), pause(3 + 2 * i)); }
            if (sig_local) TRX(30);
        } else {
            float lo[64], hi[48];
            #pragma unroll
            for (int i = 0; i < 48; i++) asm volatile("mov.b32 %0, %1;" : "=f"(hi[i]) : "f"(acc[64 + i]));
            #pragma unroll
            for (int i = 0; i < 64; i++) asm volatile("mov.b32 %0, %1;" : "=f"(lo[i]) : "f"(acc[i]));
            #pragma unroll
            for (int it = IT0 - 3; it < IT0; it++) {
                if (it == IT0 - 1) {
                    #pragma unroll
                    for (int k = 0; k < E_FILL; k++) wgmma_n96<1, 0>(hi, dA + ((IT0 - 3 + (k >> 2)) & 3) * (SLOT_BYTES >> 4) + 2 * (k & 3), dB + ((IT0 - 3 + (k >> 2)) & 3) * (SLOT_BYTES >> 4) + 1024 + 2 * (k & 3), 1);
                }
                if (it > IT0 - 3) wait_full(it);
                wgmma_fence();
                #pragma unroll
                for (int k = 0; k < 4; k++) wgmma_n128<1, 0>(lo, dA + (it & 3) * (SLOT_BYTES >> 4) + 2 * k, dB + (it & 3) * (SLOT_BYTES >> 4) + 2 * k, 1);
            }
            wgmma_commit();
            #define E_RED(i) do { if ((i) < 8) red_add_bf16x8(Y_ADDR(i), Y_WORD(lo, (i) & 7, 0), Y_WORD(lo, (i) & 7, 1), Y_WORD(lo, (i) & 7, 2), Y_WORD(lo, (i) & 7, 3)); \
                                  else red_add_bf16x8(Y_ADDR(i), Y_WORD(hi, (i) & 7, 0), Y_WORD(hi, (i) & 7, 1), Y_WORD(hi, (i) & 7, 2), Y_WORD(hi, (i) & 7, 3)); } while (0)
            #pragma unroll
            for (int j = E_FILL; j < 12; j++) {
                const int it = IT0 - 3 + (j >> 2), k = j & 3;
                if (j == E_FILL + E_SPLIT) {
                    wgmma_commit();
                    wgmma_wait<1>();
                    if (sig_local) TR(14);
                    #pragma unroll
                    for (int i = 0; i < RED_A; i++) E_RED(i);
                    wgmma_fence();
                }
                wgmma_n96<1, 0>(hi, dA + (it & 3) * (SLOT_BYTES >> 4) + 2 * k, dB + (it & 3) * (SLOT_BYTES >> 4) + 1024 + 2 * k, 1);
            }
            wgmma_commit();
            asm volatile("bar.arrive 5, 256;" ::: "memory");
            #pragma unroll
            for (int i = RED_A; i < RED_FAST; i++) E_RED(i);
            wgmma_wait<0>();
            release((bar_af - bar_empty) / 8); release((IT0 - 3) & 3); release((IT0 - 2) & 3); release((IT0 - 1) & 3);
            if (sig_local) TRL(27);
            const uint32_t t1 = clk32();
            #pragma unroll
            for (int i = RED_FAST; i < 14 - E_LATE; i++) {
                while ((int)(clk32() - t1) < (i - RED_FAST) * TP(RED_GAP)) { }
                E_RED(i);
            }
            if (sig_local) TR(29);
            float o0[56], o1[56];
            auto out_issue = [&](float (&oa)[56], int p, int j) {
                wgmma_fence();
                #pragma unroll
                for (int k = 0; k < (ABL & 32 ? 0 : 4); k++) wgmma_n112<1, 1, 8>(oa, dB + (63 << 16) + ((OUT_O(p, j) - SLOT_A) >> 4) + 128 * k, dB + ((((OUT_B(j) - OUT_A(j)) >> 4) - 1) << 16) + ((OUT_A(j) - SLOT_A) >> 4) + 128 * k, (j | k) != 0);
                wgmma_commit();
            };
            const uint32_t wa = pin(sb + w * 2048 + ((m & 1) * 8 + i8) * 128 + (((m >> 1) ^ i8) << 4)), ra = pin(sb + w * 2048 + m * 128 + ((i8 ^ m) << 4));
            auto stage = [&](float (&oa)[56], int buf, int u) {
                stsm_x4((wa ^ ((u & 3) << 5)) + buf + (u >> 2) * 8192, pack_bf16(oa[8 * u], oa[8 * u + 1]), pack_bf16(oa[8 * u + 2], oa[8 * u + 3]),
                        pack_bf16(oa[8 * u + 4], oa[8 * u + 5]), pack_bf16(oa[8 * u + 6], oa[8 * u + 7]));
            };
            __nv_bfloat16* const op = pin(out + (size_t)(mt * 128 + 1 + w * 32 + 2 * m) * NOUT + (sub & 3) * 64 + i8 * 8);
            const int c1 = 256 - (sub & 3) * 16;
            asm volatile("bar.sync 9, 256;" ::: "memory");
            #pragma unroll
            for (int j = 0; j < 7; j++) {
                if (!(j & 1)) { mbar_wait(bar_abf + 4 * j, 1); if (sig_local) TR(128 + IT0 + j); }
                out_issue(o0, 0, j);
                if (j < E_LATE) E_RED(14 - E_LATE + j);
            }
            #undef E_RED
            #pragma unroll
            for (int j = 0; j < 7; j++) {
                if (j == 3) { mbar_wait(bar_abf + 32, 1); if (sig_local) TR(192 + IT0 + j); }
                out_issue(o1, 1, j);
                if (j == 1) { wgmma_wait<2>(); if (sig_local) TR(31); }
                if (j >= 1 && j < 5) {
                    stage(o0, OUT_ST, 2 * j - 2);
                    if (j < 4) stage(o0, OUT_ST, 2 * j - 1);
                    if (j == 2 || j == 4) { __syncwarp(); if (lane == 0) mbar_arrive(bar_qkv + 4 * j - 8); }
                }
            }
            if (sig_local) mbar_arrive(bar_end);
            wgmma_wait<0>();
            if (sig_local) TRL(32);
            #pragma unroll
            for (int c = 0; c < 2; c++) {
                #pragma unroll
                for (int u = 4 * c; u < (c ? 7 : 4); u++) stage(o1, 0, u);
                __syncwarp();
                #pragma unroll
                for (int q = 0; q < 4; q++) {
                    uint4 v;
                    asm volatile("ld.shared.v4.u32 {%0, %1, %2, %3}, [%4];" : "=r"(v.x), "=r"(v.y), "=r"(v.z), "=r"(v.w) : "r"((ra ^ ((q & 1) << 6)) + c * 8192 + q * 512) : "memory");
                    if (c == 0 || i8 < 6) *reinterpret_cast<uint4*>(op + q * 8 * NOUT + (c ? c1 : 0)) = v;
                }
            }
        }
        }
        #undef Y_PAIR
        #undef Y_WORD
        #undef Y_ADDR
        if (sig_local) { TRX(33 + wg); if (wg == (late ? 1 : 0)) TRG(104); }
        TR_END();
    }
}

typedef CUresult (*EncodeFn)(CUtensorMap*, CUtensorMapDataType, cuuint32_t, void*, const cuuint64_t*, const cuuint64_t*,
                             const cuuint32_t*, const cuuint32_t*, CUtensorMapInterleave, CUtensorMapSwizzle,
                             CUtensorMapL2promotion, CUtensorMapFloatOOBfill);

void make_map(EncodeFn fn, CUtensorMap* tm, const void* ptr, uint64_t inner, uint64_t outer, uint32_t box_inner, uint32_t box_outer,
              CUtensorMapSwizzle sw = CU_TENSOR_MAP_SWIZZLE_128B, uint64_t clip = 0) {
    cuuint64_t gd[2] = {clip ? clip : inner, outer};
    cuuint64_t gs[1] = {inner * 2};
    cuuint32_t bd[2] = {box_inner, box_outer};
    cuuint32_t es[2] = {1, 1};
    fn(tm, CU_TENSOR_MAP_DATA_TYPE_BFLOAT16, 2, const_cast<void*>(ptr), gd, gs, bd, es, CU_TENSOR_MAP_INTERLEAVE_NONE,
       sw, CU_TENSOR_MAP_L2_PROMOTION_L2_128B, CU_TENSOR_MAP_FLOAT_OOB_FILL_NONE);
}
void make_map3(EncodeFn fn, CUtensorMap* tm, const void* ptr, uint64_t n0, uint64_t n1, uint64_t s1, uint64_t n2, uint64_t s2, uint32_t b1, uint32_t b2) {
    cuuint64_t gd[3] = {n0, n1, n2};
    cuuint64_t gs[2] = {s1 * 2, s2 * 2};
    cuuint32_t bd[3] = {64, b1, b2};
    cuuint32_t es[3] = {1, 1, 1};
    fn(tm, CU_TENSOR_MAP_DATA_TYPE_BFLOAT16, 3, const_cast<void*>(ptr), gd, gs, bd, es, CU_TENSOR_MAP_INTERLEAVE_NONE,
       CU_TENSOR_MAP_SWIZZLE_128B, CU_TENSOR_MAP_L2_PROMOTION_L2_128B, CU_TENSOR_MAP_FLOAT_OOB_FILL_NONE);
}
void make_map_perm(EncodeFn fn, CUtensorMap* tm, void* ptr, uint32_t n) {
    cuuint64_t gd[5] = {SEQ, 2, 4, 4, 28};
    cuuint64_t gs[4] = {SEQ * 2, 8 * SEQ * 2, 2 * SEQ * 2, 32 * SEQ * 2};
    cuuint32_t bd[5] = {64, 2, 4, 4, n};
    cuuint32_t es[5] = {1, 1, 1, 1, 1};
    fn(tm, CU_TENSOR_MAP_DATA_TYPE_BFLOAT16, 5, ptr, gd, gs, bd, es, CU_TENSOR_MAP_INTERLEAVE_NONE,
       CU_TENSOR_MAP_SWIZZLE_128B, CU_TENSOR_MAP_L2_PROMOTION_L2_128B, CU_TENSOR_MAP_FLOAT_OOB_FILL_NONE);
}

}

extern "C" void kernel_launch(void* const* d_in, const int* in_sizes, int n_in, void* d_out, int out_size) {
    (void)in_sizes; (void)n_in; (void)out_size;
    static EncodeFn fn = nullptr;
    static void* p_abT = nullptr;
    if (!fn) {
        void* p = nullptr; cudaDriverEntryPointQueryResult qr;
        cudaGetDriverEntryPoint("cuTensorMapEncodeTiled", &p, cudaEnableDefault, &qr);
        fn = (EncodeFn)p;
        cudaGetSymbolAddress(&p_abT, g_abT);
        cudaFuncSetAttribute(fused_kernel, cudaFuncAttributeMaxDynamicSharedMemorySize, SMEM_BYTES);
    }
    TMaps tm;
    make_map3(fn, &tm.xA3, d_in[0], DM, SEQ / 2, 2 * DM, 2, DM, 64, 2);
    make_map3(fn, &tm.wqkv3, d_in[1], DM, DM, 3 * DM, 3, DM, 32, 3);
    make_map(fn, &tm.wo64, d_in[2], DM, DM, 64, 64);
    make_map3(fn, &tm.outA, d_out, 64, SEQ / 2, 2 * NOUT, 4, 64, 64, 1);
    make_map3(fn, &tm.outB, (const __nv_bfloat16*)d_out + 256, 48, SEQ / 2, 2 * NOUT, 4, 48, 64, 1);
    make_map(fn, &tm.xB, d_in[3], DM, SEQ, 64, 128);
    make_map(fn, &tm.wre, d_in[4], SEQ, SEQ, 64, 128);
    make_map(fn, &tm.wim, d_in[5], SEQ, SEQ, 64, 128);
    make_map(fn, &tm.wreH, d_in[4], SEQ, SEQ, 64, 64);
    make_map(fn, &tm.wimH, d_in[5], SEQ, SEQ, 64, 64);
    make_map(fn, &tm.wdre, d_in[6], DM, DM, 64, 112);
    make_map(fn, &tm.wdim, d_in[7], DM, DM, 64, 112);
    make_map_perm(fn, &tm.abP4, p_abT, 4);
    make_map_perm(fn, &tm.abP3, p_abT, 3);
    make_map(fn, &tm.abH, p_abT, SEQ, 896, 64, 16);
    make_map(fn, &tm.ab32, p_abT, SEQ, 896, 64, 32);
    make_map(fn, &tm.ab80, p_abT, SEQ, 896, 64, 80);
    fused_kernel<<<NCTA, 384, SMEM_BYTES, cudaStreamPerThread>>>((__nv_bfloat16*)d_out,
        tm);
}
```

```cpp
#include <cuda_runtime.h>
#include <cuda_bf16.h>
#include <cuda.h>
#include <stdint.h>

namespace {

constexpr int SEQ = 2048, DM = 448, NOUT = 896;
constexpr int NCTA = 128;
constexpr int SLOT_A = 16384, SLOT_B = 28672, SLOT_BYTES = SLOT_A + SLOT_B, NSLOT = 4;
constexpr int AB_BYTES = SLOT_A + 112 * 128;
constexpr int STG_OFF = NSLOT * SLOT_BYTES;
constexpr int STG_BYTES = 7 * 7168;
constexpr int KV_PITCH = 240;
constexpr int KV_OFF = 2 * 7168, KV_PAR = 72 * KV_PITCH;
#define OUT_A(j) (((j) < 2 ? 48 + 8 * (j) : (j) < 4 ? 8 * (j) - 16 : (j) == 4 ? 136 : 80 + 8 * (j)) * 1024)
#define OUT_B(j) (((j) == 0 ? 80 : 168 + 8 * (j)) * 1024)
#define OUT_O(p, j) (((p) ? ((j) < 3 ? 152 + 8 * (j) : 8 * (j) - 8) : ((j) < 2 ? 64 + 8 * (j) : (j) < 6 ? 72 + 8 * (j) : 144)) * 1024)
#define OUT_ST OUT_O(0, 0)
constexpr int BAR_OFF = STG_OFF + STG_BYTES;
constexpr int TR_OFF = BAR_OFF + 512;
constexpr int SMEM_BYTES = TR_OFF + 1024;
constexpr int SPIN_LIMIT = 1 << 24;
#define TUNE_LIST(X) \
    X(START_GAP1, 400, 50, 0, 900)   \
    X(START_GAP, 280, 30, 0, 500)   \
    X(WARM_N, 3, 1, 0, 6)   \
    X(WARM_GAP, 150, 50, 50, 500)   \
    X(ZERO_GAP, 100, 50, 0, 300)   \
    X(ZERO_AT, 900, 200, 0, 2400)   \
    X(ABS_AT1, 500, 100, 0, 1000)   \
    X(ABS_AT, 1500, 150, 300, 3000)   \
    X(ABS_GAP, 60, 40, 0, 400)   \
    X(ABS_GAP2, 230, 40, 0, 400)   \
    X(ABS_GAP3, 100, 40, 0, 400)   \
    X(POLL_AT, 3100, 100, 2000, 4000)   \
    X(POLL_AT1, 3600, 150, 2000, 5000)   \
    X(POLL_AT2, 6300, 200, 4000, 8000)   \
    X(POLL_AT3, 9200, 200, 6000, 11000)   \
    X(OPOLL_AT, 15100, 200, 13000, 17500)   \
    X(OPOLL2, 500, 100, -1000, 1500)   \
    X(POLL_NS, 50, 100, 0, 800)   \
    X(OPOLL_NS, 100, 60, 0, 600)   \
    X(BIG_GAP, 250, 100, 0, 1000)   \
    X(W_GAP, 180, 100, 0, 900)   \
    X(HALO_WAIT, 350, 100, 0, 1500)   \
    X(O_GAP, 130, 60, 10, 600)   \
    X(PF_N, 0, 1, 0, 3)   \
    X(PF_E, 6, 1, 4, 13)   \
    X(PF_L, 14, 1, 4, 17)   \
    X(WO_AT, 7, 1, 5, 10)   \
    X(WB_AT, 10, 1, 10, 13)   \
    X(L_XAT, 13, 1, 10, 13)   \
    X(RED_GAP, 185, 30, 0, 300)   \
    X(RED_AT1, 0, 100, 0, 1000)   \
    X(RED_GAP1, 45, 30, 0, 300)   \

#define X(n, d, s, lo, hi) constexpr int n = d;
TUNE_LIST(X)
#undef X
#define TP(n) n
#define L_UP 1
#define ABL 0
#define BIG_ST 1
#define FLIP 1
#define URG(mt) ((((mt) >> 2) & 1) ^ FLIP)
#define AB_ST 7
#define AB_ST2 8
#define GAP_FLIP 1
#define L_PRE 1
#define E_FILL 2
#define KB_EARLY 14
#define O_N 2
#define QK_AT 10
#define WAIT_KIND 1
#define KV_FIRST 1
#define Q_ARR 11
#define E_SPLIT 7
#define RED_A 4
#define RED_FAST 6
#define L_ARR 11
#define OPOLL2_ON 1
#define E_LATE 2
#define L_NB 4
#define SM_CUT 1
#define RW3 9
#define RW4 99
#define START_N 2
#define REG_CONS 208
#define REG_AUX 88

struct __align__(64) TMaps { CUtensorMap xB, wdre, wdim, wre, wim, abP4, abP3, abH, ab32, ab80, wreH, wimH, wo64, xA3, wqkv3, outA, outB; };

__device__ __nv_bfloat16 g_abT[896 * SEQ];
__device__ uint4 g_o[SEQ * DM / 8];
__device__ uint4 g_halo[16 * 8 * 2 * 160];
__device__ unsigned g_flag_ab[40 * 32];
__device__ unsigned g_flag_o[16 * 32];
__device__ unsigned g_epoch[NCTA * 8];

__device__ __forceinline__ uint32_t smem_u32(const void* p) { return (uint32_t)__cvta_generic_to_shared(p); }
__device__ __forceinline__ uint32_t clk32() { uint32_t c; asm volatile("mov.u32 %0, %%clock;" : "=r"(c) :: "memory"); return c; }
__device__ __forceinline__ void give_up() { asm volatile("st.global.u32 [%0], 0;" :: "l"(0ull) : "memory"); }
__device__ __forceinline__ void mbar_init(uint32_t bar, uint32_t count) { asm volatile("mbarrier.init.shared::cta.b64 [%0], %1;" :: "r"(bar), "r"(count) : "memory"); }
__device__ __forceinline__ void mbar_expect_tx(uint32_t bar, uint32_t bytes) { asm volatile("mbarrier.arrive.expect_tx.shared::cta.b64 _, [%0], %1;" :: "r"(bar), "r"(bytes) : "memory"); }
__device__ __forceinline__ void mbar_arrive(uint32_t bar) { asm volatile("mbarrier.arrive.shared::cta.b64 _, [%0];" :: "r"(bar) : "memory"); }
__device__ __forceinline__ void mbar_arrive_remote(uint32_t bar, uint32_t cta) {
    asm volatile("{\n.reg .b32 ra;\nmapa.shared::cluster.u32 ra, %0, %1;\nmbarrier.arrive.shared::cluster.b64 _, [ra];\n}" :: "r"(bar), "r"(cta) : "memory");
}
__device__ __forceinline__ bool mbar_try_wait(uint32_t bar, uint32_t parity) {
    uint32_t ok;
    asm volatile("{\n.reg .pred p;\nmbarrier.try_wait.parity.shared::cta.b64 p, [%1], %2;\nselp.u32 %0, 1, 0, p;\n}" : "=r"(ok) : "r"(bar), "r"(parity) : "memory");
    return ok;
}
__device__ __forceinline__ bool mbar_test_wait(uint32_t bar, uint32_t parity) {
    uint32_t ok;
    asm volatile("{\n.reg .pred p;\nmbarrier.test_wait.parity.shared::cta.b64 p, [%1], %2;\nselp.u32 %0, 1, 0, p;\n}" : "=r"(ok) : "r"(bar), "r"(parity) : "memory");
    return ok;
}
#define WAIT_OP "pmevent 0;\nmbarrier.try_wait.parity.shared::cta.b64 p, [%0], %1;\n"
__device__ __forceinline__ void mbar_wait(uint32_t bar, uint32_t parity) {
    asm volatile("{\n.reg .pred p;\nWAIT:\n" WAIT_OP "@!p bra WAIT;\n}" :: "r"(bar), "r"(parity) : "memory");
}
__device__ __forceinline__ void mbar_wait_p(uint32_t bar, uint32_t parity) {
    asm volatile("{\n.reg .pred p;\nWAIT:\nmbarrier.try_wait.parity.shared::cta.b64 p, [%0], %1;\n@!p bra WAIT;\n}" :: "r"(bar), "r"(parity) : "memory");
}
__device__ __forceinline__ void mbar_wait_limit(uint32_t bar, uint32_t parity) {
    int it = 0;
    while (!mbar_try_wait(bar, parity)) { if (++it > SPIN_LIMIT) give_up(); }
}
__device__ __forceinline__ void tma_load(uint32_t dst, const CUtensorMap* tm, uint32_t bar, int c0, int c1) {
    asm volatile("cp.async.bulk.tensor.2d.shared::cluster.global.mbarrier::complete_tx::bytes [%0], [%1, {%3, %4}], [%2];"
        :: "r"(dst), "l"(tm), "r"(bar), "r"(c0), "r"(c1) : "memory");
}
__device__ __forceinline__ void tma_load_mc(uint32_t dst, const CUtensorMap* tm, uint32_t bar, int c0, int c1) {
    asm volatile("cp.async.bulk.tensor.2d.shared::cluster.global.mbarrier::complete_tx::bytes.multicast::cluster [%0], [%1, {%3, %4}], [%2], %5;"
        :: "r"(dst), "l"(tm), "r"(bar), "r"(c0), "r"(c1), "h"((uint16_t)3) : "memory");
}
__device__ __forceinline__ void tma_load3(uint32_t dst, const CUtensorMap* tm, uint32_t bar, int c0, int c1) {
    asm volatile("cp.async.bulk.tensor.3d.shared::cluster.global.mbarrier::complete_tx::bytes [%0], [%1, {%3, %4, %5}], [%2];"
        :: "r"(dst), "l"(tm), "r"(bar), "r"(c0), "r"(c1), "r"(0) : "memory");
}
__device__ __forceinline__ void tma_load3_mc(uint32_t dst, const CUtensorMap* tm, uint32_t bar, int c0, int c1, int c2) {
    asm volatile("cp.async.bulk.tensor.3d.shared::cluster.global.mbarrier::complete_tx::bytes.multicast::cluster [%0], [%1, {%3, %4, %6}], [%2], %5;"
        :: "r"(dst), "l"(tm), "r"(bar), "r"(c0), "r"(c1), "h"((uint16_t)3), "r"(c2) : "memory");
}
__device__ __forceinline__ void tma_prefetch(const CUtensorMap* tm, int c0, int c1) {
    asm volatile("cp.async.bulk.prefetch.tensor.2d.L2.global [%0, {%1, %2}];" :: "l"(tm), "r"(c0), "r"(c1) : "memory");
}
__device__ __forceinline__ void tma_prefetch3(const CUtensorMap* tm, int c0, int c1) {
    asm volatile("cp.async.bulk.prefetch.tensor.3d.L2.global [%0, {%1, %2, %3}];" :: "l"(tm), "r"(c0), "r"(c1), "r"(0) : "memory");
}
__device__ __forceinline__ void tma_store(const CUtensorMap* tm, uint32_t src, int c0, int c1) {
    asm volatile("cp.async.bulk.tensor.2d.global.shared::cta.bulk_group [%0, {%2, %3}], [%1];" :: "l"(tm), "r"(src), "r"(c0), "r"(c1) : "memory");
}
__device__ __forceinline__ void tma_store3(const CUtensorMap* tm, uint32_t src, int c1, int c2) {
    asm volatile("cp.async.bulk.tensor.3d.global.shared::cta.bulk_group [%0, {%2, %3, %4}], [%1];" :: "l"(tm), "r"(src), "r"(0), "r"(c1), "r"(c2) : "memory");
}
__device__ __forceinline__ void bulk_load(uint32_t dst, const void* src, uint32_t bytes, uint32_t bar) {
    asm volatile("cp.async.bulk.shared::cluster.global.mbarrier::complete_tx::bytes [%0], [%1], %2, [%3];" :: "r"(dst), "l"(src), "r"(bytes), "r"(bar) : "memory");
}
__device__ __forceinline__ void bulk_store(void* dst, uint32_t src, uint32_t bytes) {
    asm volatile("cp.async.bulk.global.shared::cta.bulk_group [%0], [%1], %2;" :: "l"(dst), "r"(src), "r"(bytes) : "memory");
}
__device__ __forceinline__ void tma_load5_mc(uint32_t dst, const CUtensorMap* tm, uint32_t bar, int c0, int c4) {
    asm volatile("cp.async.bulk.tensor.5d.shared::cluster.global.mbarrier::complete_tx::bytes.multicast::cluster [%0], [%1, {%3, %6, %6, %6, %4}], [%2], %5;"
        :: "r"(dst), "l"(tm), "r"(bar), "r"(c0), "r"(c4), "h"((uint16_t)3), "r"(0) : "memory");
}
__device__ __forceinline__ void red_add_bf16x8(__nv_bfloat16* p, uint32_t w0, uint32_t w1, uint32_t w2, uint32_t w3) {
    asm volatile("red.relaxed.gpu.global.add.noftz.v4.bf16x2 [%0], {%1, %2, %3, %4};" :: "l"(p), "r"(w0), "r"(w1), "r"(w2), "r"(w3) : "memory");
}
__device__ __forceinline__ void prefetch_tmap(const CUtensorMap* tm) { asm volatile("prefetch.tensormap [%0];" :: "l"(tm) : "memory"); }
__device__ __forceinline__ void cluster_arrive() { asm volatile("barrier.cluster.arrive.relaxed.aligned;" ::: "memory"); }
__device__ __forceinline__ void cluster_wait() { asm volatile("barrier.cluster.wait.aligned;" ::: "memory"); }
__device__ __forceinline__ void wgmma_fence() { asm volatile("wgmma.fence.sync.aligned;" ::: "memory"); }
__device__ __forceinline__ void wgmma_commit() { asm volatile("wgmma.commit_group.sync.aligned;" ::: "memory"); }
template<int N> __device__ __forceinline__ void wgmma_wait() { asm volatile("wgmma.wait_group.sync.aligned %0;" :: "n"(N) : "memory"); }
__device__ __forceinline__ void fence_async_smem() { asm volatile("fence.proxy.async.shared::cta;" ::: "memory"); }
__device__ __forceinline__ void fence_async_global() { asm volatile("fence.proxy.async.global;" ::: "memory"); }
__device__ __forceinline__ uint32_t desc_k(uint32_t addr) { return ((addr & 0x3FFFF) >> 4) | (1u << 16); }
__device__ __forceinline__ uint32_t desc_mn(uint32_t addr) { return ((addr & 0x3FFFF) >> 4) | ((8192u >> 4) << 16); }
template<int R> __device__ __forceinline__ void reg_set() {
    if (R > 168) asm volatile("setmaxnreg.inc.sync.aligned.u32 %0;" :: "n"(R));
    if (R < 168) asm volatile("setmaxnreg.dec.sync.aligned.u32 %0;" :: "n"(R));
}
__device__ __forceinline__ unsigned ld_acquire(const unsigned* p) { unsigned v; asm volatile("ld.acquire.gpu.global.u32 %0, [%1];" : "=r"(v) : "l"(p) : "memory"); return v; }
__device__ __forceinline__ unsigned ld_relaxed(const unsigned* p) { unsigned v; asm volatile("ld.relaxed.gpu.global.u32 %0, [%1];" : "=r"(v) : "l"(p) : "memory"); return v; }
__device__ __forceinline__ void st_release(unsigned* p, unsigned v) { asm volatile("fence.proxy.async.global;\nst.release.gpu.global.u32 [%0], %1;" :: "l"(p), "r"(v) : "memory"); }
__device__ __forceinline__ void red_release(unsigned* p, unsigned v) { asm volatile("fence.proxy.async.global;\nred.release.gpu.global.add.u32 [%0], %1;" :: "l"(p), "r"(v) : "memory"); }
__device__ __forceinline__ bool elect_one() {
    uint32_t pred;
    asm volatile("{\n.reg .pred p;\nelect.sync _|p, 0xffffffff;\nselp.u32 %0, 1, 0, p;\n}" : "=r"(pred));
    return pred;
}
__device__ __forceinline__ int pick3(int cta, int a, int b, int c) {
    int v;
    asm("{\n.reg .pred p, q;\nsetp.lt.s32 p, %1, 8;\nsetp.lt.s32 q, %1, 72;\nselp.b32 %0, %3, %4, q;\nselp.b32 %0, %2, %0, p;\n}" : "=&r"(v) : "r"(cta), "r"(a), "r"(b), "r"(c));
    return v;
}
template<typename T> __device__ __forceinline__ T pin(T v) {
    if constexpr (sizeof(T) == 8) asm volatile("" : "+l"(v) :: "memory");
    else if constexpr (T(0.5) != T(0)) asm volatile("" : "+f"(v) :: "memory");
    else asm volatile("" : "+r"(v) :: "memory");
    return v;
}
__device__ __forceinline__ void bulk_commit() { asm volatile("cp.async.bulk.commit_group;" ::: "memory"); }
__device__ __forceinline__ void bulk_wait_all() { asm volatile("cp.async.bulk.wait_group 0;" ::: "memory"); }
__device__ __forceinline__ uint32_t pack_bf16(float lo, float hi) { uint32_t r; asm("cvt.rn.bf16x2.f32 %0, %1, %2;" : "=r"(r) : "f"(hi), "f"(lo)); return r; }
__device__ __forceinline__ float bf_lo(uint32_t w) { return __uint_as_float(w << 16); }
__device__ __forceinline__ float bf_hi(uint32_t w) { return __uint_as_float(w & 0xffff0000u); }
__device__ __forceinline__ void stsm_x4(uint32_t addr, uint32_t r0, uint32_t r1, uint32_t r2, uint32_t r3) {
    asm volatile("stmatrix.sync.aligned.m8n8.x4.shared.b16 [%0], {%1, %2, %3, %4};" :: "r"(addr), "r"(r0), "r"(r1), "r"(r2), "r"(r3) : "memory");
}
__device__ __forceinline__ void stsm_x2(uint32_t addr, uint32_t r0, uint32_t r1) {
    asm volatile("stmatrix.sync.aligned.m8n8.x2.shared.b16 [%0], {%1, %2};" :: "r"(addr), "r"(r0), "r"(r1) : "memory");
}
__device__ __forceinline__ void stsm_x4_t(uint32_t addr, uint32_t r0, uint32_t r1, uint32_t r2, uint32_t r3) {
    asm volatile("stmatrix.sync.aligned.m8n8.x4.trans.shared.b16 [%0], {%1, %2, %3, %4};" :: "r"(addr), "r"(r0), "r"(r1), "r"(r2), "r"(r3) : "memory");
}
__device__ __forceinline__ void stsm_x2_t(uint32_t addr, uint32_t r0, uint32_t r1) {
    asm volatile("stmatrix.sync.aligned.m8n8.x2.trans.shared.b16 [%0], {%1, %2};" :: "r"(addr), "r"(r0), "r"(r1) : "memory");
}
__device__ __forceinline__ uint32_t movm_t(uint32_t x) { uint32_t r; asm volatile("movmatrix.sync.aligned.m8n8.trans.b16 %0, %1;" : "=r"(r) : "r"(x)); return r; }
__device__ __forceinline__ void ldsm_x4(uint32_t addr, uint32_t& r0, uint32_t& r1, uint32_t& r2, uint32_t& r3) {
    asm volatile("ldmatrix.sync.aligned.m8n8.x4.shared.b16 {%0, %1, %2, %3}, [%4];" : "=r"(r0), "=r"(r1), "=r"(r2), "=r"(r3) : "r"(addr) : "memory");
}
__device__ __forceinline__ void ldsm_x4_t(uint32_t addr, uint32_t& r0, uint32_t& r1, uint32_t& r2, uint32_t& r3) {
    asm volatile("ldmatrix.sync.aligned.m8n8.x4.trans.shared.b16 {%0, %1, %2, %3}, [%4];" : "=r"(r0), "=r"(r1), "=r"(r2), "=r"(r3) : "r"(addr) : "memory");
}
__device__ __forceinline__ void mma16816(float (&d)[4], uint32_t a0, uint32_t a1, uint32_t a2, uint32_t a3, uint32_t b0, uint32_t b1) {
    asm("mma.sync.aligned.m16n8k16.row.col.f32.bf16.bf16.f32 {%0, %1, %2, %3}, {%4, %5, %6, %7}, {%8, %9}, {%0, %1, %2, %3};"
        : "+f"(d[0]), "+f"(d[1]), "+f"(d[2]), "+f"(d[3]) : "r"(a0), "r"(a1), "r"(a2), "r"(a3), "r"(b0), "r"(b1));
}
__device__ __forceinline__ void mma1688(float (&d)[4], uint32_t a0, uint32_t a1, uint32_t b0) {
    asm("mma.sync.aligned.m16n8k8.row.col.f32.bf16.bf16.f32 {%0, %1, %2, %3}, {%4, %5}, {%6}, {%0, %1, %2, %3};"
        : "+f"(d[0]), "+f"(d[1]), "+f"(d[2]), "+f"(d[3]) : "r"(a0), "r"(a1), "r"(b0));
}
__device__ __forceinline__ uint32_t max_bf16x2(uint32_t a, uint32_t b) { uint32_t r; asm("max.bf16x2 %0, %1, %2;" : "=r"(r) : "r"(a), "r"(b)); return r; }
__device__ __forceinline__ float bf16_round(float x) { return __bfloat162float(__float2bfloat16_rn(x)); }
__device__ __forceinline__ uint32_t lds32(uint32_t addr) { uint32_t v; asm volatile("ld.shared.u32 %0, [%1];" : "=r"(v) : "r"(addr)); return v; }
__device__ __forceinline__ float ex2_approx(float x) { float y; asm("ex2.approx.ftz.f32 %0, %1;" : "=f"(y) : "f"(x)); return y; }
__device__ __forceinline__ float rcp_approx(float x) { float y; asm("rcp.approx.ftz.f32 %0, %1;" : "=f"(y) : "f"(x)); return y; }
__device__ __forceinline__ void st_b128_relaxed(uint4* p, uint32_t w0, uint32_t w1, uint32_t w2, uint32_t w3) {
    asm volatile("{\n.reg .b128 t;\n.reg .b64 lo, hi;\nmov.b64 lo, {%1, %2};\nmov.b64 hi, {%3, %4};\nmov.b128 t, {lo, hi};\nst.relaxed.gpu.global.b128 [%0], t;\n}"
        :: "l"(p), "r"(w0), "r"(w1), "r"(w2), "r"(w3) : "memory");
}
__device__ __forceinline__ uint4 ld_b128_relaxed(const uint4* p) {
    uint4 v;
    asm volatile("{\n.reg .b128 t;\n.reg .b64 lo, hi;\nld.relaxed.gpu.global.b128 t, [%4];\nmov.b128 {lo, hi}, t;\nmov.b64 {%0, %1}, lo;\nmov.b64 {%2, %3}, hi;\n}"
        : "=r"(v.x), "=r"(v.y), "=r"(v.z), "=r"(v.w) : "l"(p) : "memory");
    return v;
}

template<int SA, int TB, int HA = 0x40000040, int M>
__device__ __forceinline__ void wgmma_n8(float (&d)[M], uint32_t da, uint32_t db, int scale_d) {
    asm volatile("{\n.reg .pred p;\n.reg .b32 hi, ha;\n.reg .b64 da, db;\nmov.b32 hi, 0x40000040;\nmov.b32 ha, %9;\nmov.b64 da, {%4, ha};\nmov.b64 db, {%5, hi};\nsetp.ne.b32 p, %6, 0;\n"
        "wgmma.mma_async.sync.aligned.m64n8k16.f32.bf16.bf16 "
        "{%0, %1, %2, %3}, "
        "da, db, p, %8, 1, 0, %7;\n}\n"
        : "+f"(d[0]), "+f"(d[1]), "+f"(d[2]), "+f"(d[3])
        : "r"(da), "r"(db), "r"(scale_d), "n"(TB), "n"(SA), "n"(HA));
}
template<int SA, int TB, int HA = 0x40000040, int M>
__device__ __forceinline__ void wgmma_n96(float (&d)[M], uint32_t da, uint32_t db, int scale_d) {
    asm volatile("{\n.reg .pred p;\n.reg .b32 hi, ha;\n.reg .b64 da, db;\nmov.b32 hi, 0x40000040;\nmov.b32 ha, %53;\nmov.b64 da, {%48, ha};\nmov.b64 db, {%49, hi};\nsetp.ne.b32 p, %50, 0;\n"
        "wgmma.mma_async.sync.aligned.m64n96k16.f32.bf16.bf16 "
        "{%0, %1, %2, %3, %4, %5, %6, %7, %8, %9, %10, %11, %12, %13, %14, %15, "
        "%16, %17, %18, %19, %20, %21, %22, %23, %24, %25, %26, %27, %28, %29, %30, %31, "
        "%32, %33, %34, %35, %36, %37, %38, %39, %40, %41, %42, %43, %44, %45, %46, %47}, "
        "da, db, p, %52, 1, 0, %51;\n}\n"
        : "+f"(d[0]), "+f"(d[1]), "+f"(d[2]), "+f"(d[3]), "+f"(d[4]), "+f"(d[5]), "+f"(d[6]), "+f"(d[7]),
          "+f"(d[8]), "+f"(d[9]), "+f"(d[10]), "+f"(d[11]), "+f"(d[12]), "+f"(d[13]), "+f"(d[14]), "+f"(d[15]),
          "+f"(d[16]), "+f"(d[17]), "+f"(d[18]), "+f"(d[19]), "+f"(d[20]), "+f"(d[21]), "+f"(d[22]), "+f"(d[23]),
          "+f"(d[24]), "+f"(d[25]), "+f"(d[26]), "+f"(d[27]), "+f"(d[28]), "+f"(d[29]), "+f"(d[30]), "+f"(d[31]),
          "+f"(d[32]), "+f"(d[33]), "+f"(d[34]), "+f"(d[35]), "+f"(d[36]), "+f"(d[37]), "+f"(d[38]), "+f"(d[39]),
          "+f"(d[40]), "+f"(d[41]), "+f"(d[42]), "+f"(d[43]), "+f"(d[44]), "+f"(d[45]), "+f"(d[46]), "+f"(d[47])
        : "r"(da), "r"(db), "r"(scale_d), "n"(TB), "n"(SA), "n"(HA));
}
template<int SA, int TB, int HA = 0x40000040, int M>
__device__ __forceinline__ void wgmma_n112(float (&d)[M], uint32_t da, uint32_t db, int scale_d) {
    asm volatile("{\n.reg .pred p;\n.reg .b32 hi, ha;\n.reg .b64 da, db;\nmov.b32 hi, 0x40000040;\nmov.b32 ha, %61;\nmov.b64 da, {%56, ha};\nmov.b64 db, {%57, hi};\nsetp.ne.b32 p, %58, 0;\n"
        "wgmma.mma_async.sync.aligned.m64n112k16.f32.bf16.bf16 "
        "{%0, %1, %2, %3, %4, %5, %6, %7, %8, %9, %10, %11, %12, %13, %14, %15, "
        "%16, %17, %18, %19, %20, %21, %22, %23, %24, %25, %26, %27, %28, %29, %30, %31, "
        "%32, %33, %34, %35, %36, %37, %38, %39, %40, %41, %42, %43, %44, %45, %46, %47, "
        "%48, %49, %50, %51, %52, %53, %54, %55}, "
        "da, db, p, %60, 1, 0, %59;\n}\n"
        : "+f"(d[0]), "+f"(d[1]), "+f"(d[2]), "+f"(d[3]), "+f"(d[4]), "+f"(d[5]), "+f"(d[6]), "+f"(d[7]),
          "+f"(d[8]), "+f"(d[9]), "+f"(d[10]), "+f"(d[11]), "+f"(d[12]), "+f"(d[13]), "+f"(d[14]), "+f"(d[15]),
          "+f"(d[16]), "+f"(d[17]), "+f"(d[18]), "+f"(d[19]), "+f"(d[20]), "+f"(d[21]), "+f"(d[22]), "+f"(d[23]),
          "+f"(d[24]), "+f"(d[25]), "+f"(d[26]), "+f"(d[27]), "+f"(d[28]), "+f"(d[29]), "+f"(d[30]), "+f"(d[31]),
          "+f"(d[32]), "+f"(d[33]), "+f"(d[34]), "+f"(d[35]), "+f"(d[36]), "+f"(d[37]), "+f"(d[38]), "+f"(d[39]),
          "+f"(d[40]), "+f"(d[41]), "+f"(d[42]), "+f"(d[43]), "+f"(d[44]), "+f"(d[45]), "+f"(d[46]), "+f"(d[47]),
          "+f"(d[48]), "+f"(d[49]), "+f"(d[50]), "+f"(d[51]), "+f"(d[52]), "+f"(d[53]), "+f"(d[54]), "+f"(d[55])
        : "r"(da), "r"(db), "r"(scale_d), "n"(TB), "n"(SA), "n"(HA));
}
template<int SA, int TB, int HA = 0x40000040, int M>
__device__ __forceinline__ void wgmma_n128(float (&d)[M], uint32_t da, uint32_t db, int scale_d) {
    asm volatile("{\n.reg .pred p;\n.reg .b32 hi, ha;\n.reg .b64 da, db;\nmov.b32 hi, 0x40000040;\nmov.b32 ha, %69;\nmov.b64 da, {%64, ha};\nmov.b64 db, {%65, hi};\nsetp.ne.b32 p, %66, 0;\n"
        "wgmma.mma_async.sync.aligned.m64n128k16.f32.bf16.bf16 "
        "{%0, %1, %2, %3, %4, %5, %6, %7, %8, %9, %10, %11, %12, %13, %14, %15, "
        "%16, %17, %18, %19, %20, %21, %22, %23, %24, %25, %26, %27, %28, %29, %30, %31, "
        "%32, %33, %34, %35, %36, %37, %38, %39, %40, %41, %42, %43, %44, %45, %46, %47, "
        "%48, %49, %50, %51, %52, %53, %54, %55, %56, %57, %58, %59, %60, %61, %62, %63}, "
        "da, db, p, %68, 1, 0, %67;\n}\n"
        : "+f"(d[0]), "+f"(d[1]), "+f"(d[2]), "+f"(d[3]), "+f"(d[4]), "+f"(d[5]), "+f"(d[6]), "+f"(d[7]),
          "+f"(d[8]), "+f"(d[9]), "+f"(d[10]), "+f"(d[11]), "+f"(d[12]), "+f"(d[13]), "+f"(d[14]), "+f"(d[15]),
          "+f"(d[16]), "+f"(d[17]), "+f"(d[18]), "+f"(d[19]), "+f"(d[20]), "+f"(d[21]), "+f"(d[22]), "+f"(d[23]),
          "+f"(d[24]), "+f"(d[25]), "+f"(d[26]), "+f"(d[27]), "+f"(d[28]), "+f"(d[29]), "+f"(d[30]), "+f"(d[31]),
          "+f"(d[32]), "+f"(d[33]), "+f"(d[34]), "+f"(d[35]), "+f"(d[36]), "+f"(d[37]), "+f"(d[38]), "+f"(d[39]),
          "+f"(d[40]), "+f"(d[41]), "+f"(d[42]), "+f"(d[43]), "+f"(d[44]), "+f"(d[45]), "+f"(d[46]), "+f"(d[47]),
          "+f"(d[48]), "+f"(d[49]), "+f"(d[50]), "+f"(d[51]), "+f"(d[52]), "+f"(d[53]), "+f"(d[54]), "+f"(d[55]),
          "+f"(d[56]), "+f"(d[57]), "+f"(d[58]), "+f"(d[59]), "+f"(d[60]), "+f"(d[61]), "+f"(d[62]), "+f"(d[63])
        : "r"(da), "r"(db), "r"(scale_d), "n"(TB), "n"(SA), "n"(HA));
}
template<int SA, int TB, int HA = 0x40000040, int M>
__device__ __forceinline__ void wgmma_n224(float (&d)[M], uint32_t da, uint32_t db, int scale_d) {
    asm volatile("{\n.reg .pred p;\n.reg .b32 hi, ha;\n.reg .b64 da, db;\nmov.b32 hi, 0x40000040;\nmov.b32 ha, %117;\nmov.b64 da, {%112, ha};\nmov.b64 db, {%113, hi};\nsetp.ne.b32 p, %114, 0;\n"
        "wgmma.mma_async.sync.aligned.m64n224k16.f32.bf16.bf16 "
        "{%0, %1, %2, %3, %4, %5, %6, %7, %8, %9, %10, %11, %12, %13, %14, %15, "
        "%16, %17, %18, %19, %20, %21, %22, %23, %24, %25, %26, %27, %28, %29, %30, %31, "
        "%32, %33, %34, %35, %36, %37, %38, %39, %40, %41, %42, %43, %44, %45, %46, %47, "
        "%48, %49, %50, %51, %52, %53, %54, %55, %56, %57, %58, %59, %60, %61, %62, %63, "
        "%64, %65, %66, %67, %68, %69, %70, %71, %72, %73, %74, %75, %76, %77, %78, %79, "
        "%80, %81, %82, %83, %84, %85, %86, %87, %88, %89, %90, %91, %92, %93, %94, %95, "
        "%96, %97, %98, %99, %100, %101, %102, %103, %104, %105, %106, %107, %108, %109, %110, %111}, "
        "da, db, p, %116, 1, 0, %115;\n}\n"
        : "+f"(d[0]), "+f"(d[1]), "+f"(d[2]), "+f"(d[3]), "+f"(d[4]), "+f"(d[5]), "+f"(d[6]), "+f"(d[7]),
          "+f"(d[8]), "+f"(d[9]), "+f"(d[10]), "+f"(d[11]), "+f"(d[12]), "+f"(d[13]), "+f"(d[14]), "+f"(d[15]),
          "+f"(d[16]), "+f"(d[17]), "+f"(d[18]), "+f"(d[19]), "+f"(d[20]), "+f"(d[21]), "+f"(d[22]), "+f"(d[23]),
          "+f"(d[24]), "+f"(d[25]), "+f"(d[26]), "+f"(d[27]), "+f"(d[28]), "+f"(d[29]), "+f"(d[30]), "+f"(d[31]),
          "+f"(d[32]), "+f"(d[33]), "+f"(d[34]), "+f"(d[35]), "+f"(d[36]), "+f"(d[37]), "+f"(d[38]), "+f"(d[39]),
          "+f"(d[40]), "+f"(d[41]), "+f"(d[42]), "+f"(d[43]), "+f"(d[44]), "+f"(d[45]), "+f"(d[46]), "+f"(d[47]),
          "+f"(d[48]), "+f"(d[49]), "+f"(d[50]), "+f"(d[51]), "+f"(d[52]), "+f"(d[53]), "+f"(d[54]), "+f"(d[55]),
          "+f"(d[56]), "+f"(d[57]), "+f"(d[58]), "+f"(d[59]), "+f"(d[60]), "+f"(d[61]), "+f"(d[62]), "+f"(d[63]),
          "+f"(d[64]), "+f"(d[65]), "+f"(d[66]), "+f"(d[67]), "+f"(d[68]), "+f"(d[69]), "+f"(d[70]), "+f"(d[71]),
          "+f"(d[72]), "+f"(d[73]), "+f"(d[74]), "+f"(d[75]), "+f"(d[76]), "+f"(d[77]), "+f"(d[78]), "+f"(d[79]),
          "+f"(d[80]), "+f"(d[81]), "+f"(d[82]), "+f"(d[83]), "+f"(d[84]), "+f"(d[85]), "+f"(d[86]), "+f"(d[87]),
          "+f"(d[88]), "+f"(d[89]), "+f"(d[90]), "+f"(d[91]), "+f"(d[92]), "+f"(d[93]), "+f"(d[94]), "+f"(d[95]),
          "+f"(d[96]), "+f"(d[97]), "+f"(d[98]), "+f"(d[99]), "+f"(d[100]), "+f"(d[101]), "+f"(d[102]), "+f"(d[103]),
          "+f"(d[104]), "+f"(d[105]), "+f"(d[106]), "+f"(d[107]), "+f"(d[108]), "+f"(d[109]), "+f"(d[110]), "+f"(d[111])
        : "r"(da), "r"(db), "r"(scale_d), "n"(TB), "n"(SA), "n"(HA));
}
template<int TB, int SA = 1>
__device__ __forceinline__ void wgmma_rs_n32(float (&d)[16], const uint32_t (&a)[4], uint32_t db, int scale_d) {
    asm volatile("{\n.reg .pred p;\n.reg .b32 hi;\n.reg .b64 db;\nmov.b32 hi, 0x40000040;\nmov.b64 db, {%20, hi};\nsetp.ne.b32 p, %21, 0;\n"
        "wgmma.mma_async.sync.aligned.m64n32k16.f32.bf16.bf16 "
        "{%0, %1, %2, %3, %4, %5, %6, %7, %8, %9, %10, %11, %12, %13, %14, %15}, "
        "{%16, %17, %18, %19}, db, p, %23, 1, %22;\n}\n"
        : "+f"(d[0]), "+f"(d[1]), "+f"(d[2]), "+f"(d[3]), "+f"(d[4]), "+f"(d[5]), "+f"(d[6]), "+f"(d[7]),
          "+f"(d[8]), "+f"(d[9]), "+f"(d[10]), "+f"(d[11]), "+f"(d[12]), "+f"(d[13]), "+f"(d[14]), "+f"(d[15])
        : "r"(a[0]), "r"(a[1]), "r"(a[2]), "r"(a[3]), "r"(db), "r"(scale_d), "n"(TB), "n"(SA));
}
template<int TB, int SA = 1>
__device__ __forceinline__ void wgmma_rs_n56(float (&d)[28], const uint32_t (&a)[4], uint32_t db, int scale_d) {
    asm volatile("{\n.reg .pred p;\n.reg .b32 hi;\n.reg .b64 db;\nmov.b32 hi, 0x40000040;\nmov.b64 db, {%32, hi};\nsetp.ne.b32 p, %33, 0;\n"
        "wgmma.mma_async.sync.aligned.m64n56k16.f32.bf16.bf16 "
        "{%0, %1, %2, %3, %4, %5, %6, %7, %8, %9, %10, %11, %12, %13, %14, %15, "
        "%16, %17, %18, %19, %20, %21, %22, %23, %24, %25, %26, %27}, "
        "{%28, %29, %30, %31}, db, p, %35, 1, %34;\n}\n"
        : "+f"(d[0]), "+f"(d[1]), "+f"(d[2]), "+f"(d[3]), "+f"(d[4]), "+f"(d[5]), "+f"(d[6]), "+f"(d[7]),
          "+f"(d[8]), "+f"(d[9]), "+f"(d[10]), "+f"(d[11]), "+f"(d[12]), "+f"(d[13]), "+f"(d[14]), "+f"(d[15]),
          "+f"(d[16]), "+f"(d[17]), "+f"(d[18]), "+f"(d[19]), "+f"(d[20]), "+f"(d[21]), "+f"(d[22]), "+f"(d[23]),
          "+f"(d[24]), "+f"(d[25]), "+f"(d[26]), "+f"(d[27])
        : "r"(a[0]), "r"(a[1]), "r"(a[2]), "r"(a[3]), "r"(db), "r"(scale_d), "n"(TB), "n"(SA));
}
template<int TB, int SA = 1>
__device__ __forceinline__ void wgmma_rs_n64(float (&d)[32], const uint32_t (&a)[4], uint32_t db, int scale_d) {
    asm volatile("{\n.reg .pred p;\n.reg .b32 hi;\n.reg .b64 db;\nmov.b32 hi, 0x40000040;\nmov.b64 db, {%36, hi};\nsetp.ne.b32 p, %37, 0;\n"
        "wgmma.mma_async.sync.aligned.m64n64k16.f32.bf16.bf16 "
        "{%0, %1, %2, %3, %4, %5, %6, %7, %8, %9, %10, %11, %12, %13, %14, %15, "
        "%16, %17, %18, %19, %20, %21, %22, %23, %24, %25, %26, %27, %28, %29, %30, %31}, "
        "{%32, %33, %34, %35}, db, p, %39, 1, %38;\n}\n"
        : "+f"(d[0]), "+f"(d[1]), "+f"(d[2]), "+f"(d[3]), "+f"(d[4]), "+f"(d[5]), "+f"(d[6]), "+f"(d[7]),
          "+f"(d[8]), "+f"(d[9]), "+f"(d[10]), "+f"(d[11]), "+f"(d[12]), "+f"(d[13]), "+f"(d[14]), "+f"(d[15]),
          "+f"(d[16]), "+f"(d[17]), "+f"(d[18]), "+f"(d[19]), "+f"(d[20]), "+f"(d[21]), "+f"(d[22]), "+f"(d[23]),
          "+f"(d[24]), "+f"(d[25]), "+f"(d[26]), "+f"(d[27]), "+f"(d[28]), "+f"(d[29]), "+f"(d[30]), "+f"(d[31])
        : "r"(a[0]), "r"(a[1]), "r"(a[2]), "r"(a[3]), "r"(db), "r"(scale_d), "n"(TB), "n"(SA));
}
template<int TB, int SA = 1>
__device__ __forceinline__ void wgmma_rs_n96(float (&d)[48], const uint32_t (&a)[4], uint32_t db, int scale_d) {
    asm volatile("{\n.reg .pred p;\n.reg .b32 hi;\n.reg .b64 db;\nmov.b32 hi, 0x40000040;\nmov.b64 db, {%52, hi};\nsetp.ne.b32 p, %53, 0;\n"
        "wgmma.mma_async.sync.aligned.m64n96k16.f32.bf16.bf16 "
        "{%0, %1, %2, %3, %4, %5, %6, %7, %8, %9, %10, %11, %12, %13, %14, %15, "
        "%16, %17, %18, %19, %20, %21, %22, %23, %24, %25, %26, %27, %28, %29, %30, %31, "
        "%32, %33, %34, %35, %36, %37, %38, %39, %40, %41, %42, %43, %44, %45, %46, %47}, "
        "{%48, %49, %50, %51}, db, p, %55, 1, %54;\n}\n"
        : "+f"(d[0]), "+f"(d[1]), "+f"(d[2]), "+f"(d[3]), "+f"(d[4]), "+f"(d[5]), "+f"(d[6]), "+f"(d[7]),
          "+f"(d[8]), "+f"(d[9]), "+f"(d[10]), "+f"(d[11]), "+f"(d[12]), "+f"(d[13]), "+f"(d[14]), "+f"(d[15]),
          "+f"(d[16]), "+f"(d[17]), "+f"(d[18]), "+f"(d[19]), "+f"(d[20]), "+f"(d[21]), "+f"(d[22]), "+f"(d[23]),
          "+f"(d[24]), "+f"(d[25]), "+f"(d[26]), "+f"(d[27]), "+f"(d[28]), "+f"(d[29]), "+f"(d[30]), "+f"(d[31]),
          "+f"(d[32]), "+f"(d[33]), "+f"(d[34]), "+f"(d[35]), "+f"(d[36]), "+f"(d[37]), "+f"(d[38]), "+f"(d[39]),
          "+f"(d[40]), "+f"(d[41]), "+f"(d[42]), "+f"(d[43]), "+f"(d[44]), "+f"(d[45]), "+f"(d[46]), "+f"(d[47])
        : "r"(a[0]), "r"(a[1]), "r"(a[2]), "r"(a[3]), "r"(db), "r"(scale_d), "n"(TB), "n"(SA));
}
template<int TB, int SA = 1>
__device__ __forceinline__ void wgmma_rs_n112(float (&d)[56], const uint32_t (&a)[4], uint32_t db, int scale_d) {
    asm volatile("{\n.reg .pred p;\n.reg .b32 hi;\n.reg .b64 db;\nmov.b32 hi, 0x40000040;\nmov.b64 db, {%60, hi};\nsetp.ne.b32 p, %61, 0;\n"
        "wgmma.mma_async.sync.aligned.m64n112k16.f32.bf16.bf16 "
        "{%0, %1, %2, %3, %4, %5, %6, %7, %8, %9, %10, %11, %12, %13, %14, %15, "
        "%16, %17, %18, %19, %20, %21, %22, %23, %24, %25, %26, %27, %28, %29, %30, %31, "
        "%32, %33, %34, %35, %36, %37, %38, %39, %40, %41, %42, %43, %44, %45, %46, %47, "
        "%48, %49, %50, %51, %52, %53, %54, %55}, "
        "{%56, %57, %58, %59}, db, p, %63, 1, %62;\n}\n"
        : "+f"(d[0]), "+f"(d[1]), "+f"(d[2]), "+f"(d[3]), "+f"(d[4]), "+f"(d[5]), "+f"(d[6]), "+f"(d[7]),
          "+f"(d[8]), "+f"(d[9]), "+f"(d[10]), "+f"(d[11]), "+f"(d[12]), "+f"(d[13]), "+f"(d[14]), "+f"(d[15]),
          "+f"(d[16]), "+f"(d[17]), "+f"(d[18]), "+f"(d[19]), "+f"(d[20]), "+f"(d[21]), "+f"(d[22]), "+f"(d[23]),
          "+f"(d[24]), "+f"(d[25]), "+f"(d[26]), "+f"(d[27]), "+f"(d[28]), "+f"(d[29]), "+f"(d[30]), "+f"(d[31]),
          "+f"(d[32]), "+f"(d[33]), "+f"(d[34]), "+f"(d[35]), "+f"(d[36]), "+f"(d[37]), "+f"(d[38]), "+f"(d[39]),
          "+f"(d[40]), "+f"(d[41]), "+f"(d[42]), "+f"(d[43]), "+f"(d[44]), "+f"(d[45]), "+f"(d[46]), "+f"(d[47]),
          "+f"(d[48]), "+f"(d[49]), "+f"(d[50]), "+f"(d[51]), "+f"(d[52]), "+f"(d[53]), "+f"(d[54]), "+f"(d[55])
        : "r"(a[0]), "r"(a[1]), "r"(a[2]), "r"(a[3]), "r"(db), "r"(scale_d), "n"(TB), "n"(SA));
}
template<int TB, int SA = 1>
__device__ __forceinline__ void wgmma_rs_n224(float (&d)[112], const uint32_t (&a)[4], uint32_t db, int scale_d) {
    asm volatile("{\n.reg .pred p;\n.reg .b32 hi;\n.reg .b64 db;\nmov.b32 hi, 0x40000040;\nmov.b64 db, {%116, hi};\nsetp.ne.b32 p, %117, 0;\n"
        "wgmma.mma_async.sync.aligned.m64n224k16.f32.bf16.bf16 "
        "{%0, %1, %2, %3, %4, %5, %6, %7, %8, %9, %10, %11, %12, %13, %14, %15, "
        "%16, %17, %18, %19, %20, %21, %22, %23, %24, %25, %26, %27, %28, %29, %30, %31, "
        "%32, %33, %34, %35, %36, %37, %38, %39, %40, %41, %42, %43, %44, %45, %46, %47, "
        "%48, %49, %50, %51, %52, %53, %54, %55, %56, %57, %58, %59, %60, %61, %62, %63, "
        "%64, %65, %66, %67, %68, %69, %70, %71, %72, %73, %74, %75, %76, %77, %78, %79, "
        "%80, %81, %82, %83, %84, %85, %86, %87, %88, %89, %90, %91, %92, %93, %94, %95, "
        "%96, %97, %98, %99, %100, %101, %102, %103, %104, %105, %106, %107, %108, %109, %110, %111}, "
        "{%112, %113, %114, %115}, db, p, %119, 1, %118;\n}\n"
        : "+f"(d[0]), "+f"(d[1]), "+f"(d[2]), "+f"(d[3]), "+f"(d[4]), "+f"(d[5]), "+f"(d[6]), "+f"(d[7]),
          "+f"(d[8]), "+f"(d[9]), "+f"(d[10]), "+f"(d[11]), "+f"(d[12]), "+f"(d[13]), "+f"(d[14]), "+f"(d[15]),
          "+f"(d[16]), "+f"(d[17]), "+f"(d[18]), "+f"(d[19]), "+f"(d[20]), "+f"(d[21]), "+f"(d[22]), "+f"(d[23]),
          "+f"(d[24]), "+f"(d[25]), "+f"(d[26]), "+f"(d[27]), "+f"(d[28]), "+f"(d[29]), "+f"(d[30]), "+f"(d[31]),
          "+f"(d[32]), "+f"(d[33]), "+f"(d[34]), "+f"(d[35]), "+f"(d[36]), "+f"(d[37]), "+f"(d[38]), "+f"(d[39]),
          "+f"(d[40]), "+f"(d[41]), "+f"(d[42]), "+f"(d[43]), "+f"(d[44]), "+f"(d[45]), "+f"(d[46]), "+f"(d[47]),
          "+f"(d[48]), "+f"(d[49]), "+f"(d[50]), "+f"(d[51]), "+f"(d[52]), "+f"(d[53]), "+f"(d[54]), "+f"(d[55]),
          "+f"(d[56]), "+f"(d[57]), "+f"(d[58]), "+f"(d[59]), "+f"(d[60]), "+f"(d[61]), "+f"(d[62]), "+f"(d[63]),
          "+f"(d[64]), "+f"(d[65]), "+f"(d[66]), "+f"(d[67]), "+f"(d[68]), "+f"(d[69]), "+f"(d[70]), "+f"(d[71]),
          "+f"(d[72]), "+f"(d[73]), "+f"(d[74]), "+f"(d[75]), "+f"(d[76]), "+f"(d[77]), "+f"(d[78]), "+f"(d[79]),
          "+f"(d[80]), "+f"(d[81]), "+f"(d[82]), "+f"(d[83]), "+f"(d[84]), "+f"(d[85]), "+f"(d[86]), "+f"(d[87]),
          "+f"(d[88]), "+f"(d[89]), "+f"(d[90]), "+f"(d[91]), "+f"(d[92]), "+f"(d[93]), "+f"(d[94]), "+f"(d[95]),
          "+f"(d[96]), "+f"(d[97]), "+f"(d[98]), "+f"(d[99]), "+f"(d[100]), "+f"(d[101]), "+f"(d[102]), "+f"(d[103]),
          "+f"(d[104]), "+f"(d[105]), "+f"(d[106]), "+f"(d[107]), "+f"(d[108]), "+f"(d[109]), "+f"(d[110]), "+f"(d[111])
        : "r"(a[0]), "r"(a[1]), "r"(a[2]), "r"(a[3]), "r"(db), "r"(scale_d), "n"(TB), "n"(SA));
}

#define TR(idx) do {} while (0)
#define TRL(idx) do {} while (0)
#define TRX(idx) do {} while (0)
#define TRG(idx) do {} while (0)
#define TR_END() do {} while (0)

template<int V> struct Int { static constexpr int value = V; };
constexpr float ATT_SCALE = 0.18898223650461361f;
constexpr float LOG2E = 1.4426950408889634f;
constexpr uint32_t MASKED = 0xce6ece6eu;

__global__ void __cluster_dims__(2, 1, 1) __launch_bounds__(384, 1)
fused_kernel(__nv_bfloat16* __restrict__ out,
    const __grid_constant__ TMaps tm) {
    extern __shared__ __align__(1024) uint8_t smem_raw[];
    const uint32_t sb = smem_u32(smem_raw);
    const uint32_t bars = sb + BAR_OFF;
    const uint32_t bar_full = bars, bar_empty = bars + 32, bar_abf = bars + 64  , bar_ab = bars + 128  , bar_free = bars + 296  , bar_halo = bars + 152;
    const uint32_t bar_o = bars + 160, bar_qkv = bars + 176  , bar_sf = bars + 200, bar_se = bar_sf + 32  ;
    const uint32_t bar_fl = bars + 256  , bar_go = bars + 240  , bar_end = bars + 192, bar_af = bars + 312;
    const uint32_t stg = sb + STG_OFF;
    const int cta = blockIdx.x, r = cta & 1, cl = cta >> 1;
    const int place = pick3(cta, 32 + 8 * cl, cl - 4, cl - 3 + ((cl * 37 - 36 * 37) >> 8));
    const int mt = (place & 7) * 2 + r;
    const int sub = place >> 3;
    const CUtensorMap* tmWd = sub < 4 ? &tm.wdre : &tm.wdim;
    uint32_t t_first = 0;
    if (threadIdx.x < 32 + (((uint32_t)(uintptr_t)tmWd | sb | (mt << 6)) & 32) && elect_one()) {
        prefetch_tmap(tmWd); prefetch_tmap(&tm.xB);
        #pragma unroll
        for (int kb = 0; kb < START_N; kb++) {
            mbar_init(bar_abf + 8 * kb, 1);
            mbar_expect_tx(bar_abf + 8 * kb, AB_BYTES);
            tma_load(sb + kb * AB_BYTES + SLOT_A, tmWd, bar_abf + 8 * kb, kb * 64, (sub & 3) * 112);
            tma_load(sb + kb * AB_BYTES, &tm.xB, bar_abf + 8 * kb, kb * 64, mt * 128);
        }
        t_first = clk32();
    }
    const int tid = threadIdx.x, warp = __shfl_sync(0xffffffffu, tid >> 5, 0), lane = tid & 31;
    const bool late = sub < 4;
    const int nh = sub & 1, part = (sub >> 1) & 1;
    const int nj = late ? 32 - KB_EARLY : KB_EARLY;
    static_assert(KB_EARLY == 14, "order of the k-blocks");
    const uint32_t t0 = clk32();
    auto clear_out = [&]() {
        while ((int)(clk32() - t0) < TP(ZERO_AT)) { }
        uint4* zp = reinterpret_cast<uint4*>(out + (size_t)(mt * 128 + sub * 16 + (warp - 2) * 8) * NOUT + DM) + lane;
        #pragma unroll 1
        for (int j = 0; j < (ABL & 8 ? 0 : 8); j++) {
            while ((int)(clk32() - t0) < TP(ZERO_AT) + j * TP(ZERO_GAP)) { }
            zp[j * (NOUT / 8)] = make_uint4(0, 0, 0, 0);
            if (lane < 24) zp[j * (NOUT / 8) + 32] = make_uint4(0, 0, 0, 0);
        }
    };
    if (warp == 0) {
        if (elect_one()) {
            #pragma unroll
            for (int s = START_N; s < 7; s++) mbar_init(bar_abf + 8 * s, 1);
            #pragma unroll
            for (int s = 0; s < NSLOT; s++) { mbar_init(bar_full + 8 * s, 1); mbar_init(bar_empty + 8 * s, 4); }
            asm volatile("fence.mbarrier_init.release.cluster;" ::: "memory");
        }
        __syncwarp();
        cluster_arrive();
        if (elect_one()) {
            #pragma unroll 1
            for (int kb = START_N; kb < 7; kb++) {
                while ((int)(clk32() - t_first) < TP(START_GAP1) + (kb - START_N) * TP(START_GAP)) { }
                const uint32_t a = sb + kb * AB_BYTES, fb = bar_abf + 8 * kb;
                mbar_expect_tx(fb, AB_BYTES);
                tma_load(a, &tm.xB, fb, kb * 64, mt * 128);
                tma_load(a + SLOT_A, tmWd, fb, kb * 64, (sub & 3) * 112);
            }
            TR(2);
            prefetch_tmap(&tm.xA3); prefetch_tmap(&tm.wqkv3);
        }
        __syncwarp();
    } else if (warp < 4) {
        cluster_arrive();
        if (warp >= 2) clear_out();
    }
    if (warp < 4) {
      reg_set<REG_AUX>();
      const CUtensorMap* tmB = r ? &tm.abP3 : &tm.abP4;
      const uint32_t boff = SLOT_A + r * 16384;
      const int bgrp = part * 14 + nh * 7 + r * 4;
      if (warp == 0) {
        cluster_wait();
        if (elect_one()) {
        uint32_t slot = sb, fb = bar_full, par = 0;
        auto advance = [&]() { if (fb == bar_full + 24) { fb = bar_full; slot = sb; par ^= 1; } else { fb += 8; slot += SLOT_BYTES; } };
        const CUtensorMap* tmW = part ? &tm.wim : &tm.wre;
        const CUtensorMap* tmH = part ? &tm.wimH : &tm.wreH;
        const int qc = sub * 56 - (sub & 1) * 8;
        auto next_kc = [&](int kc, int wi) { return wi == 3 ? (late ? 14 * 64 : 2 * 64) : wi == nj / 2 - 1 ? (late ? 15 * 64 : 64) : kc + (FLIP && wi == 1 ? -768 : wi < nj / 2 ? 256 : 128); };
        #pragma unroll 1
        for (int it = 0; it < 7; it++) {
            mbar_wait_p(fb + 32, par);
            mbar_expect_tx(fb, SLOT_A + 3 * 8192);
            tma_load3(slot, &tm.xA3, fb, it * 64, mt * 64);
            tma_load3_mc(slot + SLOT_A + r * 12288, &tm.wqkv3, fb, qc, it * 64 + r * 32, 0);
            TRL(64 + it);
            if (r && it == 2) {
                const int c = (7 - sub) * 8 + (mt >> 1), c7 = (c * 37) >> 8;
                tma_prefetch3(&tm.xA3, (3 + (sub >> 1)) * 64, (mt - (sub & 1)) * 64);
                if (c7 < 8) tma_prefetch3(&tm.wqkv3, (c - 7 * c7) * 64, 192 + c7 * 32);
            }
            if (it == 1) { prefetch_tmap(tmW); prefetch_tmap(tmB); prefetch_tmap(tmH); }
            advance();
        }
        int kc = (late ? 1024 : 0) + 512 * FLIP;
        #pragma unroll 1
        for (int wi = 0; wi < nj - late; wi++) {
            mbar_wait_p(fb + 32, par);
            if (TP(W_GAP) && wi > 0 && wi < 4) { const uint32_t t1 = clk32() + TP(W_GAP); while ((int)(clk32() - t1) < 0) { } }
            mbar_expect_tx(fb, SLOT_BYTES);
            tma_load(slot, tmW, fb, kc, mt * 128);
            TR(224 + 7 + wi);
            if (wi >= 4) {
                if (wi == 4 || wi == nj / 2) mbar_wait(bar_fl + (wi == 4 ? 16 : 24), 0);
                tma_load5_mc(slot + boff, tmB, fb, kc, bgrp);
                TR(64 + 7 + wi);
            } else mbar_arrive(bar_go + 8 * wi);
            advance();
            kc = next_kc(kc, wi);
            if (wi == (late ? TP(PF_L) : TP(PF_E))) tma_prefetch(tmH, (late ? 29 : 13) * 64, mt * 128 + nh * 64);
            if (late) {
                if (wi == TP(L_XAT) - 1) {
                    mbar_wait(bar_se, 0);
                    mbar_expect_tx(bar_sf, SLOT_BYTES);
                    tma_load5_mc(stg + boff, tmB, bar_sf, 31 * 64, bgrp);
                }
                if (wi == TP(L_XAT)) tma_load(stg, tmW, bar_sf, 31 * 64, mt * 128);
            } else if (wi == TP(WB_AT)) {
                mbar_wait(bar_se, 0);
                #pragma unroll
                for (int j = 1; j < 7; j += 2) tma_load_mc(sb + OUT_B(j) + r * 8192, &tm.wo64, bar_abf, 256 + 48 * (sub & 3), (j + r) * 64);
            } else if (wi == TP(WO_AT) - 1) {
                const int c = mt * 4 + (sub & 3), c7 = (c * 37) >> 8;
                if (c < 49) tma_prefetch(&tm.wo64, (c - 7 * c7) * 64, c7 * 64); else prefetch_tmap(&tm.wo64);
            }
        }
        if (!late) {
            const uint4* const po = g_o + mt * 7168;
            const int ca = 64 * (sub & 3), cb = 256 + 48 * (sub & 3);
            auto load_w = [&](int d0, int c0, int j0, int d1, int c1, int j1, int g) { tma_load_mc(sb + (r ? d1 : d0), &tm.wo64, bar_abf + 8 * g, r ? c1 : c0, (r ? j1 : j0) * 64); };
            auto load_o = [&](int p, int j, int n, int g) { bulk_load(sb + OUT_O(p, j), po + p * 3584 + j * 512, n * 8192, bar_abf + 8 * g); };
            #pragma unroll
            for (int g = 0; g < 5; g++) mbar_expect_tx(bar_abf + 8 * g, (g == 0 ? 11 : g == 2 ? 5 : 4) * 8192);
            mbar_wait_p(bar_empty + 8, 1);
            load_w(OUT_A(0), ca, 0, OUT_A(1), ca, 1, 0);
            if (r == 0) load_w(OUT_B(0), cb, 0, 0, 0, 0, 0);
            TR(64 + 7 + KB_EARLY);
            mbar_wait_p(bar_fl + 32, 0);
            TR(3);
            load_o(0, 0, 2, 0);
            mbar_wait_p(bar_af, 0);
            load_w(OUT_A(2), ca, 2, OUT_A(3), ca, 3, 1); load_o(0, 2, 2, 1);
            if (r) load_w(0, 0, 0, OUT_A(4), ca, 4, 2);
            TR(64 + 7 + KB_EARLY + 1);
            mbar_wait_p(bar_empty + 16, 1);
            load_o(0, 4, 2, 2); load_w(OUT_A(5), ca, 5, OUT_A(6), ca, 6, 2);
            TR(64 + 7 + KB_EARLY + 2);
            mbar_wait_p(bar_empty + 24, 1);
            load_o(0, 6, 4, 3);
            TR(64 + 7 + KB_EARLY + 3);
            mbar_wait_p(bar_empty, 0);
            load_o(1, 3, 4, 4);
            TR(64 + 7 + KB_EARLY + 4);
        }
        mbar_arrive(bar_end);
        }
      } else {
        const unsigned epoch = ld_relaxed(&g_epoch[cta * 8]) + 1;
        cluster_wait();
        auto forward = [&](const unsigned* fl, unsigned target, auto first, uint32_t bar, uint32_t again) {
            for (int spin = 0; !__all_sync(0xffffffffu, (int)(ld_acquire(fl) - target) >= 0);) {
                if ((int)(clk32() - again) < 0) { while ((int)(clk32() - again) < 0) { } } else __nanosleep(target != epoch ? TP(OPOLL_NS) : TP(POLL_NS));
                if (++spin > SPIN_LIMIT) give_up();
            }
            if (elect_one()) {
                fence_async_global();
                if constexpr (decltype(first)::value == 2) { if (atomicExch(reinterpret_cast<unsigned*>(smem_raw + BAR_OFF + 144), 1u) == 0) mbar_arrive(bar); }
                else if constexpr (!decltype(first)::value) mbar_arrive(bar);
                else {
                    #pragma unroll
                    for (int i = 0; i < 2; i++) {
                        const int wi = 2 * (warp - 2) + i, sl = (wi + 3) & 3;
                        mbar_wait_limit(bar_go + 8 * wi, 0);
                        tma_load5_mc(sb + sl * SLOT_BYTES + boff, tmB, bar_full + 8 * sl, (late ? 1024 : 0) + 256 * (wi ^ 2 * FLIP), bgrp);
                        TR(64 + 7 + wi);
                        if (i == 0) { const uint32_t t1 = clk32() + TP(BIG_GAP); while ((int)(clk32() - t1) < 0) { } }
                    }
                }
            }
            __syncwarp();
        };
        const int frow = part * 4 + nh * 2 + (lane & 1), st0 = late ? 8 : 0;
        const int ft = late ? min(7 + (lane >> 1), 15) : min(lane >> 1, 6);
        const unsigned* const fl2 = &g_flag_ab[(32 + frow) * 32 + (late ? min(7 + (lane & 14), 15) : min(1 + (lane & 14), 5))];
        const unsigned* const fl3 = &g_flag_ab[(16 + 8 * (ft & 1) + frow) * 32 + ft];
        if (warp == 1) {
            if (elect_one()) {
                prefetch_tmap(&tm.abH); if (BIG_ST) { prefetch_tmap(&tm.ab80); prefetch_tmap(&tm.ab32); }
                const int e0 = pin(sub * 112 - (sub & 2) * 16), e1 = pin((sub & 3) == 2 ? 224 : 0);
                #pragma unroll 1
                for (int hf = 0; hf < 2; hf++) {
                    const int gap = pin(hf ? (r ? TP(ABS_GAP3) : TP(ABS_GAP2)) : (r ? TP(ABS_GAP) : 0)), sc = pin(mt * 128 + hf * 64);
                    const uint32_t src = pin(hf ? stg : sb + 7 * AB_BYTES);
                    unsigned* const fl = pin(&g_flag_ab[((hf ? 2 + r : r ? 4 : URG(mt)) * 8 + sub) * 32 + mt]);
                    mbar_wait(bar_ab + 8 * hf, 0);
                    fence_async_smem();
                    uint32_t t1 = clk32() + (hf ? 0 : r ? TP(ABS_AT) : URG(mt) * TP(ABS_AT1));
                    if (BIG_ST && (hf | r) == 0) {
                        if (URG(mt)) { while ((int)(clk32() - t1) < 0) { } }
                        TR(4);
                        tma_store(&tm.ab80, src + 4096, sc, e0 + 32);
                        tma_store(&tm.ab32, src, sc, e0 + e1);
                    } else
                    #pragma unroll
                    for (int i = 0; i < 7; i++) {
                        if (i == 0 || gap) { while ((int)(clk32() - t1) < 0) { } }
                        t1 += gap;
                        if (i == 0 && hf == 0) TR(4);
                        if (hf > r && i % 3 == 0 && i / 3 < TP(PF_N)) tma_prefetch(part ? &tm.wim : &tm.wre, (late ? 1024 : 0) + ((i / 3) ^ 2 * FLIP) * 256, (mt + nh) * 128);
                        tma_store(&tm.abH, src + i * 2048, sc, e0 + i * 16 + (i < 2 ? e1 : 0));
                    }
                    bulk_commit();
                    bulk_wait_all();
                    if (hf) TR(5);
                    mbar_arrive(bar_free + 8 * hf);
                    st_release(fl, epoch);
                    TR(hf ? 6 : 38);
                }
                uint4* const po = pin(g_o + mt * 7168 + sub * 448);
                mbar_wait(bar_o, 0);
                fence_async_smem();
                TR(9);
                {
                    uint32_t t2 = clk32();
                    #pragma unroll 1
                    for (int i = 0; i < 2 * O_N; i++) {
                        while ((int)(clk32() - t2) < 0) { }
                        t2 += TP(O_GAP);
                        bulk_store(po + (i >= O_N ? 3584 - 448 : 0) + i * (448 / O_N), stg + i * (7168 / O_N), 7168 / O_N);
                    }
                }
                bulk_commit();
                TR(62);
                bulk_wait_all();
                TR(111);
                mbar_arrive(bar_se); mbar_arrive_remote(bar_se, r ^ 1);
                red_release(&g_flag_o[mt * 32], 1);
                TR(17); TRG(102);
                if (!late) {
                    prefetch_tmap(&tm.outA); prefetch_tmap(&tm.outB);
                    #pragma unroll
                    for (int c = 0; c < 2; c++) {
                        mbar_wait(bar_qkv + 8 * c, 1);
                        fence_async_smem();
                        tma_store3(c ? &tm.outB : &tm.outA, sb + OUT_ST + c * 8192, mt * 64, sub & 3);
                    }
                    bulk_commit();
                    asm volatile("cp.async.bulk.wait_group.read 0;" ::: "memory");
                    TR(19);
                }
            }
            __syncwarp();
        } else {
            asm volatile("st.shared.u32 [%0], %1;" :: "r"(bars + 168), "r"(epoch) : "memory");
            if (OPOLL2_ON) asm volatile("st.shared.u32 [%0], %1;" :: "r"(bars + 144), "r"(0) : "memory");
            __syncwarp();
            if (lane == 0) mbar_arrive(bar_ab + 8);
            mbar_wait_limit(bar_ab, 0);
            const uint32_t ta = clk32();
            if (tid == 96) TRG(98);
            const bool rest = warp == 3 && __all_sync(0xffffffffu, (int)(ld_acquire(lane >= 22 ? fl2 : fl3) - epoch) >= 0);
            forward(&g_flag_ab[((warp - 2) * 8 + frow) * 32 + st0 + 4 * ((warp - 2) ^ FLIP) + (lane & 2)], epoch, Int<1>(), 0, ta + (warp == 2 ? TP(POLL_AT) : TP(POLL_AT1)));
            if (warp == 2) {
                const uint4* const hp = pin(g_halo + (max(mt - 1, 0) * 8 + sub) * 320 + lane);
                const uint32_t ha = pin(stg + KV_OFF + (lane & 7) * KV_PITCH + (lane >> 3) * 16);
                mbar_wait(mt > 0 ? bar_go + 24 : bar_qkv, 0);
                uint4 v[10];
                if (mt > 0) {
                    const uint32_t tq = clk32();
                    while ((int)(clk32() - tq) < TP(HALO_WAIT)) { }
                    #pragma unroll 1
                    for (;;) {
                        uint32_t bad = 0;
                        #pragma unroll
                        for (int j = 0; j < 10; j++) v[j] = ld_b128_relaxed(hp + j * 32);
                        #pragma unroll
                        for (int j = 0; j < 10; j++) bad |= v[j].w ^ epoch;
                        if (__all_sync(0xffffffffu, bad == 0) || (ABL & 1)) break;
                        __nanosleep(200);
                    }
                } else {
                    const uint32_t r0 = stg + KV_OFF + 8 * KV_PITCH + 112 + (lane & 3) * 4;
                    v[0].x = v[0].y = v[0].z = v[1].x = v[1].y = v[1].z = v[2].x = 0;
                    v[2].y = lds32(r0); v[2].z = lds32(r0 + 16); v[3].x = lds32(r0 + 32); v[3].y = lds32(r0 + 48); v[3].z = lds32(r0 + 64); v[4].x = lds32(r0 + 80); v[4].y = lds32(r0 + 96);
                    #pragma unroll
                    for (int j = 0; j < 5; j++) v[5 + j] = v[j];
                }
                mbar_wait(bar_free, 0);
                #pragma unroll
                for (int p = 0; p < 2; p++) {
                    const uint4* u = v + 5 * p;
                    stsm_x4(ha + p * KV_PAR, u[0].x, u[0].y, u[0].z, u[1].x);
                    stsm_x4(ha + p * KV_PAR + 64, u[1].y, u[1].z, u[2].x, u[2].y);
                    stsm_x4(ha + p * KV_PAR + 128, u[2].z, u[3].x, u[3].y, u[3].z);
                    stsm_x2(ha + p * KV_PAR + 192, u[4].x, u[4].y);
                }
                __syncwarp();
                if (lane == 0) { mbar_arrive(bar_halo); TR(10); TRG(100); }
                if (OPOLL2_ON && !late) {
                    mbar_wait(bar_ab + 8, 0);
                    const uint32_t at = ta + TP(OPOLL_AT) + TP(OPOLL2);
                    while ((int)(clk32() - at) < 0) { }
                    forward(&g_flag_o[mt * 32], epoch * 8, Int<2>(), bar_fl + 32, at);
                }
            } else {
                #pragma unroll 1
                for (int j = 2; j < (late ? 4 : 5); j++) {
                    const unsigned* const fl = j == 2 ? fl2 : j == 4 ? &g_flag_o[mt * 32] : lane < 24 ? fl3 : &g_flag_ab[(16 + 8 * r + (lane & 7)) * 32 + mt];
                    const uint32_t at = ta + (j == 2 ? TP(POLL_AT2) : j == 3 ? TP(POLL_AT3) : TP(OPOLL_AT));
                    if (!rest) { while ((int)(clk32() - at) < 0) { } }
                    if (OPOLL2_ON && j == 4) { mbar_wait(bar_ab + 8, 0); forward(fl, epoch * 8, Int<2>(), bar_fl + 32, at); } else
                    forward(fl, j == 4 ? epoch * 8 : epoch, Int<0>(), bar_fl + 8 * j, at);
                    if (lane == 0) TR(j == 3 ? 39 : j == 4 ? 13 : 35 + j);
                }
                mbar_wait_limit(bar_end, 0);
            }
            __syncwarp();
        }
      }
      TR_END();
    } else {
        if (tid == 128) {
            mbar_init(bar_ab, 4); mbar_init(bar_ab + 8, 6); mbar_init(bar_free, 1); mbar_init(bar_free + 8, 1); mbar_init(bar_qkv, 4); mbar_init(bar_qkv + 8, 4); mbar_init(bar_o, 8);
            mbar_init(bar_halo, 1); mbar_init(bar_end, 3);
            #pragma unroll
            for (int j = 0; j < 7; j++) mbar_init(bar_go + 8 * j, 1);
            mbar_init(bar_sf, 1); mbar_init(bar_se, 2); mbar_init(bar_af, 4);
            asm volatile("fence.mbarrier_init.release.cluster;" ::: "memory");
        }
        __syncwarp();
        cluster_arrive();
        if (warp >= 8) {
            float d[4];
            #pragma unroll 1
            for (int i = 0; i < TP(WARM_N); i++) {
                const uint32_t t1 = clk32();
                wgmma_fence();
                wgmma_n8<1, 0>(d, desc_k(sb + 7 * AB_BYTES), desc_k(sb + 7 * AB_BYTES), 0);
                wgmma_commit();
                wgmma_wait<0>();
                while ((int)(clk32() - t1) < TP(WARM_GAP)) { }
                __syncwarp();
            }
        }
        cluster_wait();
        const int wg = warp >> 3, w = warp & 3, cw = warp - 4;

        const bool sig_local = (tid & 127) == 0;
        const int i8 = lane & 7, m = lane >> 3;
        const bool sig = (tid & 95) == 0;
        uint32_t rel;
        asm("mapa.shared::cluster.u32 %0, %1, %2;" : "=r"(rel) : "r"(bar_empty), "r"(r ^ (w & 1)));
        auto done = [&](int it) { (void)it; if ((tid & 127) == 64) TRL(160 + it); };
        auto release = [&](int s) { if (sig) asm volatile("mbarrier.arrive.shared::cluster.b64 _, [%0];" :: "r"(rel + 8 * s) : "memory"); };
        const uint32_t dA = desc_k(sb + wg * 8192), dB = desc_k(sb + SLOT_A), dBt = desc_mn(sb + SLOT_A);
        const uint32_t a_frag = sb + wg * 8192 + (w * 16 + (lane & 15)) * 128 + (((lane >> 4) ^ i8) << 4);
        auto wait_full = [&](int it) { mbar_wait(bar_full + 8 * (it & 3), (it >> 2) & 1); if (sig_local) TR(128 + wg * 64 + it); };
        uint32_t kq[4][4], vq[14], qb[2][8];
        {
            float aq[28], ak[28], av[28];
            uint32_t mh0 = 0;
            uint32_t af[2][4][4];
            auto load_af = [&](int it) {
                wait_full(it);
                #pragma unroll
                for (int k = 0; k < 4; k++) ldsm_x4((a_frag ^ (k << 5)) + (it & 3) * SLOT_BYTES, af[it & 1][k][0], af[it & 1][k][1], af[it & 1][k][2], af[it & 1][k][3]);
            };
            uint32_t abw[28], base;
            auto stage_ab = [&](int j0, int j1) {
                #pragma unroll
                for (int j = j0; j < j1; j++) {
                    if (j < 7) stsm_x4_t(base + j * 2048, abw[4 * j], abw[4 * j + 1], abw[4 * j + 2], abw[4 * j + 3]);
                    else { __syncwarp(); if (lane == 0) mbar_arrive(bar_ab + 8 * wg); }
                }
            };
            {
                float bacc[56];
                base = pin((wg ? stg : sb + 7 * AB_BYTES) + (((2 * w + (m & 1)) ^ i8) << 4) + ((m >> 1) * 8 + i8) * 128);
                auto ab_loop = [&](auto sign) {
                auto ab_issue = [&](int kb) {
                    mbar_wait_p(bar_abf + 8 * kb, 0);
                    if (kb == 0 && wg == 1) asm volatile("bar.sync 3, 256;" ::: "memory");
                    if (sig_local) TR(112 + wg * 8 + kb);
                    wgmma_fence();
                    #pragma unroll
                    for (int k = 0; k < 4; k++) wgmma_n112<decltype(sign)::value, 0>(bacc, dA + kb * (AB_BYTES >> 4) + 2 * k, dB + kb * (AB_BYTES >> 4) + 2 * k, (kb | k) != 0);
                    wgmma_commit();
                    if (kb == 0 && wg == 0) asm volatile("bar.arrive 3, 256;" ::: "memory");
                };
                #pragma unroll
                for (int kb = 0; kb < 5; kb++) {
                    ab_issue(kb);
                    if (kb > 0) wgmma_wait<1>();
                    if (kb == 2 || kb == 3) release(kb - 2);
                }
                if (wg == 0) {
                    ab_issue(5);
                    ab_issue(6);
                    asm volatile("bar.arrive 4, 256;" ::: "memory");
                    wgmma_wait<2>();
                    release(2);
                } else {
                    uint32_t xf[8][4];
                    #pragma unroll
                    for (int j = 0; j < 8; j++) {
                        if ((j & 3) == 0) mbar_wait(bar_abf + 8 * (5 + (j >> 2)), 0);
                        ldsm_x4((a_frag ^ ((j & 3) << 5)) + (5 + (j >> 2)) * AB_BYTES, xf[j][0], xf[j][1], xf[j][2], xf[j][3]);
                    }
                    wgmma_wait<0>();
                    release(2);
                    asm volatile("bar.sync 4, 256;" ::: "memory");
                    wgmma_fence();
                    #pragma unroll
                    for (int j = 0; j < 8; j++) {
                        wgmma_rs_n112<0, decltype(sign)::value>(bacc, xf[j], dB + (5 + (j >> 2)) * (AB_BYTES >> 4) + 2 * (j & 3), 1);
                        if ((j & 3) == 3) wgmma_commit();
                    }
                }
                };
                if (sub >> 2) ab_loop(Int<-1>()); else ab_loop(Int<1>());
                wgmma_wait<1>();
                release(3);
                reg_set<REG_CONS>();
                if (wg == 1) load_af(0);
                wgmma_wait<0>();
                if (sig_local) TRX(21 + wg);
                if (AB_ST) { if (wg == 0) asm volatile("bar.arrive 3, 256;" ::: "memory"); else asm volatile("bar.sync 3, 256;" ::: "memory"); }
                #pragma unroll
                for (int j = 0; j < 28; j++) abw[j] = pack_bf16(bacc[2 * j], bacc[2 * j + 1]);
                stage_ab(0, AB_ST);
                if (wg == 0 || AB_ST == 7) stage_ab(AB_ST, 8);
            }
            const uint32_t dQ = dBt + (sub & 1);
            #pragma unroll
            for (int it = 0; it < 7; it++) {
                const uint32_t o = (it & 3) * (SLOT_BYTES >> 4);
                if (it > 0 || wg == 0) load_af(it);
                if (it == 5) mh0 = pin((lane & 3) < 2 ? 0xffffffffu : 0u);
                if (AB_ST < 7 && wg == 1) { if (it == 1) stage_ab(AB_ST, AB_ST2); if (it == 2) stage_ab(AB_ST2, 8); }
                wgmma_wait<0>();
                if (it > 0) { release((it - 1) & 3); done(it - 1); }
                if (it == 0 && sig_local) TRL(60 + wg);
                if (wg == 0) { if (it > 0) asm volatile("bar.sync 6, 256;" ::: "memory"); } else asm volatile("bar.sync 8, 256;" ::: "memory");
                wgmma_fence();
                #pragma unroll
                for (int j = 0; j < 12; j++) {
                    const int k = it < 6 || !KV_FIRST ? j / 3 : j < 8 ? j >> 1 : j - 8, x = it < 6 || !KV_FIRST ? j % 3 : j < 8 ? j & 1 : 2;
                    const uint32_t d = dQ + o + (k >> 1) * 768 + (k & 1) * 128;
                    if (j == Q_ARR) { if (wg == 0) asm volatile("bar.arrive 8, 256;" ::: "memory"); else asm volatile("bar.arrive 6, 256;" ::: "memory"); }
                    if (x == 0) wgmma_rs_n56<1>(ak, af[it & 1][k], d + 256, (it | k) != 0);
                    if (x == 1) wgmma_rs_n56<1>(av, af[it & 1][k], d + 512, (it | k) != 0);
                    if (x == 2) wgmma_rs_n56<1>(aq, af[it & 1][k], d, (it | k) != 0);
                    if (KV_FIRST && it == 6 && j == 7) wgmma_commit();
                }
                wgmma_commit();
            }
            uint4* const hp = pin(g_halo + (mt * 8 + sub) * 320 + wg * 160 + lane);
            mbar_wait(bar_ab + 8, 0);
            const uint32_t epoch = lds32(bars + 168);
            wgmma_wait<KV_FIRST>();
            #pragma unroll
            for (int j = 0; j < 16; j++) kq[j >> 2][j & 3] = pin(pack_bf16(ak[2 * (j - 2 * (j > 7))], ak[1 + 2 * (j - 2 * (j > 7))]));
            #pragma unroll
            for (int j = 0; j < 14; j++) vq[j] = pin(pack_bf16(av[2 * j], av[2 * j + 1]));
            if (w == 3 && !(ABL & 1)) {
                st_b128_relaxed(hp, kq[0][1], kq[0][3], kq[1][1], epoch);
                st_b128_relaxed(hp + 32, kq[1][3], kq[2][3], kq[3][1], epoch);
                st_b128_relaxed(hp + 64, kq[3][3], vq[1], vq[3], epoch);
                st_b128_relaxed(hp + 96, vq[5], vq[7], vq[9], epoch);
                st_b128_relaxed(hp + 128, vq[11], vq[13], 0u, epoch);
                if (lane == 0) TR(8);
            }
            wgmma_wait<0>();
            release(6 & 3);
            if (sig_local) TRX(23 + wg);
            #pragma unroll
            for (int j = 0; j < 14; j++) qb[j & 1][(j >> 1) + (j > 7)] = pin(pack_bf16(aq[2 * j], aq[2 * j + 1]));
            #pragma unroll
            for (int j = 0; j < 2; j++) { qb[j][4] = qb[j][3] & ~mh0; qb[j][3] &= mh0; }
        }
        float acc[112];
        const int it1 = 7 + nj;
        auto big_issue = [&](int slot, bool first) {
            wgmma_fence();
            #pragma unroll
            for (int k = 0; k < 4; k++) wgmma_n224<1, 0>(acc, dA + slot * (SLOT_BYTES >> 4) + 2 * k, dB + slot * (SLOT_BYTES >> 4) + 2 * k, !first || k != 0);
            wgmma_commit();
        };
        if (wg == 1) {
            asm volatile("bar.sync 7, 256;" ::: "memory");
            big_issue(3, true);
        } else {
            wait_full(7);
            asm volatile("bar.sync 6, 256;" ::: "memory");
            big_issue(3, true);
            asm volatile("bar.arrive 7, 256;" ::: "memory");
            if (sig_local) TR(20);
        }
        {
            auto plain = [&](int it) {
                wait_full(it); wgmma_wait<0>(); release((it - 1) & 3); done(it - 1); big_issue(it & 3, false);
                mbar_wait(bar_free, 0);
            };
            auto before_mma = [&](int it, int last) {
                if (wg == last) {
                    mbar_wait_limit(bar_full + 8 * (it & 3), (it >> 2) & 1);
                    if (sig_local) TR(128 + last * 64 + it);
                    asm volatile("bar.sync 2, 256;" ::: "memory");
                    wgmma_wait<0>();
                    release((it - 1) & 3);
                    done(it - 1);
                } else {
                    if (GAP_FLIP) { wgmma_wait<0>(); release((it - 1) & 3); }
                    asm volatile("bar.arrive 2, 256;" ::: "memory");
                }
            };
            auto after_mma = [&](int it, int last) {
                if (wg == (last ^ 1)) {
                    if (!GAP_FLIP) { wgmma_wait<0>(); release((it - 1) & 3); }
                    asm volatile("bar.sync 7, 256;" ::: "memory");
                    big_issue(it & 3, false);
                } else {
                    big_issue(it & 3, false);
                    asm volatile("bar.arrive 7, 256;" ::: "memory");
                }
            };
            const uint32_t kvw = stg + KV_OFF + wg * KV_PAR + (w * 16 + i8) * KV_PITCH;
            const uint32_t a_k = kvw + (m & 1) * 8 * KV_PITCH + (m >> 1) * 16, a_v = kvw + (m >> 1) * 8 * KV_PITCH + 112 + (m & 1) * 16;
            mbar_wait(bar_free, 0);
            #pragma unroll
            for (int u = 0; u < (ABL & 64 ? 0 : 3); u++) stsm_x4(a_k + 8 * KV_PITCH + 112 + u * 32, vq[4 * u], vq[4 * u + 1], vq[4 * u + 2], vq[4 * u + 3]);
            if (!(ABL & 64)) stsm_x2(a_k + 8 * KV_PITCH + 112 + 96, vq[12], vq[13]);
            plain(8);
            #pragma unroll
            for (int u = 0; u < (ABL & 64 ? 1 : 4); u++) stsm_x4(a_k + 8 * KV_PITCH + (2 * u - (u > 1)) * 16, kq[u][0], kq[u][1], kq[u][2], kq[u][3]);
            __syncwarp();
            if (lane == 0) mbar_arrive(bar_qkv + 8 * wg);
            if (sig_local) TR(25 + wg);
            uint32_t kp[4][4], vt[8][4], pb[4][2];
            auto load_v = [&](int n) {
                #pragma unroll
                for (int u = 0; u < 4; u++) {
                    if ((ABL & 64) && u > 0) { vt[2 * u + n][0] = vq[u]; vt[2 * u + n][1] = vq[u + 4]; vt[2 * u + n][2] = vq[u + 8]; vt[2 * u + n][3] = vq[u + n]; } else
                    ldsm_x4_t(a_v + n * 8 * KV_PITCH + (2 * u - (u > 1)) * 16, vt[2 * u + n][0], vt[2 * u + n][1], vt[2 * u + n][2], vt[2 * u + n][3]);
                }
            };
            load_v(1);
            plain(9);
            if (QK_AT > 10) plain(10);
            mbar_wait(w == 0 && !(ABL & 2) ? bar_halo : bar_qkv + 8 * wg, 0);
            #pragma unroll
            for (int u = 0; u < 4; u++) {
                if ((ABL & 64) && u > 0) { kp[u][0] = kq[u][1]; kp[u][1] = kq[u][0]; kp[u][2] = kq[u][3]; kp[u][3] = kq[u][2]; } else
                ldsm_x4(a_k + (2 * u - (u > 1)) * 16, kp[u][0], kp[u][1], kp[u][2], kp[u][3]);
            }
            if (sig_local) TR(54 + wg);
            before_mma(QK_AT, GAP_FLIP);
            float s[4][4];
            #pragma unroll
            for (int i = 0; i < 16; i++) s[i >> 2][i & 3] = 0.f;
            #pragma unroll
            for (int i = 0; i < (ABL & 4 ? 0 : 8); i++) {
                const int n = i & 1, h = (i >> 1) & 1, ks = 2 * h + (i >> 2);
                if (n) mma16816(s[i & 3], kq[ks][0], kq[ks][1], kq[ks][2], kq[ks][3], qb[1][2 * ks], qb[1][2 * ks + 1]);
                else mma16816(s[i & 3], kp[ks][0], kp[ks][1], kp[ks][2], kp[ks][3], qb[0][2 * ks], qb[0][2 * ks + 1]);
            }
            #pragma unroll
            for (int i = 0; i < 16; i++) asm volatile("" : "+f"(s[i >> 2][i & 3]) :: "memory");
            after_mma(QK_AT, GAP_FLIP);
            if (sig_local) TR(48 + wg);
            const int g = lane >> 2, t2 = 2 * (lane & 3);
            const uint32_t mlo = (t2 > g ? 0xffffu : 0u) | (t2 + 1 > g ? 0xffff0000u : 0u), before = (mt | w) == 0 ? mlo : 0u;
            uint32_t y[4], mx[2];
            #pragma unroll
            for (int i = 0; i < 4; i++) {
                const uint32_t x = pack_bf16(g > t2 ? s[i][0] : s[i][2], g > t2 + 1 ? s[i][1] : s[i][3]);
                y[i] = movm_t(pack_bf16(bf_lo(x) * ATT_SCALE, bf_hi(x) * ATT_SCALE));
                if (!(i & 1)) y[i] = (y[i] & ~before) | (MASKED & before);
            }
            #pragma unroll
            for (int h = 0; h < 2; h++) {
                mx[h] = max_bf16x2(__byte_perm(y[2 * h], y[2 * h + 1], 0x5410), __byte_perm(y[2 * h], y[2 * h + 1], 0x7632));
                mx[h] = pin(max_bf16x2(mx[h], __shfl_xor_sync(0xffffffffu, mx[h], 1)));
            }
            load_v(0);
            if (sig_local) TR(50 + wg);
            const bool second = wg == (GAP_FLIP ^ 1);
            if (SM_CUT == 0 || !second) plain(QK_AT + 1);
            #pragma unroll
            for (int h = 0; h < 2; h++) mx[h] = max_bf16x2(mx[h], __shfl_xor_sync(0xffffffffu, mx[h], 2));
            float e0[4], e1[4], sum[4];
            #pragma unroll
            for (int i = 0; i < 4; i++) {
                const float mi = i & 1 ? bf_hi(mx[i >> 1]) : bf_lo(mx[i >> 1]);
                e0[i] = ex2_approx((bf_lo(y[i]) - mi) * LOG2E); e1[i] = ex2_approx((bf_hi(y[i]) - mi) * LOG2E);
                sum[i] = e0[i] + e1[i];
                if (SM_CUT == 1) { e0[i] = pin(e0[i]); e1[i] = pin(e1[i]); sum[i] = pin(sum[i]); }
            }
            if (SM_CUT == 1 && second) plain(QK_AT + 1);
            #pragma unroll
            for (int i = 0; i < 4; i++) {
                sum[i] += __shfl_xor_sync(0xffffffffu, sum[i], 1);
                if (SM_CUT == 2) { e0[i] = pin(e0[i]); e1[i] = pin(e1[i]); sum[i] = pin(sum[i]); }
            }
            if (SM_CUT == 2 && second) plain(QK_AT + 1);
            #pragma unroll
            for (int i = 0; i < 4; i++) {
                sum[i] += __shfl_xor_sync(0xffffffffu, sum[i], 2);
                const float inv = rcp_approx(sum[i]);
                const uint32_t p = pack_bf16(e0[i] * inv, e1[i] * inv);
                pb[i][0] = pin(p & mlo); pb[i][1] = pin(p & ~mlo);
            }
            if (sig_local) TR(52 + wg);
            before_mma(QK_AT + 2, 0);
            float ao[8][4];
            #pragma unroll
            for (int i = 0; i < 8; i++) {
                ao[i][0] = ao[i][1] = ao[i][2] = ao[i][3] = 0.f;
                if (!(ABL & 4)) mma16816(ao[i], vt[i][0], vt[i][1], vt[i][2], vt[i][3], pb[(i >> 2) * 2 + (i & 1)][0], pb[(i >> 2) * 2 + (i & 1)][1]);
            }
            #pragma unroll
            for (int i = 0; i < 32; i++) asm volatile("" : "+f"(ao[i >> 2][i & 3]) :: "memory");
            after_mma(QK_AT + 2, 0);
            if (sig_local) TRX(11 + wg);
            if (g >= 4) { ao[2][2] = ao[4][0]; ao[2][3] = ao[4][1]; ao[3][2] = ao[5][0]; ao[3][3] = ao[5][1]; }
            mbar_wait(bar_free + 8, 0);
            const uint32_t orow = stg + wg * 7168 + (m >> 1) * 1024 + (w * 16 + (lane & 15)) * 16;
            stsm_x4_t(orow, pack_bf16(ao[0][0], ao[0][1]), pack_bf16(ao[1][0], ao[1][1]), pack_bf16(ao[0][2], ao[0][3]), pack_bf16(ao[1][2], ao[1][3]));
            stsm_x4_t(orow + 2048, pack_bf16(ao[2][0], ao[2][1]), pack_bf16(ao[3][0], ao[3][1]), pack_bf16(ao[2][2], ao[2][3]), pack_bf16(ao[3][2], ao[3][3]));
            stsm_x4_t(orow + 4096, pack_bf16(ao[4][2], ao[4][3]), pack_bf16(ao[5][2], ao[5][3]), pack_bf16(ao[6][0], ao[6][1]), pack_bf16(ao[7][0], ao[7][1]));
            stsm_x2_t(orow + 6144, pack_bf16(ao[6][2], ao[6][3]), pack_bf16(ao[7][2], ao[7][3]));
            __syncwarp();
            if (lane == 0) mbar_arrive(bar_o);
        }
        uint32_t af[4 * L_NB][4];
        #pragma unroll 1
        for (int it = QK_AT + 3; it < it1 - (late ? L_NB : 3); it++) {
            wait_full(it);
            wgmma_wait<0>();
            if (it != 7 + 32 - KB_EARLY - 4) release((it - 1) & 3);
            done(it - 1);
            big_issue(it & 3, false);
            if (L_PRE && it == 7 + 32 - KB_EARLY - L_NB - 2) {
                mbar_wait(bar_sf, 0);
                #pragma unroll
                for (int k = 0; k < 4; k++) ldsm_x4((a_frag ^ (k << 5)) + NSLOT * SLOT_BYTES, af[k][0], af[k][1], af[k][2], af[k][3]);
            }
        }
        mbar_wait(bar_fl + 24, 0);
        if (tid == 128) atomicAdd(&g_epoch[cta * 8], 1);
        __nv_bfloat16* const yp = pin(out + (size_t)(mt * 128 + cw * 16 + (lane >> 2)) * NOUT + DM + nh * 256 + (lane & 3) * 8);
        const int y6 = 192 - nh * 224;
        #define Y_WORD(A, i, jj) pack_bf16(A[16 * ((i) >> 1) + 4 * (jj) + 2 * ((i) & 1)], A[16 * ((i) >> 1) + 4 * (jj) + 2 * ((i) & 1) + 1])
        #define Y_ADDR(i) (yp + ((i) & 1) * 8 * NOUT + ((i) < 12 ? ((i) >> 1) * 32 : y6))
        const bool odd = lane & 4;
        __nv_bfloat16* const yq = pin(odd ? yp - NOUT + 32 : yp);
        #define Y_PAIR(A, i, B, j, rh, C, PAUSE) do { \
            uint32_t x_[4], y_[4]; \
            _Pragma("unroll") \
            for (int jj = 0; jj < 4; jj++) { \
                const uint32_t u_ = Y_WORD(A, 2 * (i) + (rh), jj), v_ = Y_WORD(B, 2 * (j) + (rh), jj), o_ = __shfl_xor_sync(0xffffffffu, odd ? u_ : v_, 4); \
                x_[jj] = odd ? o_ : u_; y_[jj] = odd ? v_ : o_; \
            } \
            red_add_bf16x8(yq + (rh) * 8 * NOUT + (C), x_[0], x_[1], x_[2], x_[3]); \
            PAUSE; \
            red_add_bf16x8(yq + ((rh) * 8 + 1) * NOUT + (C), y_[0], y_[1], y_[2], y_[3]); \
        } while (0)
        if (late) {
            constexpr int IT = 7 + 32 - KB_EARLY - L_NB;
            #define L_SLOT(j) ((j) == 0 ? NSLOT : (IT + (j) - 1) & 3)
            auto load_af = [&](int j) {
                if (j == 0) mbar_wait(bar_sf, 0); else wait_full(IT + j - 1);
                #pragma unroll
                for (int k = 0; k < 4; k++) ldsm_x4((a_frag ^ (k << 5)) + L_SLOT(j) * SLOT_BYTES, af[4 * j + k][0], af[4 * j + k][1], af[4 * j + k][2], af[4 * j + k][3]);
            };
            if (!L_PRE) load_af(0);
            load_af(1);
            if (L_UP) load_af(2);
            wgmma_wait<0>();
            done(IT - 1);
            if (!L_UP && wg == 1) load_af(2);
            if (L_NB == 4 && wg == 1) load_af(L_NB - 1);
            auto issue = [&](auto& p, auto c0, int j0, int j1, bool first, bool last) {
                constexpr int W = sizeof(p) / 2, C0 = decltype(c0)::value;
                if (wg == 0) { if (!first) asm volatile("bar.sync 9, 256;" ::: "memory"); } else asm volatile("bar.sync 5, 256;" ::: "memory");
                wgmma_fence();
                #pragma unroll
                for (int j = j0; j < j1; j++) {
                    if (!L_UP && first && j == 8) { if (wg == 0) load_af(2); wgmma_fence(); }
                    if (L_NB == 4 && first && j == 12) { if (wg == 0) load_af(L_NB - 1); wgmma_fence(); }
                    if (j == j1 - 12 + L_ARR) { if (wg == 0) asm volatile("bar.arrive 5, 256;" ::: "memory"); else if (!last) asm volatile("bar.arrive 9, 256;" ::: "memory"); }
                    const uint32_t d = dB + L_SLOT(j >> 2) * (SLOT_BYTES >> 4) + C0 * 8 + 2 * (j & 3);
                    if constexpr (W == 96) wgmma_rs_n96<0>(p, af[j], d, 1); else if constexpr (W == 64) wgmma_rs_n64<0>(p, af[j], d, 1); else wgmma_rs_n32<0>(p, af[j], d, 1);
                }
                wgmma_commit();
            };
            float pa[48], p0[32], p1[32];
            #pragma unroll
            for (int i = 0; i < 48; i++) asm volatile("mov.b32 %0, %1;" : "=f"(pa[i]) : "f"(acc[64 + i]));
            #pragma unroll
            for (int i = 0; i < 32; i++) asm volatile("mov.b32 %0, %1;" : "=f"(p1[i]) : "f"(acc[32 + i]));
            #pragma unroll
            for (int i = 0; i < 32; i++) asm volatile("mov.b32 %0, %1;" : "=f"(p0[i]) : "f"(acc[i]));
            issue(pa, Int<128>(), 0, 4 * L_NB, true, false);
            wgmma_wait<0>();
            if (sig_local) TRL(14 + wg);
            Y_PAIR(pa, 0, pa, 1, 0, 128, ); Y_PAIR(pa, 0, pa, 1, 1, 128, );
            #pragma unroll
            for (int i = 0; i < 2; i++) red_add_bf16x8(Y_ADDR(12 + i), Y_WORD(pa, 4 + i, 0), Y_WORD(pa, 4 + i, 1), Y_WORD(pa, 4 + i, 2), Y_WORD(pa, 4 + i, 3));
            issue(p0, Int<0>(), 0, 4 * L_NB, false, false);
            wgmma_wait<0>();
            Y_PAIR(p0, 0, p0, 1, 0, 0, ); Y_PAIR(p0, 0, p0, 1, 1, 0, );
            issue(p1, Int<64>(), 0, 4 * L_NB, false, true);
            if (sig_local) mbar_arrive(bar_end);
            wgmma_wait<0>();
            if (sig_local) TRX(27 + wg);
            Y_PAIR(p1, 0, p1, 1, 0, 64, ); Y_PAIR(p1, 0, p1, 1, 1, 64, );
            if (sig_local) TR(29 + wg);
        } else {
        constexpr int IT0 = 7 + KB_EARLY;
        auto load_af = [&](int j) {
            wait_full(IT0 - 3 + j);
            #pragma unroll
            for (int k = 0; k < 4; k++) ldsm_x4((a_frag ^ (k << 5)) + ((IT0 - 3 + j) & 3) * SLOT_BYTES, af[4 * j + k][0], af[4 * j + k][1], af[4 * j + k][2], af[4 * j + k][3]);
        };
        wait_full(IT0 - 3);
        wgmma_wait<0>();
        release((IT0 - 4) & 3);
        done(IT0 - 4);
        if (wg == 1) {
            load_af(0); load_af(1); load_af(2);
            asm volatile("bar.sync 5, 256;" ::: "memory");
            release((bar_af - bar_empty) / 8);
            #pragma unroll
            for (int it = IT0 - 3; it < IT0; it++) {
                if (it == IT0 - 1) { wgmma_wait<1>(); release((it - 2) & 3); }
                wgmma_fence();
                #pragma unroll
                for (int k = 0; k < 4; k++) wgmma_rs_n224<0>(acc, af[4 * (it - IT0 + 3) + k], dB + (it & 3) * (SLOT_BYTES >> 4) + 2 * k, 1);
                wgmma_commit();
            }
            asm volatile("bar.arrive 9, 256;" ::: "memory");
            wgmma_wait<1>();
            release((IT0 - 2) & 3);
            wgmma_wait<0>();
            release((IT0 - 1) & 3);
            if (sig_local) { mbar_arrive(bar_end); TRL(28); }
            const uint32_t t1 = clk32() + TP(RED_AT1);
            auto pause = [&](int i) {
                if (i == RW3) mbar_wait(bar_abf + 24, 1);
                if (i == RW4) mbar_wait(bar_abf + 32, 1);
                while ((int)(clk32() - t1) < i * TP(RED_GAP1)) { }
            };
            #pragma unroll
            for (int i = 0; i < 2; i++) { pause(i); red_add_bf16x8(Y_ADDR(12 + i), Y_WORD(acc, 12 + i, 0), Y_WORD(acc, 12 + i, 1), Y_WORD(acc, 12 + i, 2), Y_WORD(acc, 12 + i, 3)); }
            #pragma unroll
            for (int i = 0; i < 6; i++) { pause(2 + 2 * i); Y_PAIR(acc, i & 6, acc, (i & 6) + 1, i & 1, 32 * (i & 6), pause(3 + 2 * i)); }
            if (sig_local) TRX(30);
        } else {
            float lo[64], hi[48];
            #pragma unroll
            for (int i = 0; i < 48; i++) asm volatile("mov.b32 %0, %1;" : "=f"(hi[i]) : "f"(acc[64 + i]));
            #pragma unroll
            for (int i = 0; i < 64; i++) asm volatile("mov.b32 %0, %1;" : "=f"(lo[i]) : "f"(acc[i]));
            #pragma unroll
            for (int it = IT0 - 3; it < IT0; it++) {
                if (it == IT0 - 1) {
                    #pragma unroll
                    for (int k = 0; k < E_FILL; k++) wgmma_n96<1, 0>(hi, dA + ((IT0 - 3 + (k >> 2)) & 3) * (SLOT_BYTES >> 4) + 2 * (k & 3), dB + ((IT0 - 3 + (k >> 2)) & 3) * (SLOT_BYTES >> 4) + 1024 + 2 * (k & 3), 1);
                }
                if (it > IT0 - 3) wait_full(it);
                wgmma_fence();
                #pragma unroll
                for (int k = 0; k < 4; k++) wgmma_n128<1, 0>(lo, dA + (it & 3) * (SLOT_BYTES >> 4) + 2 * k, dB + (it & 3) * (SLOT_BYTES >> 4) + 2 * k, 1);
            }
            wgmma_commit();
            #define E_RED(i) do { if ((i) < 8) red_add_bf16x8(Y_ADDR(i), Y_WORD(lo, (i) & 7, 0), Y_WORD(lo, (i) & 7, 1), Y_WORD(lo, (i) & 7, 2), Y_WORD(lo, (i) & 7, 3)); \
                                  else red_add_bf16x8(Y_ADDR(i), Y_WORD(hi, (i) & 7, 0), Y_WORD(hi, (i) & 7, 1), Y_WORD(hi, (i) & 7, 2), Y_WORD(hi, (i) & 7, 3)); } while (0)
            #pragma unroll
            for (int j = E_FILL; j < 12; j++) {
                const int it = IT0 - 3 + (j >> 2), k = j & 3;
                if (j == E_FILL + E_SPLIT) {
                    wgmma_commit();
                    wgmma_wait<1>();
                    if (sig_local) TR(14);
                    #pragma unroll
                    for (int i = 0; i < RED_A; i++) E_RED(i);
                    wgmma_fence();
                }
                wgmma_n96<1, 0>(hi, dA + (it & 3) * (SLOT_BYTES >> 4) + 2 * k, dB + (it & 3) * (SLOT_BYTES >> 4) + 1024 + 2 * k, 1);
            }
            wgmma_commit();
            asm volatile("bar.arrive 5, 256;" ::: "memory");
            #pragma unroll
            for (int i = RED_A; i < RED_FAST; i++) E_RED(i);
            wgmma_wait<0>();
            release((bar_af - bar_empty) / 8); release((IT0 - 3) & 3); release((IT0 - 2) & 3); release((IT0 - 1) & 3);
            if (sig_local) TRL(27);
            const uint32_t t1 = clk32();
            #pragma unroll
            for (int i = RED_FAST; i < 14 - E_LATE; i++) {
                while ((int)(clk32() - t1) < (i - RED_FAST) * TP(RED_GAP)) { }
                E_RED(i);
            }
            if (sig_local) TR(29);
            float o0[56], o1[56];
            auto out_issue = [&](float (&oa)[56], int p, int j) {
                wgmma_fence();
                #pragma unroll
                for (int k = 0; k < (ABL & 32 ? 0 : 4); k++) wgmma_n112<1, 1, 8>(oa, dB + (63 << 16) + ((OUT_O(p, j) - SLOT_A) >> 4) + 128 * k, dB + ((((OUT_B(j) - OUT_A(j)) >> 4) - 1) << 16) + ((OUT_A(j) - SLOT_A) >> 4) + 128 * k, (j | k) != 0);
                wgmma_commit();
            };
            const uint32_t wa = pin(sb + w * 2048 + ((m & 1) * 8 + i8) * 128 + (((m >> 1) ^ i8) << 4)), ra = pin(sb + w * 2048 + m * 128 + ((i8 ^ m) << 4));
            auto stage = [&](float (&oa)[56], int buf, int u) {
                stsm_x4((wa ^ ((u & 3) << 5)) + buf + (u >> 2) * 8192, pack_bf16(oa[8 * u], oa[8 * u + 1]), pack_bf16(oa[8 * u + 2], oa[8 * u + 3]),
                        pack_bf16(oa[8 * u + 4], oa[8 * u + 5]), pack_bf16(oa[8 * u + 6], oa[8 * u + 7]));
            };
            __nv_bfloat16* const op = pin(out + (size_t)(mt * 128 + 1 + w * 32 + 2 * m) * NOUT + (sub & 3) * 64 + i8 * 8);
            const int c1 = 256 - (sub & 3) * 16;
            asm volatile("bar.sync 9, 256;" ::: "memory");
            #pragma unroll
            for (int j = 0; j < 7; j++) {
                if (!(j & 1)) { mbar_wait(bar_abf + 4 * j, 1); if (sig_local) TR(128 + IT0 + j); }
                out_issue(o0, 0, j);
                if (j < E_LATE) E_RED(14 - E_LATE + j);
            }
            #undef E_RED
            #pragma unroll
            for (int j = 0; j < 7; j++) {
                if (j == 3) { mbar_wait(bar_abf + 32, 1); if (sig_local) TR(192 + IT0 + j); }
                out_issue(o1, 1, j);
                if (j == 1) { wgmma_wait<2>(); if (sig_local) TR(31); }
                if (j >= 1 && j < 5) {
                    stage(o0, OUT_ST, 2 * j - 2);
                    if (j < 4) stage(o0, OUT_ST, 2 * j - 1);
                    if (j == 2 || j == 4) { __syncwarp(); if (lane == 0) mbar_arrive(bar_qkv + 4 * j - 8); }
                }
            }
            if (sig_local) mbar_arrive(bar_end);
            wgmma_wait<0>();
            if (sig_local) TRL(32);
            #pragma unroll
            for (int c = 0; c < 2; c++) {
                #pragma unroll
                for (int u = 4 * c; u < (c ? 7 : 4); u++) stage(o1, 0, u);
                __syncwarp();
                #pragma unroll
                for (int q = 0; q < 4; q++) {
                    uint4 v;
                    asm volatile("ld.shared.v4.u32 {%0, %1, %2, %3}, [%4];" : "=r"(v.x), "=r"(v.y), "=r"(v.z), "=r"(v.w) : "r"((ra ^ ((q & 1) << 6)) + c * 8192 + q * 512) : "memory");
                    if (c == 0 || i8 < 6) *reinterpret_cast<uint4*>(op + q * 8 * NOUT + (c ? c1 : 0)) = v;
                }
            }
        }
        }
        #undef Y_PAIR
        #undef Y_WORD
        #undef Y_ADDR
        if (sig_local) { TRX(33 + wg); if (wg == (late ? 1 : 0)) TRG(104); }
        TR_END();
    }
}

typedef CUresult (*EncodeFn)(CUtensorMap*, CUtensorMapDataType, cuuint32_t, void*, const cuuint64_t*, const cuuint64_t*,
                             const cuuint32_t*, const cuuint32_t*, CUtensorMapInterleave, CUtensorMapSwizzle,
                             CUtensorMapL2promotion, CUtensorMapFloatOOBfill);

void make_map(EncodeFn fn, CUtensorMap* tm, const void* ptr, uint64_t inner, uint64_t outer, uint32_t box_inner, uint32_t box_outer,
              CUtensorMapSwizzle sw = CU_TENSOR_MAP_SWIZZLE_128B, uint64_t clip = 0) {
    cuuint64_t gd[2] = {clip ? clip : inner, outer};
    cuuint64_t gs[1] = {inner * 2};
    cuuint32_t bd[2] = {box_inner, box_outer};
    cuuint32_t es[2] = {1, 1};
    fn(tm, CU_TENSOR_MAP_DATA_TYPE_BFLOAT16, 2, const_cast<void*>(ptr), gd, gs, bd, es, CU_TENSOR_MAP_INTERLEAVE_NONE,
       sw, CU_TENSOR_MAP_L2_PROMOTION_L2_128B, CU_TENSOR_MAP_FLOAT_OOB_FILL_NONE);
}
void make_map3(EncodeFn fn, CUtensorMap* tm, const void* ptr, uint64_t n0, uint64_t n1, uint64_t s1, uint64_t n2, uint64_t s2, uint32_t b1, uint32_t b2) {
    cuuint64_t gd[3] = {n0, n1, n2};
    cuuint64_t gs[2] = {s1 * 2, s2 * 2};
    cuuint32_t bd[3] = {64, b1, b2};
    cuuint32_t es[3] = {1, 1, 1};
    fn(tm, CU_TENSOR_MAP_DATA_TYPE_BFLOAT16, 3, const_cast<void*>(ptr), gd, gs, bd, es, CU_TENSOR_MAP_INTERLEAVE_NONE,
       CU_TENSOR_MAP_SWIZZLE_128B, CU_TENSOR_MAP_L2_PROMOTION_L2_128B, CU_TENSOR_MAP_FLOAT_OOB_FILL_NONE);
}
void make_map_perm(EncodeFn fn, CUtensorMap* tm, void* ptr, uint32_t n) {
    cuuint64_t gd[5] = {SEQ, 2, 4, 4, 28};
    cuuint64_t gs[4] = {SEQ * 2, 8 * SEQ * 2, 2 * SEQ * 2, 32 * SEQ * 2};
    cuuint32_t bd[5] = {64, 2, 4, 4, n};
    cuuint32_t es[5] = {1, 1, 1, 1, 1};
    fn(tm, CU_TENSOR_MAP_DATA_TYPE_BFLOAT16, 5, ptr, gd, gs, bd, es, CU_TENSOR_MAP_INTERLEAVE_NONE,
       CU_TENSOR_MAP_SWIZZLE_128B, CU_TENSOR_MAP_L2_PROMOTION_L2_128B, CU_TENSOR_MAP_FLOAT_OOB_FILL_NONE);
}

}

extern "C" void kernel_launch(void* const* d_in, const int* in_sizes, int n_in, void* d_out, int out_size) {
    (void)in_sizes; (void)n_in; (void)out_size;
    static EncodeFn fn = nullptr;
    static void* p_abT = nullptr;
    if (!fn) {
        void* p = nullptr; cudaDriverEntryPointQueryResult qr;
        cudaGetDriverEntryPoint("cuTensorMapEncodeTiled", &p, cudaEnableDefault, &qr);
        fn = (EncodeFn)p;
        cudaGetSymbolAddress(&p_abT, g_abT);
        cudaFuncSetAttribute(fused_kernel, cudaFuncAttributeMaxDynamicSharedMemorySize, SMEM_BYTES);
    }
    TMaps tm;
    make_map3(fn, &tm.xA3, d_in[0], DM, SEQ / 2, 2 * DM, 2, DM, 64, 2);
    make_map3(fn, &tm.wqkv3, d_in[1], DM, DM, 3 * DM, 3, DM, 32, 3);
    make_map(fn, &tm.wo64, d_in[2], DM, DM, 64, 64);
    make_map3(fn, &tm.outA, d_out, 64, SEQ / 2, 2 * NOUT, 4, 64, 64, 1);
    make_map3(fn, &tm.outB, (const __nv_bfloat16*)d_out + 256, 48, SEQ / 2, 2 * NOUT, 4, 48, 64, 1);
    make_map(fn, &tm.xB, d_in[3], DM, SEQ, 64, 128);
    make_map(fn, &tm.wre, d_in[4], SEQ, SEQ, 64, 128);
    make_map(fn, &tm.wim, d_in[5], SEQ, SEQ, 64, 128);
    make_map(fn, &tm.wreH, d_in[4], SEQ, SEQ, 64, 64);
    make_map(fn, &tm.wimH, d_in[5], SEQ, SEQ, 64, 64);
    make_map(fn, &tm.wdre, d_in[6], DM, DM, 64, 112);
    make_map(fn, &tm.wdim, d_in[7], DM, DM, 64, 112);
    make_map_perm(fn, &tm.abP4, p_abT, 4);
    make_map_perm(fn, &tm.abP3, p_abT, 3);
    make_map(fn, &tm.abH, p_abT, SEQ, 896, 64, 16);
    make_map(fn, &tm.ab32, p_abT, SEQ, 896, 64, 32);
    make_map(fn, &tm.ab80, p_abT, SEQ, 896, 64, 80);
    fused_kernel<<<NCTA, 384, SMEM_BYTES, cudaStreamPerThread>>>((__nv_bfloat16*)d_out,
        tm);
}
```

```cpp
#include <cuda_runtime.h>
#include <cuda_bf16.h>
#include <cuda.h>
#include <stdint.h>

namespace {

constexpr int SEQ = 2048, DM = 448, NOUT = 896;
constexpr int NCTA = 128;
constexpr int SLOT_A = 16384, SLOT_B = 28672, SLOT_BYTES = SLOT_A + SLOT_B, NSLOT = 4;
constexpr int AB_BYTES = SLOT_A + 112 * 128;
constexpr int STG_OFF = NSLOT * SLOT_BYTES;
constexpr int STG_BYTES = 7 * 7168;
constexpr int KV_PITCH = 240;
constexpr int KV_OFF = 2 * 7168, KV_PAR = 72 * KV_PITCH;
#define OUT_A(j) (((j) < 2 ? 48 + 8 * (j) : (j) < 4 ? 8 * (j) - 16 : (j) == 4 ? 136 : 80 + 8 * (j)) * 1024)
#define OUT_B(j) (((j) == 0 ? 80 : 168 + 8 * (j)) * 1024)
#define OUT_O(p, j) (((p) ? ((j) < 3 ? 152 + 8 * (j) : 8 * (j) - 8) : ((j) < 2 ? 64 + 8 * (j) : (j) < 6 ? 72 + 8 * (j) : 144)) * 1024)
#define OUT_ST OUT_O(0, 0)
constexpr int BAR_OFF = STG_OFF + STG_BYTES;
constexpr int TR_OFF = BAR_OFF + 512;
constexpr int SMEM_BYTES = TR_OFF + 1024;
constexpr int SPIN_LIMIT = 1 << 24;
#define TUNE_LIST(X) \
    X(START_GAP1, 400, 50, 0, 900)   \
    X(START_GAP, 280, 30, 0, 500)   \
    X(WARM_N, 3, 1, 0, 6)   \
    X(WARM_GAP, 150, 50, 50, 500)   \
    X(ZERO_GAP, 100, 50, 0, 300)   \
    X(ZERO_AT, 900, 200, 0, 2400)   \
    X(ABS_AT1, 500, 100, 0, 1000)   \
    X(ABS_AT, 1500, 150, 300, 3000)   \
    X(ABS_GAP, 60, 40, 0, 400)   \
    X(ABS_GAP2, 230, 40, 0, 400)   \
    X(ABS_GAP3, 100, 40, 0, 400)   \
    X(POLL_AT, 3100, 100, 2000, 4000)   \
    X(POLL_AT1, 3600, 150, 2000, 5000)   \
    X(POLL_AT2, 6300, 200, 4000, 8000)   \
    X(POLL_AT3, 9200, 200, 6000, 11000)   \
    X(OPOLL_AT, 15100, 200, 13000, 17500)   \
    X(OPOLL2, 500, 100, -1000, 1500)   \
    X(POLL_NS, 50, 100, 0, 800)   \
    X(OPOLL_NS, 100, 60, 0, 600)   \
    X(BIG_GAP, 250, 100, 0, 1000)   \
    X(W_GAP, 180, 100, 0, 900)   \
    X(HALO_WAIT, 350, 100, 0, 1500)   \
    X(O_GAP, 130, 60, 10, 600)   \
    X(PF_N, 0, 1, 0, 3)   \
    X(PF_E, 6, 1, 4, 13)   \
    X(PF_L, 14, 1, 4, 17)   \
    X(WO_AT, 7, 1, 5, 10)   \
    X(WB_AT, 10, 1, 10, 13)   \
    X(L_XAT, 13, 1, 10, 13)   \
    X(RED_GAP, 185, 30, 0, 300)   \
    X(RED_AT1, 0, 100, 0, 1000)   \
    X(RED_GAP1, 45, 30, 0, 300)   \

#define X(n, d, s, lo, hi) constexpr int n = d;
TUNE_LIST(X)
#undef X
#define TP(n) n
#define L_UP 1
#define ABL 0
#define BIG_ST 1
#define FLIP 1
#define URG(mt) ((((mt) >> 2) & 1) ^ FLIP)
#define AB_ST 7
#define AB_ST2 8
#define GAP_FLIP 1
#define L_PRE 1
#define E_FILL 2
#define KB_EARLY 14
#define O_N 2
#define QK_AT 10
#define WAIT_KIND 1
#define KV_FIRST 1
#define Q_ARR 11
#define E_SPLIT 7
#define RED_A 4
#define RED_FAST 6
#define L_ARR 11
#define OPOLL2_ON 1
#define E_LATE 2
#define L_NB 4
#define SM_CUT 1
#define RW3 9
#define RW4 99
#define START_N 2
#define REG_CONS 208
#define REG_AUX 88

struct __align__(64) TMaps { CUtensorMap xB, wdre, wdim, wre, wim, abP4, abP3, abH, ab32, ab80, wreH, wimH, wo64, xA3, wqkv3, outA, outB; };

__device__ __nv_bfloat16 g_abT[896 * SEQ];
__device__ uint4 g_o[SEQ * DM / 8];
__device__ uint4 g_halo[16 * 8 * 2 * 160];
__device__ unsigned g_flag_ab[40 * 32];
__device__ unsigned g_flag_o[16 * 32];
__device__ unsigned g_epoch[NCTA * 8];

__device__ __forceinline__ uint32_t smem_u32(const void* p) { return (uint32_t)__cvta_generic_to_shared(p); }
__device__ __forceinline__ uint32_t clk32() { uint32_t c; asm volatile("mov.u32 %0, %%clock;" : "=r"(c) :: "memory"); return c; }
__device__ __forceinline__ void give_up() { asm volatile("st.global.u32 [%0], 0;" :: "l"(0ull) : "memory"); }
__device__ __forceinline__ void mbar_init(uint32_t bar, uint32_t count) { asm volatile("mbarrier.init.shared::cta.b64 [%0], %1;" :: "r"(bar), "r"(count) : "memory"); }
__device__ __forceinline__ void mbar_expect_tx(uint32_t bar, uint32_t bytes) { asm volatile("mbarrier.arrive.expect_tx.shared::cta.b64 _, [%0], %1;" :: "r"(bar), "r"(bytes) : "memory"); }
__device__ __forceinline__ void mbar_arrive(uint32_t bar) { asm volatile("mbarrier.arrive.shared::cta.b64 _, [%0];" :: "r"(bar) : "memory"); }
__device__ __forceinline__ void mbar_arrive_remote(uint32_t bar, uint32_t cta) {
    asm volatile("{\n.reg .b32 ra;\nmapa.shared::cluster.u32 ra, %0, %1;\nmbarrier.arrive.shared::cluster.b64 _, [ra];\n}" :: "r"(bar), "r"(cta) : "memory");
}
__device__ __forceinline__ bool mbar_try_wait(uint32_t bar, uint32_t parity) {
    uint32_t ok;
    asm volatile("{\n.reg .pred p;\nmbarrier.try_wait.parity.shared::cta.b64 p, [%1], %2;\nselp.u32 %0, 1, 0, p;\n}" : "=r"(ok) : "r"(bar), "r"(parity) : "memory");
    return ok;
}
__device__ __forceinline__ bool mbar_test_wait(uint32_t bar, uint32_t parity) {
    uint32_t ok;
    asm volatile("{\n.reg .pred p;\nmbarrier.test_wait.parity.shared::cta.b64 p, [%1], %2;\nselp.u32 %0, 1, 0, p;\n}" : "=r"(ok) : "r"(bar), "r"(parity) : "memory");
    return ok;
}
#define WAIT_OP "pmevent 0;\nmbarrier.try_wait.parity.shared::cta.b64 p, [%0], %1;\n"
__device__ __forceinline__ void mbar_wait(uint32_t bar, uint32_t parity) {
    asm volatile("{\n.reg .pred p;\nWAIT:\n" WAIT_OP "@!p bra WAIT;\n}" :: "r"(bar), "r"(parity) : "memory");
}
__device__ __forceinline__ void mbar_wait_p(uint32_t bar, uint32_t parity) {
    asm volatile("{\n.reg .pred p;\nWAIT:\nmbarrier.try_wait.parity.shared::cta.b64 p, [%0], %1;\n@!p bra WAIT;\n}" :: "r"(bar), "r"(parity) : "memory");
}
__device__ __forceinline__ void mbar_wait_limit(uint32_t bar, uint32_t parity) {
    int it = 0;
    while (!mbar_try_wait(bar, parity)) { if (++it > SPIN_LIMIT) give_up(); }
}
__device__ __forceinline__ void tma_load(uint32_t dst, const CUtensorMap* tm, uint32_t bar, int c0, int c1) {
    asm volatile("cp.async.bulk.tensor.2d.shared::cluster.global.mbarrier::complete_tx::bytes [%0], [%1, {%3, %4}], [%2];"
        :: "r"(dst), "l"(tm), "r"(bar), "r"(c0), "r"(c1) : "memory");
}
__device__ __forceinline__ uint64_t policy_evict_first() { uint64_t p; asm volatile("createpolicy.fractional.L2::evict_first.b64 %0, 1.0;" : "=l"(p)); return p; }
__device__ __forceinline__ void tma_load_hint(uint32_t dst, const CUtensorMap* tm, uint32_t bar, int c0, int c1, uint64_t pol) {
    asm volatile("cp.async.bulk.tensor.2d.shared::cluster.global.mbarrier::complete_tx::bytes.L2::cache_hint [%0], [%1, {%3, %4}], [%2], %5;"
        :: "r"(dst), "l"(tm), "r"(bar), "r"(c0), "r"(c1), "l"(pol) : "memory");
}
__device__ __forceinline__ void tma_load_mc(uint32_t dst, const CUtensorMap* tm, uint32_t bar, int c0, int c1) {
    asm volatile("cp.async.bulk.tensor.2d.shared::cluster.global.mbarrier::complete_tx::bytes.multicast::cluster [%0], [%1, {%3, %4}], [%2], %5;"
        :: "r"(dst), "l"(tm), "r"(bar), "r"(c0), "r"(c1), "h"((uint16_t)3) : "memory");
}
__device__ __forceinline__ void tma_load3(uint32_t dst, const CUtensorMap* tm, uint32_t bar, int c0, int c1) {
    asm volatile("cp.async.bulk.tensor.3d.shared::cluster.global.mbarrier::complete_tx::bytes [%0], [%1, {%3, %4, %5}], [%2];"
        :: "r"(dst), "l"(tm), "r"(bar), "r"(c0), "r"(c1), "r"(0) : "memory");
}
__device__ __forceinline__ void tma_load3_mc(uint32_t dst, const CUtensorMap* tm, uint32_t bar, int c0, int c1, int c2) {
    asm volatile("cp.async.bulk.tensor.3d.shared::cluster.global.mbarrier::complete_tx::bytes.multicast::cluster [%0], [%1, {%3, %4, %6}], [%2], %5;"
        :: "r"(dst), "l"(tm), "r"(bar), "r"(c0), "r"(c1), "h"((uint16_t)3), "r"(c2) : "memory");
}
__device__ __forceinline__ void tma_prefetch(const CUtensorMap* tm, int c0, int c1) {
    asm volatile("cp.async.bulk.prefetch.tensor.2d.L2.global [%0, {%1, %2}];" :: "l"(tm), "r"(c0), "r"(c1) : "memory");
}
__device__ __forceinline__ void tma_prefetch3(const CUtensorMap* tm, int c0, int c1) {
    asm volatile("cp.async.bulk.prefetch.tensor.3d.L2.global [%0, {%1, %2, %3}];" :: "l"(tm), "r"(c0), "r"(c1), "r"(0) : "memory");
}
__device__ __forceinline__ void tma_store(const CUtensorMap* tm, uint32_t src, int c0, int c1) {
    asm volatile("cp.async.bulk.tensor.2d.global.shared::cta.bulk_group [%0, {%2, %3}], [%1];" :: "l"(tm), "r"(src), "r"(c0), "r"(c1) : "memory");
}
__device__ __forceinline__ void tma_store3(const CUtensorMap* tm, uint32_t src, int c1, int c2) {
    asm volatile("cp.async.bulk.tensor.3d.global.shared::cta.bulk_group [%0, {%2, %3, %4}], [%1];" :: "l"(tm), "r"(src), "r"(0), "r"(c1), "r"(c2) : "memory");
}
__device__ __forceinline__ void bulk_load(uint32_t dst, const void* src, uint32_t bytes, uint32_t bar) {
    asm volatile("cp.async.bulk.shared::cluster.global.mbarrier::complete_tx::bytes [%0], [%1], %2, [%3];" :: "r"(dst), "l"(src), "r"(bytes), "r"(bar) : "memory");
}
__device__ __forceinline__ void bulk_store(void* dst, uint32_t src, uint32_t bytes) {
    asm volatile("cp.async.bulk.global.shared::cta.bulk_group [%0], [%1], %2;" :: "l"(dst), "r"(src), "r"(bytes) : "memory");
}
__device__ __forceinline__ void tma_load5_mc(uint32_t dst, const CUtensorMap* tm, uint32_t bar, int c0, int c4) {
    asm volatile("cp.async.bulk.tensor.5d.shared::cluster.global.mbarrier::complete_tx::bytes.multicast::cluster [%0], [%1, {%3, %6, %6, %6, %4}], [%2], %5;"
        :: "r"(dst), "l"(tm), "r"(bar), "r"(c0), "r"(c4), "h"((uint16_t)3), "r"(0) : "memory");
}
__device__ __forceinline__ void red_add_bf16x8(__nv_bfloat16* p, uint32_t w0, uint32_t w1, uint32_t w2, uint32_t w3) {
    asm volatile("red.relaxed.gpu.global.add.noftz.v4.bf16x2 [%0], {%1, %2, %3, %4};" :: "l"(p), "r"(w0), "r"(w1), "r"(w2), "r"(w3) : "memory");
}
__device__ __forceinline__ void prefetch_tmap(const CUtensorMap* tm) { asm volatile("prefetch.tensormap [%0];" :: "l"(tm) : "memory"); }
__device__ __forceinline__ void cluster_arrive() { asm volatile("barrier.cluster.arrive.relaxed.aligned;" ::: "memory"); }
__device__ __forceinline__ void cluster_wait() { asm volatile("barrier.cluster.wait.aligned;" ::: "memory"); }
__device__ __forceinline__ void wgmma_fence() { asm volatile("wgmma.fence.sync.aligned;" ::: "memory"); }
__device__ __forceinline__ void wgmma_commit() { asm volatile("wgmma.commit_group.sync.aligned;" ::: "memory"); }
template<int N> __device__ __forceinline__ void wgmma_wait() { asm volatile("wgmma.wait_group.sync.aligned %0;" :: "n"(N) : "memory"); }
__device__ __forceinline__ void fence_async_smem() { asm volatile("fence.proxy.async.shared::cta;" ::: "memory"); }
__device__ __forceinline__ void fence_async_global() { asm volatile("fence.proxy.async.global;" ::: "memory"); }
__device__ __forceinline__ uint32_t desc_k(uint32_t addr) { return ((addr & 0x3FFFF) >> 4) | (1u << 16); }
__device__ __forceinline__ uint32_t desc_mn(uint32_t addr) { return ((addr & 0x3FFFF) >> 4) | ((8192u >> 4) << 16); }
template<int R> __device__ __forceinline__ void reg_set() {
    if (R > 168) asm volatile("setmaxnreg.inc.sync.aligned.u32 %0;" :: "n"(R));
    if (R < 168) asm volatile("setmaxnreg.dec.sync.aligned.u32 %0;" :: "n"(R));
}
__device__ __forceinline__ unsigned ld_acquire(const unsigned* p) { unsigned v; asm volatile("ld.acquire.gpu.global.u32 %0, [%1];" : "=r"(v) : "l"(p) : "memory"); return v; }
__device__ __forceinline__ unsigned ld_relaxed(const unsigned* p) { unsigned v; asm volatile("ld.relaxed.gpu.global.u32 %0, [%1];" : "=r"(v) : "l"(p) : "memory"); return v; }
__device__ __forceinline__ void st_release(unsigned* p, unsigned v) { asm volatile("fence.proxy.async.global;\nst.release.gpu.global.u32 [%0], %1;" :: "l"(p), "r"(v) : "memory"); }
__device__ __forceinline__ void red_release(unsigned* p, unsigned v) { asm volatile("fence.proxy.async.global;\nred.release.gpu.global.add.u32 [%0], %1;" :: "l"(p), "r"(v) : "memory"); }
__device__ __forceinline__ bool elect_one() {
    uint32_t pred;
    asm volatile("{\n.reg .pred p;\nelect.sync _|p, 0xffffffff;\nselp.u32 %0, 1, 0, p;\n}" : "=r"(pred));
    return pred;
}
__device__ __forceinline__ int pick3(int cta, int a, int b, int c) {
    int v;
    asm("{\n.reg .pred p, q;\nsetp.lt.s32 p, %1, 8;\nsetp.lt.s32 q, %1, 72;\nselp.b32 %0, %3, %4, q;\nselp.b32 %0, %2, %0, p;\n}" : "=&r"(v) : "r"(cta), "r"(a), "r"(b), "r"(c));
    return v;
}
template<typename T> __device__ __forceinline__ T pin(T v) {
    if constexpr (sizeof(T) == 8) asm volatile("" : "+l"(v) :: "memory");
    else if constexpr (T(0.5) != T(0)) asm volatile("" : "+f"(v) :: "memory");
    else asm volatile("" : "+r"(v) :: "memory");
    return v;
}
__device__ __forceinline__ void bulk_commit() { asm volatile("cp.async.bulk.commit_group;" ::: "memory"); }
__device__ __forceinline__ void bulk_wait_all() { asm volatile("cp.async.bulk.wait_group 0;" ::: "memory"); }
__device__ __forceinline__ uint32_t pack_bf16(float lo, float hi) { uint32_t r; asm("cvt.rn.bf16x2.f32 %0, %1, %2;" : "=r"(r) : "f"(hi), "f"(lo)); return r; }
__device__ __forceinline__ float bf_lo(uint32_t w) { return __uint_as_float(w << 16); }
__device__ __forceinline__ float bf_hi(uint32_t w) { return __uint_as_float(w & 0xffff0000u); }
__device__ __forceinline__ void stsm_x4(uint32_t addr, uint32_t r0, uint32_t r1, uint32_t r2, uint32_t r3) {
    asm volatile("stmatrix.sync.aligned.m8n8.x4.shared.b16 [%0], {%1, %2, %3, %4};" :: "r"(addr), "r"(r0), "r"(r1), "r"(r2), "r"(r3) : "memory");
}
__device__ __forceinline__ void stsm_x2(uint32_t addr, uint32_t r0, uint32_t r1) {
    asm volatile("stmatrix.sync.aligned.m8n8.x2.shared.b16 [%0], {%1, %2};" :: "r"(addr), "r"(r0), "r"(r1) : "memory");
}
__device__ __forceinline__ void stsm_x4_t(uint32_t addr, uint32_t r0, uint32_t r1, uint32_t r2, uint32_t r3) {
    asm volatile("stmatrix.sync.aligned.m8n8.x4.trans.shared.b16 [%0], {%1, %2, %3, %4};" :: "r"(addr), "r"(r0), "r"(r1), "r"(r2), "r"(r3) : "memory");
}
__device__ __forceinline__ void stsm_x2_t(uint32_t addr, uint32_t r0, uint32_t r1) {
    asm volatile("stmatrix.sync.aligned.m8n8.x2.trans.shared.b16 [%0], {%1, %2};" :: "r"(addr), "r"(r0), "r"(r1) : "memory");
}
__device__ __forceinline__ uint32_t movm_t(uint32_t x) { uint32_t r; asm volatile("movmatrix.sync.aligned.m8n8.trans.b16 %0, %1;" : "=r"(r) : "r"(x)); return r; }
__device__ __forceinline__ void ldsm_x4(uint32_t addr, uint32_t& r0, uint32_t& r1, uint32_t& r2, uint32_t& r3) {
    asm volatile("ldmatrix.sync.aligned.m8n8.x4.shared.b16 {%0, %1, %2, %3}, [%4];" : "=r"(r0), "=r"(r1), "=r"(r2), "=r"(r3) : "r"(addr) : "memory");
}
__device__ __forceinline__ void ldsm_x4_t(uint32_t addr, uint32_t& r0, uint32_t& r1, uint32_t& r2, uint32_t& r3) {
    asm volatile("ldmatrix.sync.aligned.m8n8.x4.trans.shared.b16 {%0, %1, %2, %3}, [%4];" : "=r"(r0), "=r"(r1), "=r"(r2), "=r"(r3) : "r"(addr) : "memory");
}
__device__ __forceinline__ void mma16816(float (&d)[4], uint32_t a0, uint32_t a1, uint32_t a2, uint32_t a3, uint32_t b0, uint32_t b1) {
    asm("mma.sync.aligned.m16n8k16.row.col.f32.bf16.bf16.f32 {%0, %1, %2, %3}, {%4, %5, %6, %7}, {%8, %9}, {%0, %1, %2, %3};"
        : "+f"(d[0]), "+f"(d[1]), "+f"(d[2]), "+f"(d[3]) : "r"(a0), "r"(a1), "r"(a2), "r"(a3), "r"(b0), "r"(b1));
}
__device__ __forceinline__ void mma1688(float (&d)[4], uint32_t a0, uint32_t a1, uint32_t b0) {
    asm("mma.sync.aligned.m16n8k8.row.col.f32.bf16.bf16.f32 {%0, %1, %2, %3}, {%4, %5}, {%6}, {%0, %1, %2, %3};"
        : "+f"(d[0]), "+f"(d[1]), "+f"(d[2]), "+f"(d[3]) : "r"(a0), "r"(a1), "r"(b0));
}
__device__ __forceinline__ uint32_t max_bf16x2(uint32_t a, uint32_t b) { uint32_t r; asm("max.bf16x2 %0, %1, %2;" : "=r"(r) : "r"(a), "r"(b)); return r; }
__device__ __forceinline__ float bf16_round(float x) { return __bfloat162float(__float2bfloat16_rn(x)); }
__device__ __forceinline__ uint32_t lds32(uint32_t addr) { uint32_t v; asm volatile("ld.shared.u32 %0, [%1];" : "=r"(v) : "r"(addr)); return v; }
__device__ __forceinline__ float ex2_approx(float x) { float y; asm("ex2.approx.ftz.f32 %0, %1;" : "=f"(y) : "f"(x)); return y; }
__device__ __forceinline__ float rcp_approx(float x) { float y; asm("rcp.approx.ftz.f32 %0, %1;" : "=f"(y) : "f"(x)); return y; }
__device__ __forceinline__ void st_b128_relaxed(uint4* p, uint32_t w0, uint32_t w1, uint32_t w2, uint32_t w3) {
    asm volatile("{\n.reg .b128 t;\n.reg .b64 lo, hi;\nmov.b64 lo, {%1, %2};\nmov.b64 hi, {%3, %4};\nmov.b128 t, {lo, hi};\nst.relaxed.gpu.global.b128 [%0], t;\n}"
        :: "l"(p), "r"(w0), "r"(w1), "r"(w2), "r"(w3) : "memory");
}
__device__ __forceinline__ uint4 ld_b128_relaxed(const uint4* p) {
    uint4 v;
    asm volatile("{\n.reg .b128 t;\n.reg .b64 lo, hi;\nld.relaxed.gpu.global.b128 t, [%4];\nmov.b128 {lo, hi}, t;\nmov.b64 {%0, %1}, lo;\nmov.b64 {%2, %3}, hi;\n}"
        : "=r"(v.x), "=r"(v.y), "=r"(v.z), "=r"(v.w) : "l"(p) : "memory");
    return v;
}

template<int SA, int TB, int HA = 0x40000040, int M>
__device__ __forceinline__ void wgmma_n8(float (&d)[M], uint32_t da, uint32_t db, int scale_d) {
    asm volatile("{\n.reg .pred p;\n.reg .b32 hi, ha;\n.reg .b64 da, db;\nmov.b32 hi, 0x40000040;\nmov.b32 ha, %9;\nmov.b64 da, {%4, ha};\nmov.b64 db, {%5, hi};\nsetp.ne.b32 p, %6, 0;\n"
        "wgmma.mma_async.sync.aligned.m64n8k16.f32.bf16.bf16 "
        "{%0, %1, %2, %3}, "
        "da, db, p, %8, 1, 0, %7;\n}\n"
        : "+f"(d[0]), "+f"(d[1]), "+f"(d[2]), "+f"(d[3])
        : "r"(da), "r"(db), "r"(scale_d), "n"(TB), "n"(SA), "n"(HA));
}
template<int SA, int TB, int HA = 0x40000040, int M>
__device__ __forceinline__ void wgmma_n96(float (&d)[M], uint32_t da, uint32_t db, int scale_d) {
    asm volatile("{\n.reg .pred p;\n.reg .b32 hi, ha;\n.reg .b64 da, db;\nmov.b32 hi, 0x40000040;\nmov.b32 ha, %53;\nmov.b64 da, {%48, ha};\nmov.b64 db, {%49, hi};\nsetp.ne.b32 p, %50, 0;\n"
        "wgmma.mma_async.sync.aligned.m64n96k16.f32.bf16.bf16 "
        "{%0, %1, %2, %3, %4, %5, %6, %7, %8, %9, %10, %11, %12, %13, %14, %15, "
        "%16, %17, %18, %19, %20, %21, %22, %23, %24, %25, %26, %27, %28, %29, %30, %31, "
        "%32, %33, %34, %35, %36, %37, %38, %39, %40, %41, %42, %43, %44, %45, %46, %47}, "
        "da, db, p, %52, 1, 0, %51;\n}\n"
        : "+f"(d[0]), "+f"(d[1]), "+f"(d[2]), "+f"(d[3]), "+f"(d[4]), "+f"(d[5]), "+f"(d[6]), "+f"(d[7]),
          "+f"(d[8]), "+f"(d[9]), "+f"(d[10]), "+f"(d[11]), "+f"(d[12]), "+f"(d[13]), "+f"(d[14]), "+f"(d[15]),
          "+f"(d[16]), "+f"(d[17]), "+f"(d[18]), "+f"(d[19]), "+f"(d[20]), "+f"(d[21]), "+f"(d[22]), "+f"(d[23]),
          "+f"(d[24]), "+f"(d[25]), "+f"(d[26]), "+f"(d[27]), "+f"(d[28]), "+f"(d[29]), "+f"(d[30]), "+f"(d[31]),
          "+f"(d[32]), "+f"(d[33]), "+f"(d[34]), "+f"(d[35]), "+f"(d[36]), "+f"(d[37]), "+f"(d[38]), "+f"(d[39]),
          "+f"(d[40]), "+f"(d[41]), "+f"(d[42]), "+f"(d[43]), "+f"(d[44]), "+f"(d[45]), "+f"(d[46]), "+f"(d[47])
        : "r"(da), "r"(db), "r"(scale_d), "n"(TB), "n"(SA), "n"(HA));
}
template<int SA, int TB, int HA = 0x40000040, int M>
__device__ __forceinline__ void wgmma_n112(float (&d)[M], uint32_t da, uint32_t db, int scale_d) {
    asm volatile("{\n.reg .pred p;\n.reg .b32 hi, ha;\n.reg .b64 da, db;\nmov.b32 hi, 0x40000040;\nmov.b32 ha, %61;\nmov.b64 da, {%56, ha};\nmov.b64 db, {%57, hi};\nsetp.ne.b32 p, %58, 0;\n"
        "wgmma.mma_async.sync.aligned.m64n112k16.f32.bf16.bf16 "
        "{%0, %1, %2, %3, %4, %5, %6, %7, %8, %9, %10, %11, %12, %13, %14, %15, "
        "%16, %17, %18, %19, %20, %21, %22, %23, %24, %25, %26, %27, %28, %29, %30, %31, "
        "%32, %33, %34, %35, %36, %37, %38, %39, %40, %41, %42, %43, %44, %45, %46, %47, "
        "%48, %49, %50, %51, %52, %53, %54, %55}, "
        "da, db, p, %60, 1, 0, %59;\n}\n"
        : "+f"(d[0]), "+f"(d[1]), "+f"(d[2]), "+f"(d[3]), "+f"(d[4]), "+f"(d[5]), "+f"(d[6]), "+f"(d[7]),
          "+f"(d[8]), "+f"(d[9]), "+f"(d[10]), "+f"(d[11]), "+f"(d[12]), "+f"(d[13]), "+f"(d[14]), "+f"(d[15]),
          "+f"(d[16]), "+f"(d[17]), "+f"(d[18]), "+f"(d[19]), "+f"(d[20]), "+f"(d[21]), "+f"(d[22]), "+f"(d[23]),
          "+f"(d[24]), "+f"(d[25]), "+f"(d[26]), "+f"(d[27]), "+f"(d[28]), "+f"(d[29]), "+f"(d[30]), "+f"(d[31]),
          "+f"(d[32]), "+f"(d[33]), "+f"(d[34]), "+f"(d[35]), "+f"(d[36]), "+f"(d[37]), "+f"(d[38]), "+f"(d[39]),
          "+f"(d[40]), "+f"(d[41]), "+f"(d[42]), "+f"(d[43]), "+f"(d[44]), "+f"(d[45]), "+f"(d[46]), "+f"(d[47]),
          "+f"(d[48]), "+f"(d[49]), "+f"(d[50]), "+f"(d[51]), "+f"(d[52]), "+f"(d[53]), "+f"(d[54]), "+f"(d[55])
        : "r"(da), "r"(db), "r"(scale_d), "n"(TB), "n"(SA), "n"(HA));
}
template<int SA, int TB, int HA = 0x40000040, int M>
__device__ __forceinline__ void wgmma_n128(float (&d)[M], uint32_t da, uint32_t db, int scale_d) {
    asm volatile("{\n.reg .pred p;\n.reg .b32 hi, ha;\n.reg .b64 da, db;\nmov.b32 hi, 0x40000040;\nmov.b32 ha, %69;\nmov.b64 da, {%64, ha};\nmov.b64 db, {%65, hi};\nsetp.ne.b32 p, %66, 0;\n"
        "wgmma.mma_async.sync.aligned.m64n128k16.f32.bf16.bf16 "
        "{%0, %1, %2, %3, %4, %5, %6, %7, %8, %9, %10, %11, %12, %13, %14, %15, "
        "%16, %17, %18, %19, %20, %21, %22, %23, %24, %25, %26, %27, %28, %29, %30, %31, "
        "%32, %33, %34, %35, %36, %37, %38, %39, %40, %41, %42, %43, %44, %45, %46, %47, "
        "%48, %49, %50, %51, %52, %53, %54, %55, %56, %57, %58, %59, %60, %61, %62, %63}, "
        "da, db, p, %68, 1, 0, %67;\n}\n"
        : "+f"(d[0]), "+f"(d[1]), "+f"(d[2]), "+f"(d[3]), "+f"(d[4]), "+f"(d[5]), "+f"(d[6]), "+f"(d[7]),
          "+f"(d[8]), "+f"(d[9]), "+f"(d[10]), "+f"(d[11]), "+f"(d[12]), "+f"(d[13]), "+f"(d[14]), "+f"(d[15]),
          "+f"(d[16]), "+f"(d[17]), "+f"(d[18]), "+f"(d[19]), "+f"(d[20]), "+f"(d[21]), "+f"(d[22]), "+f"(d[23]),
          "+f"(d[24]), "+f"(d[25]), "+f"(d[26]), "+f"(d[27]), "+f"(d[28]), "+f"(d[29]), "+f"(d[30]), "+f"(d[31]),
          "+f"(d[32]), "+f"(d[33]), "+f"(d[34]), "+f"(d[35]), "+f"(d[36]), "+f"(d[37]), "+f"(d[38]), "+f"(d[39]),
          "+f"(d[40]), "+f"(d[41]), "+f"(d[42]), "+f"(d[43]), "+f"(d[44]), "+f"(d[45]), "+f"(d[46]), "+f"(d[47]),
          "+f"(d[48]), "+f"(d[49]), "+f"(d[50]), "+f"(d[51]), "+f"(d[52]), "+f"(d[53]), "+f"(d[54]), "+f"(d[55]),
          "+f"(d[56]), "+f"(d[57]), "+f"(d[58]), "+f"(d[59]), "+f"(d[60]), "+f"(d[61]), "+f"(d[62]), "+f"(d[63])
        : "r"(da), "r"(db), "r"(scale_d), "n"(TB), "n"(SA), "n"(HA));
}
template<int SA, int TB, int HA = 0x40000040, int M>
__device__ __forceinline__ void wgmma_n224(float (&d)[M], uint32_t da, uint32_t db, int scale_d) {
    asm volatile("{\n.reg .pred p;\n.reg .b32 hi, ha;\n.reg .b64 da, db;\nmov.b32 hi, 0x40000040;\nmov.b32 ha, %117;\nmov.b64 da, {%112, ha};\nmov.b64 db, {%113, hi};\nsetp.ne.b32 p, %114, 0;\n"
        "wgmma.mma_async.sync.aligned.m64n224k16.f32.bf16.bf16 "
        "{%0, %1, %2, %3, %4, %5, %6, %7, %8, %9, %10, %11, %12, %13, %14, %15, "
        "%16, %17, %18, %19, %20, %21, %22, %23, %24, %25, %26, %27, %28, %29, %30, %31, "
        "%32, %33, %34, %35, %36, %37, %38, %39, %40, %41, %42, %43, %44, %45, %46, %47, "
        "%48, %49, %50, %51, %52, %53, %54, %55, %56, %57, %58, %59, %60, %61, %62, %63, "
        "%64, %65, %66, %67, %68, %69, %70, %71, %72, %73, %74, %75, %76, %77, %78, %79, "
        "%80, %81, %82, %83, %84, %85, %86, %87, %88, %89, %90, %91, %92, %93, %94, %95, "
        "%96, %97, %98, %99, %100, %101, %102, %103, %104, %105, %106, %107, %108, %109, %110, %111}, "
        "da, db, p, %116, 1, 0, %115;\n}\n"
        : "+f"(d[0]), "+f"(d[1]), "+f"(d[2]), "+f"(d[3]), "+f"(d[4]), "+f"(d[5]), "+f"(d[6]), "+f"(d[7]),
          "+f"(d[8]), "+f"(d[9]), "+f"(d[10]), "+f"(d[11]), "+f"(d[12]), "+f"(d[13]), "+f"(d[14]), "+f"(d[15]),
          "+f"(d[16]), "+f"(d[17]), "+f"(d[18]), "+f"(d[19]), "+f"(d[20]), "+f"(d[21]), "+f"(d[22]), "+f"(d[23]),
          "+f"(d[24]), "+f"(d[25]), "+f"(d[26]), "+f"(d[27]), "+f"(d[28]), "+f"(d[29]), "+f"(d[30]), "+f"(d[31]),
          "+f"(d[32]), "+f"(d[33]), "+f"(d[34]), "+f"(d[35]), "+f"(d[36]), "+f"(d[37]), "+f"(d[38]), "+f"(d[39]),
          "+f"(d[40]), "+f"(d[41]), "+f"(d[42]), "+f"(d[43]), "+f"(d[44]), "+f"(d[45]), "+f"(d[46]), "+f"(d[47]),
          "+f"(d[48]), "+f"(d[49]), "+f"(d[50]), "+f"(d[51]), "+f"(d[52]), "+f"(d[53]), "+f"(d[54]), "+f"(d[55]),
          "+f"(d[56]), "+f"(d[57]), "+f"(d[58]), "+f"(d[59]), "+f"(d[60]), "+f"(d[61]), "+f"(d[62]), "+f"(d[63]),
          "+f"(d[64]), "+f"(d[65]), "+f"(d[66]), "+f"(d[67]), "+f"(d[68]), "+f"(d[69]), "+f"(d[70]), "+f"(d[71]),
          "+f"(d[72]), "+f"(d[73]), "+f"(d[74]), "+f"(d[75]), "+f"(d[76]), "+f"(d[77]), "+f"(d[78]), "+f"(d[79]),
          "+f"(d[80]), "+f"(d[81]), "+f"(d[82]), "+f"(d[83]), "+f"(d[84]), "+f"(d[85]), "+f"(d[86]), "+f"(d[87]),
          "+f"(d[88]), "+f"(d[89]), "+f"(d[90]), "+f"(d[91]), "+f"(d[92]), "+f"(d[93]), "+f"(d[94]), "+f"(d[95]),
          "+f"(d[96]), "+f"(d[97]), "+f"(d[98]), "+f"(d[99]), "+f"(d[100]), "+f"(d[101]), "+f"(d[102]), "+f"(d[103]),
          "+f"(d[104]), "+f"(d[105]), "+f"(d[106]), "+f"(d[107]), "+f"(d[108]), "+f"(d[109]), "+f"(d[110]), "+f"(d[111])
        : "r"(da), "r"(db), "r"(scale_d), "n"(TB), "n"(SA), "n"(HA));
}
template<int TB, int SA = 1>
__device__ __forceinline__ void wgmma_rs_n32(float (&d)[16], const uint32_t (&a)[4], uint32_t db, int scale_d) {
    asm volatile("{\n.reg .pred p;\n.reg .b32 hi;\n.reg .b64 db;\nmov.b32 hi, 0x40000040;\nmov.b64 db, {%20, hi};\nsetp.ne.b32 p, %21, 0;\n"
        "wgmma.mma_async.sync.aligned.m64n32k16.f32.bf16.bf16 "
        "{%0, %1, %2, %3, %4, %5, %6, %7, %8, %9, %10, %11, %12, %13, %14, %15}, "
        "{%16, %17, %18, %19}, db, p, %23, 1, %22;\n}\n"
        : "+f"(d[0]), "+f"(d[1]), "+f"(d[2]), "+f"(d[3]), "+f"(d[4]), "+f"(d[5]), "+f"(d[6]), "+f"(d[7]),
          "+f"(d[8]), "+f"(d[9]), "+f"(d[10]), "+f"(d[11]), "+f"(d[12]), "+f"(d[13]), "+f"(d[14]), "+f"(d[15])
        : "r"(a[0]), "r"(a[1]), "r"(a[2]), "r"(a[3]), "r"(db), "r"(scale_d), "n"(TB), "n"(SA));
}
template<int TB, int SA = 1>
__device__ __forceinline__ void wgmma_rs_n56(float (&d)[28], const uint32_t (&a)[4], uint32_t db, int scale_d) {
    asm volatile("{\n.reg .pred p;\n.reg .b32 hi;\n.reg .b64 db;\nmov.b32 hi, 0x40000040;\nmov.b64 db, {%32, hi};\nsetp.ne.b32 p, %33, 0;\n"
        "wgmma.mma_async.sync.aligned.m64n56k16.f32.bf16.bf16 "
        "{%0, %1, %2, %3, %4, %5, %6, %7, %8, %9, %10, %11, %12, %13, %14, %15, "
        "%16, %17, %18, %19, %20, %21, %22, %23, %24, %25, %26, %27}, "
        "{%28, %29, %30, %31}, db, p, %35, 1, %34;\n}\n"
        : "+f"(d[0]), "+f"(d[1]), "+f"(d[2]), "+f"(d[3]), "+f"(d[4]), "+f"(d[5]), "+f"(d[6]), "+f"(d[7]),
          "+f"(d[8]), "+f"(d[9]), "+f"(d[10]), "+f"(d[11]), "+f"(d[12]), "+f"(d[13]), "+f"(d[14]), "+f"(d[15]),
          "+f"(d[16]), "+f"(d[17]), "+f"(d[18]), "+f"(d[19]), "+f"(d[20]), "+f"(d[21]), "+f"(d[22]), "+f"(d[23]),
          "+f"(d[24]), "+f"(d[25]), "+f"(d[26]), "+f"(d[27])
        : "r"(a[0]), "r"(a[1]), "r"(a[2]), "r"(a[3]), "r"(db), "r"(scale_d), "n"(TB), "n"(SA));
}
template<int TB, int SA = 1>
__device__ __forceinline__ void wgmma_rs_n64(float (&d)[32], const uint32_t (&a)[4], uint32_t db, int scale_d) {
    asm volatile("{\n.reg .pred p;\n.reg .b32 hi;\n.reg .b64 db;\nmov.b32 hi, 0x40000040;\nmov.b64 db, {%36, hi};\nsetp.ne.b32 p, %37, 0;\n"
        "wgmma.mma_async.sync.aligned.m64n64k16.f32.bf16.bf16 "
        "{%0, %1, %2, %3, %4, %5, %6, %7, %8, %9, %10, %11, %12, %13, %14, %15, "
        "%16, %17, %18, %19, %20, %21, %22, %23, %24, %25, %26, %27, %28, %29, %30, %31}, "
        "{%32, %33, %34, %35}, db, p, %39, 1, %38;\n}\n"
        : "+f"(d[0]), "+f"(d[1]), "+f"(d[2]), "+f"(d[3]), "+f"(d[4]), "+f"(d[5]), "+f"(d[6]), "+f"(d[7]),
          "+f"(d[8]), "+f"(d[9]), "+f"(d[10]), "+f"(d[11]), "+f"(d[12]), "+f"(d[13]), "+f"(d[14]), "+f"(d[15]),
          "+f"(d[16]), "+f"(d[17]), "+f"(d[18]), "+f"(d[19]), "+f"(d[20]), "+f"(d[21]), "+f"(d[22]), "+f"(d[23]),
          "+f"(d[24]), "+f"(d[25]), "+f"(d[26]), "+f"(d[27]), "+f"(d[28]), "+f"(d[29]), "+f"(d[30]), "+f"(d[31])
        : "r"(a[0]), "r"(a[1]), "r"(a[2]), "r"(a[3]), "r"(db), "r"(scale_d), "n"(TB), "n"(SA));
}
template<int TB, int SA = 1>
__device__ __forceinline__ void wgmma_rs_n96(float (&d)[48], const uint32_t (&a)[4], uint32_t db, int scale_d) {
    asm volatile("{\n.reg .pred p;\n.reg .b32 hi;\n.reg .b64 db;\nmov.b32 hi, 0x40000040;\nmov.b64 db, {%52, hi};\nsetp.ne.b32 p, %53, 0;\n"
        "wgmma.mma_async.sync.aligned.m64n96k16.f32.bf16.bf16 "
        "{%0, %1, %2, %3, %4, %5, %6, %7, %8, %9, %10, %11, %12, %13, %14, %15, "
        "%16, %17, %18, %19, %20, %21, %22, %23, %24, %25, %26, %27, %28, %29, %30, %31, "
        "%32, %33, %34, %35, %36, %37, %38, %39, %40, %41, %42, %43, %44, %45, %46, %47}, "
        "{%48, %49, %50, %51}, db, p, %55, 1, %54;\n}\n"
        : "+f"(d[0]), "+f"(d[1]), "+f"(d[2]), "+f"(d[3]), "+f"(d[4]), "+f"(d[5]), "+f"(d[6]), "+f"(d[7]),
          "+f"(d[8]), "+f"(d[9]), "+f"(d[10]), "+f"(d[11]), "+f"(d[12]), "+f"(d[13]), "+f"(d[14]), "+f"(d[15]),
          "+f"(d[16]), "+f"(d[17]), "+f"(d[18]), "+f"(d[19]), "+f"(d[20]), "+f"(d[21]), "+f"(d[22]), "+f"(d[23]),
          "+f"(d[24]), "+f"(d[25]), "+f"(d[26]), "+f"(d[27]), "+f"(d[28]), "+f"(d[29]), "+f"(d[30]), "+f"(d[31]),
          "+f"(d[32]), "+f"(d[33]), "+f"(d[34]), "+f"(d[35]), "+f"(d[36]), "+f"(d[37]), "+f"(d[38]), "+f"(d[39]),
          "+f"(d[40]), "+f"(d[41]), "+f"(d[42]), "+f"(d[43]), "+f"(d[44]), "+f"(d[45]), "+f"(d[46]), "+f"(d[47])
        : "r"(a[0]), "r"(a[1]), "r"(a[2]), "r"(a[3]), "r"(db), "r"(scale_d), "n"(TB), "n"(SA));
}
template<int TB, int SA = 1>
__device__ __forceinline__ void wgmma_rs_n112(float (&d)[56], const uint32_t (&a)[4], uint32_t db, int scale_d) {
    asm volatile("{\n.reg .pred p;\n.reg .b32 hi;\n.reg .b64 db;\nmov.b32 hi, 0x40000040;\nmov.b64 db, {%60, hi};\nsetp.ne.b32 p, %61, 0;\n"
        "wgmma.mma_async.sync.aligned.m64n112k16.f32.bf16.bf16 "
        "{%0, %1, %2, %3, %4, %5, %6, %7, %8, %9, %10, %11, %12, %13, %14, %15, "
        "%16, %17, %18, %19, %20, %21, %22, %23, %24, %25, %26, %27, %28, %29, %30, %31, "
        "%32, %33, %34, %35, %36, %37, %38, %39, %40, %41, %42, %43, %44, %45, %46, %47, "
        "%48, %49, %50, %51, %52, %53, %54, %55}, "
        "{%56, %57, %58, %59}, db, p, %63, 1, %62;\n}\n"
        : "+f"(d[0]), "+f"(d[1]), "+f"(d[2]), "+f"(d[3]), "+f"(d[4]), "+f"(d[5]), "+f"(d[6]), "+f"(d[7]),
          "+f"(d[8]), "+f"(d[9]), "+f"(d[10]), "+f"(d[11]), "+f"(d[12]), "+f"(d[13]), "+f"(d[14]), "+f"(d[15]),
          "+f"(d[16]), "+f"(d[17]), "+f"(d[18]), "+f"(d[19]), "+f"(d[20]), "+f"(d[21]), "+f"(d[22]), "+f"(d[23]),
          "+f"(d[24]), "+f"(d[25]), "+f"(d[26]), "+f"(d[27]), "+f"(d[28]), "+f"(d[29]), "+f"(d[30]), "+f"(d[31]),
          "+f"(d[32]), "+f"(d[33]), "+f"(d[34]), "+f"(d[35]), "+f"(d[36]), "+f"(d[37]), "+f"(d[38]), "+f"(d[39]),
          "+f"(d[40]), "+f"(d[41]), "+f"(d[42]), "+f"(d[43]), "+f"(d[44]), "+f"(d[45]), "+f"(d[46]), "+f"(d[47]),
          "+f"(d[48]), "+f"(d[49]), "+f"(d[50]), "+f"(d[51]), "+f"(d[52]), "+f"(d[53]), "+f"(d[54]), "+f"(d[55])
        : "r"(a[0]), "r"(a[1]), "r"(a[2]), "r"(a[3]), "r"(db), "r"(scale_d), "n"(TB), "n"(SA));
}
template<int TB, int SA = 1>
__device__ __forceinline__ void wgmma_rs_n224(float (&d)[112], const uint32_t (&a)[4], uint32_t db, int scale_d) {
    asm volatile("{\n.reg .pred p;\n.reg .b32 hi;\n.reg .b64 db;\nmov.b32 hi, 0x40000040;\nmov.b64 db, {%116, hi};\nsetp.ne.b32 p, %117, 0;\n"
        "wgmma.mma_async.sync.aligned.m64n224k16.f32.bf16.bf16 "
        "{%0, %1, %2, %3, %4, %5, %6, %7, %8, %9, %10, %11, %12, %13, %14, %15, "
        "%16, %17, %18, %19, %20, %21, %22, %23, %24, %25, %26, %27, %28, %29, %30, %31, "
        "%32, %33, %34, %35, %36, %37, %38, %39, %40, %41, %42, %43, %44, %45, %46, %47, "
        "%48, %49, %50, %51, %52, %53, %54, %55, %56, %57, %58, %59, %60, %61, %62, %63, "
        "%64, %65, %66, %67, %68, %69, %70, %71, %72, %73, %74, %75, %76, %77, %78, %79, "
        "%80, %81, %82, %83, %84, %85, %86, %87, %88, %89, %90, %91, %92, %93, %94, %95, "
        "%96, %97, %98, %99, %100, %101, %102, %103, %104, %105, %106, %107, %108, %109, %110, %111}, "
        "{%112, %113, %114, %115}, db, p, %119, 1, %118;\n}\n"
        : "+f"(d[0]), "+f"(d[1]), "+f"(d[2]), "+f"(d[3]), "+f"(d[4]), "+f"(d[5]), "+f"(d[6]), "+f"(d[7]),
          "+f"(d[8]), "+f"(d[9]), "+f"(d[10]), "+f"(d[11]), "+f"(d[12]), "+f"(d[13]), "+f"(d[14]), "+f"(d[15]),
          "+f"(d[16]), "+f"(d[17]), "+f"(d[18]), "+f"(d[19]), "+f"(d[20]), "+f"(d[21]), "+f"(d[22]), "+f"(d[23]),
          "+f"(d[24]), "+f"(d[25]), "+f"(d[26]), "+f"(d[27]), "+f"(d[28]), "+f"(d[29]), "+f"(d[30]), "+f"(d[31]),
          "+f"(d[32]), "+f"(d[33]), "+f"(d[34]), "+f"(d[35]), "+f"(d[36]), "+f"(d[37]), "+f"(d[38]), "+f"(d[39]),
          "+f"(d[40]), "+f"(d[41]), "+f"(d[42]), "+f"(d[43]), "+f"(d[44]), "+f"(d[45]), "+f"(d[46]), "+f"(d[47]),
          "+f"(d[48]), "+f"(d[49]), "+f"(d[50]), "+f"(d[51]), "+f"(d[52]), "+f"(d[53]), "+f"(d[54]), "+f"(d[55]),
          "+f"(d[56]), "+f"(d[57]), "+f"(d[58]), "+f"(d[59]), "+f"(d[60]), "+f"(d[61]), "+f"(d[62]), "+f"(d[63]),
          "+f"(d[64]), "+f"(d[65]), "+f"(d[66]), "+f"(d[67]), "+f"(d[68]), "+f"(d[69]), "+f"(d[70]), "+f"(d[71]),
          "+f"(d[72]), "+f"(d[73]), "+f"(d[74]), "+f"(d[75]), "+f"(d[76]), "+f"(d[77]), "+f"(d[78]), "+f"(d[79]),
          "+f"(d[80]), "+f"(d[81]), "+f"(d[82]), "+f"(d[83]), "+f"(d[84]), "+f"(d[85]), "+f"(d[86]), "+f"(d[87]),
          "+f"(d[88]), "+f"(d[89]), "+f"(d[90]), "+f"(d[91]), "+f"(d[92]), "+f"(d[93]), "+f"(d[94]), "+f"(d[95]),
          "+f"(d[96]), "+f"(d[97]), "+f"(d[98]), "+f"(d[99]), "+f"(d[100]), "+f"(d[101]), "+f"(d[102]), "+f"(d[103]),
          "+f"(d[104]), "+f"(d[105]), "+f"(d[106]), "+f"(d[107]), "+f"(d[108]), "+f"(d[109]), "+f"(d[110]), "+f"(d[111])
        : "r"(a[0]), "r"(a[1]), "r"(a[2]), "r"(a[3]), "r"(db), "r"(scale_d), "n"(TB), "n"(SA));
}

#define TR(idx) do {} while (0)
#define TRL(idx) do {} while (0)
#define TRX(idx) do {} while (0)
#define TRG(idx) do {} while (0)
#define TR_END() do {} while (0)

template<int V> struct Int { static constexpr int value = V; };
constexpr float ATT_SCALE = 0.18898223650461361f;
constexpr float LOG2E = 1.4426950408889634f;
constexpr uint32_t MASKED = 0xce6ece6eu;

__global__ void __cluster_dims__(2, 1, 1) __launch_bounds__(384, 1)
fused_kernel(__nv_bfloat16* __restrict__ out,
    const __grid_constant__ TMaps tm) {
    extern __shared__ __align__(1024) uint8_t smem_raw[];
    const uint32_t sb = smem_u32(smem_raw);
    const uint32_t bars = sb + BAR_OFF;
    const uint32_t bar_full = bars, bar_empty = bars + 32, bar_abf = bars + 64  , bar_ab = bars + 128  , bar_free = bars + 296  , bar_halo = bars + 152;
    const uint32_t bar_o = bars + 160, bar_qkv = bars + 176  , bar_sf = bars + 200, bar_se = bar_sf + 32  ;
    const uint32_t bar_fl = bars + 256  , bar_go = bars + 240  , bar_end = bars + 192, bar_af = bars + 312;
    const uint32_t stg = sb + STG_OFF;
    const int cta = blockIdx.x, r = cta & 1, cl = cta >> 1;
    const int place = pick3(cta, 32 + 8 * cl, cl - 4, cl - 3 + ((cl * 37 - 36 * 37) >> 8));
    const int mt = (place & 7) * 2 + r;
    const int sub = place >> 3;
    const CUtensorMap* tmWd = sub < 4 ? &tm.wdre : &tm.wdim;
    uint32_t t_first = 0;
    if (threadIdx.x < 32 + (((uint32_t)(uintptr_t)tmWd | sb | (mt << 6)) & 32) && elect_one()) {
        prefetch_tmap(tmWd); prefetch_tmap(&tm.xB);
        #pragma unroll
        for (int kb = 0; kb < START_N; kb++) {
            mbar_init(bar_abf + 8 * kb, 1);
            mbar_expect_tx(bar_abf + 8 * kb, AB_BYTES);
            tma_load(sb + kb * AB_BYTES + SLOT_A, tmWd, bar_abf + 8 * kb, kb * 64, (sub & 3) * 112);
            tma_load(sb + kb * AB_BYTES, &tm.xB, bar_abf + 8 * kb, kb * 64, mt * 128);
        }
        t_first = clk32();
    }
    const int tid = threadIdx.x, warp = __shfl_sync(0xffffffffu, tid >> 5, 0), lane = tid & 31;
    const bool late = sub < 4;
    const int nh = sub & 1, part = (sub >> 1) & 1;
    const int nj = late ? 32 - KB_EARLY : KB_EARLY;
    static_assert(KB_EARLY == 14, "order of the k-blocks");
    const uint32_t t0 = clk32();
    auto clear_out = [&]() {
        while ((int)(clk32() - t0) < TP(ZERO_AT)) { }
        uint4* zp = reinterpret_cast<uint4*>(out + (size_t)(mt * 128 + sub * 16 + (warp - 2) * 8) * NOUT + DM) + lane;
        #pragma unroll 1
        for (int j = 0; j < (ABL & 8 ? 0 : 8); j++) {
            while ((int)(clk32() - t0) < TP(ZERO_AT) + j * TP(ZERO_GAP)) { }
            zp[j * (NOUT / 8)] = make_uint4(0, 0, 0, 0);
            if (lane < 24) zp[j * (NOUT / 8) + 32] = make_uint4(0, 0, 0, 0);
        }
    };
    if (warp == 0) {
        if (elect_one()) {
            #pragma unroll
            for (int s = START_N; s < 7; s++) mbar_init(bar_abf + 8 * s, 1);
            #pragma unroll
            for (int s = 0; s < NSLOT; s++) { mbar_init(bar_full + 8 * s, 1); mbar_init(bar_empty + 8 * s, 4); }
            asm volatile("fence.mbarrier_init.release.cluster;" ::: "memory");
        }
        __syncwarp();
        cluster_arrive();
        if (elect_one()) {
            #pragma unroll 1
            for (int kb = START_N; kb < 7; kb++) {
                while ((int)(clk32() - t_first) < TP(START_GAP1) + (kb - START_N) * TP(START_GAP)) { }
                const uint32_t a = sb + kb * AB_BYTES, fb = bar_abf + 8 * kb;
                mbar_expect_tx(fb, AB_BYTES);
                tma_load(a, &tm.xB, fb, kb * 64, mt * 128);
                tma_load(a + SLOT_A, tmWd, fb, kb * 64, (sub & 3) * 112);
            }
            TR(2);
            prefetch_tmap(&tm.xA3); prefetch_tmap(&tm.wqkv3);
        }
        __syncwarp();
    } else if (warp < 4) {
        cluster_arrive();
        if (warp >= 2) clear_out();
    }
    if (warp < 4) {
      reg_set<REG_AUX>();
      const CUtensorMap* tmB = r ? &tm.abP3 : &tm.abP4;
      const uint32_t boff = SLOT_A + r * 16384;
      const int bgrp = part * 14 + nh * 7 + r * 4;
      if (warp == 0) {
        cluster_wait();
        if (elect_one()) {
        uint32_t slot = sb, fb = bar_full, par = 0;
        auto advance = [&]() { if (fb == bar_full + 24) { fb = bar_full; slot = sb; par ^= 1; } else { fb += 8; slot += SLOT_BYTES; } };
        const uint64_t pol = policy_evict_first();
        const CUtensorMap* tmW = part ? &tm.wim : &tm.wre;
        const CUtensorMap* tmH = part ? &tm.wimH : &tm.wreH;
        const int qc = sub * 56 - (sub & 1) * 8;
        auto next_kc = [&](int kc, int wi) { return wi == 3 ? (late ? 14 * 64 : 2 * 64) : wi == nj / 2 - 1 ? (late ? 15 * 64 : 64) : kc + (FLIP && wi == 1 ? -768 : wi < nj / 2 ? 256 : 128); };
        #pragma unroll 1
        for (int it = 0; it < 7; it++) {
            mbar_wait_p(fb + 32, par);
            mbar_expect_tx(fb, SLOT_A + 3 * 8192);
            tma_load3(slot, &tm.xA3, fb, it * 64, mt * 64);
            tma_load3_mc(slot + SLOT_A + r * 12288, &tm.wqkv3, fb, qc, it * 64 + r * 32, 0);
            TRL(64 + it);
            if (r && it == 2) {
                const int c = (7 - sub) * 8 + (mt >> 1), c7 = (c * 37) >> 8;
                tma_prefetch3(&tm.xA3, (3 + (sub >> 1)) * 64, (mt - (sub & 1)) * 64);
                if (c7 < 8) tma_prefetch3(&tm.wqkv3, (c - 7 * c7) * 64, 192 + c7 * 32);
            }
            if (it == 1) { prefetch_tmap(tmW); prefetch_tmap(tmB); prefetch_tmap(tmH); }
            advance();
        }
        int kc = (late ? 1024 : 0) + 512 * FLIP;
        #pragma unroll 1
        for (int wi = 0; wi < nj - late; wi++) {
            mbar_wait_p(fb + 32, par);
            if (TP(W_GAP) && wi > 0 && wi < 4) { const uint32_t t1 = clk32() + TP(W_GAP); while ((int)(clk32() - t1) < 0) { } }
            mbar_expect_tx(fb, SLOT_BYTES);
            tma_load_hint(slot, tmW, fb, kc, mt * 128, pol);
            TR(224 + 7 + wi);
            if (wi >= 4) {
                if (wi == 4 || wi == nj / 2) mbar_wait(bar_fl + (wi == 4 ? 16 : 24), 0);
                tma_load5_mc(slot + boff, tmB, fb, kc, bgrp);
                TR(64 + 7 + wi);
            } else mbar_arrive(bar_go + 8 * wi);
            advance();
            kc = next_kc(kc, wi);
            if (wi == (late ? TP(PF_L) : TP(PF_E))) tma_prefetch(tmH, (late ? 29 : 13) * 64, mt * 128 + nh * 64);
            if (late) {
                if (wi == TP(L_XAT) - 1) {
                    mbar_wait(bar_se, 0);
                    mbar_expect_tx(bar_sf, SLOT_BYTES);
                    tma_load5_mc(stg + boff, tmB, bar_sf, 31 * 64, bgrp);
                }
                if (wi == TP(L_XAT)) tma_load_hint(stg, tmW, bar_sf, 31 * 64, mt * 128, pol);
            } else if (wi == TP(WB_AT)) {
                mbar_wait(bar_se, 0);
                #pragma unroll
                for (int j = 1; j < 7; j += 2) tma_load_mc(sb + OUT_B(j) + r * 8192, &tm.wo64, bar_abf, 256 + 48 * (sub & 3), (j + r) * 64);
            } else if (wi == TP(WO_AT) - 1) {
                const int c = mt * 4 + (sub & 3), c7 = (c * 37) >> 8;
                if (c < 49) tma_prefetch(&tm.wo64, (c - 7 * c7) * 64, c7 * 64); else prefetch_tmap(&tm.wo64);
            }
        }
        if (!late) {
            const uint4* const po = g_o + mt * 7168;
            const int ca = 64 * (sub & 3), cb = 256 + 48 * (sub & 3);
            auto load_w = [&](int d0, int c0, int j0, int d1, int c1, int j1, int g) { tma_load_mc(sb + (r ? d1 : d0), &tm.wo64, bar_abf + 8 * g, r ? c1 : c0, (r ? j1 : j0) * 64); };
            auto load_o = [&](int p, int j, int n, int g) { bulk_load(sb + OUT_O(p, j), po + p * 3584 + j * 512, n * 8192, bar_abf + 8 * g); };
            #pragma unroll
            for (int g = 0; g < 5; g++) mbar_expect_tx(bar_abf + 8 * g, (g == 0 ? 11 : g == 2 ? 5 : 4) * 8192);
            mbar_wait_p(bar_empty + 8, 1);
            load_w(OUT_A(0), ca, 0, OUT_A(1), ca, 1, 0);
            if (r == 0) load_w(OUT_B(0), cb, 0, 0, 0, 0, 0);
            TR(64 + 7 + KB_EARLY);
            mbar_wait_p(bar_fl + 32, 0);
            TR(3);
            load_o(0, 0, 2, 0);
            mbar_wait_p(bar_af, 0);
            load_w(OUT_A(2), ca, 2, OUT_A(3), ca, 3, 1); load_o(0, 2, 2, 1);
            if (r) load_w(0, 0, 0, OUT_A(4), ca, 4, 2);
            TR(64 + 7 + KB_EARLY + 1);
            mbar_wait_p(bar_empty + 16, 1);
            load_o(0, 4, 2, 2); load_w(OUT_A(5), ca, 5, OUT_A(6), ca, 6, 2);
            TR(64 + 7 + KB_EARLY + 2);
            mbar_wait_p(bar_empty + 24, 1);
            load_o(0, 6, 4, 3);
            TR(64 + 7 + KB_EARLY + 3);
            mbar_wait_p(bar_empty, 0);
            load_o(1, 3, 4, 4);
            TR(64 + 7 + KB_EARLY + 4);
        }
        mbar_arrive(bar_end);
        }
      } else {
        const unsigned epoch = ld_relaxed(&g_epoch[cta * 8]) + 1;
        cluster_wait();
        auto forward = [&](const unsigned* fl, unsigned target, auto first, uint32_t bar, uint32_t again) {
            for (int spin = 0; !__all_sync(0xffffffffu, (int)(ld_acquire(fl) - target) >= 0);) {
                if ((int)(clk32() - again) < 0) { while ((int)(clk32() - again) < 0) { } } else __nanosleep(target != epoch ? TP(OPOLL_NS) : TP(POLL_NS));
                if (++spin > SPIN_LIMIT) give_up();
            }
            if (elect_one()) {
                fence_async_global();
                if constexpr (decltype(first)::value == 2) { if (atomicExch(reinterpret_cast<unsigned*>(smem_raw + BAR_OFF + 144), 1u) == 0) mbar_arrive(bar); }
                else if constexpr (!decltype(first)::value) mbar_arrive(bar);
                else {
                    #pragma unroll
                    for (int i = 0; i < 2; i++) {
                        const int wi = 2 * (warp - 2) + i, sl = (wi + 3) & 3;
                        mbar_wait_limit(bar_go + 8 * wi, 0);
                        tma_load5_mc(sb + sl * SLOT_BYTES + boff, tmB, bar_full + 8 * sl, (late ? 1024 : 0) + 256 * (wi ^ 2 * FLIP), bgrp);
                        TR(64 + 7 + wi);
                        if (i == 0) { const uint32_t t1 = clk32() + TP(BIG_GAP); while ((int)(clk32() - t1) < 0) { } }
                    }
                }
            }
            __syncwarp();
        };
        const int frow = part * 4 + nh * 2 + (lane & 1), st0 = late ? 8 : 0;
        const int ft = late ? min(7 + (lane >> 1), 15) : min(lane >> 1, 6);
        const unsigned* const fl2 = &g_flag_ab[(32 + frow) * 32 + (late ? min(7 + (lane & 14), 15) : min(1 + (lane & 14), 5))];
        const unsigned* const fl3 = &g_flag_ab[(16 + 8 * (ft & 1) + frow) * 32 + ft];
        if (warp == 1) {
            if (elect_one()) {
                prefetch_tmap(&tm.abH); if (BIG_ST) { prefetch_tmap(&tm.ab80); prefetch_tmap(&tm.ab32); }
                const int e0 = pin(sub * 112 - (sub & 2) * 16), e1 = pin((sub & 3) == 2 ? 224 : 0);
                #pragma unroll 1
                for (int hf = 0; hf < 2; hf++) {
                    const int gap = pin(hf ? (r ? TP(ABS_GAP3) : TP(ABS_GAP2)) : (r ? TP(ABS_GAP) : 0)), sc = pin(mt * 128 + hf * 64);
                    const uint32_t src = pin(hf ? stg : sb + 7 * AB_BYTES);
                    unsigned* const fl = pin(&g_flag_ab[((hf ? 2 + r : r ? 4 : URG(mt)) * 8 + sub) * 32 + mt]);
                    mbar_wait(bar_ab + 8 * hf, 0);
                    fence_async_smem();
                    uint32_t t1 = clk32() + (hf ? 0 : r ? TP(ABS_AT) : URG(mt) * TP(ABS_AT1));
                    if (BIG_ST && (hf | r) == 0) {
                        if (URG(mt)) { while ((int)(clk32() - t1) < 0) { } }
                        TR(4);
                        tma_store(&tm.ab80, src + 4096, sc, e0 + 32);
                        tma_store(&tm.ab32, src, sc, e0 + e1);
                    } else
                    #pragma unroll
                    for (int i = 0; i < 7; i++) {
                        if (i == 0 || gap) { while ((int)(clk32() - t1) < 0) { } }
                        t1 += gap;
                        if (i == 0 && hf == 0) TR(4);
                        if (hf > r && i % 3 == 0 && i / 3 < TP(PF_N)) tma_prefetch(part ? &tm.wim : &tm.wre, (late ? 1024 : 0) + ((i / 3) ^ 2 * FLIP) * 256, (mt + nh) * 128);
                        tma_store(&tm.abH, src + i * 2048, sc, e0 + i * 16 + (i < 2 ? e1 : 0));
                    }
                    bulk_commit();
                    bulk_wait_all();
                    if (hf) TR(5);
                    mbar_arrive(bar_free + 8 * hf);
                    st_release(fl, epoch);
                    TR(hf ? 6 : 38);
                }
                uint4* const po = pin(g_o + mt * 7168 + sub * 448);
                mbar_wait(bar_o, 0);
                fence_async_smem();
                TR(9);
                {
                    uint32_t t2 = clk32();
                    #pragma unroll 1
                    for (int i = 0; i < 2 * O_N; i++) {
                        while ((int)(clk32() - t2) < 0) { }
                        t2 += TP(O_GAP);
                        bulk_store(po + (i >= O_N ? 3584 - 448 : 0) + i * (448 / O_N), stg + i * (7168 / O_N), 7168 / O_N);
                    }
                }
                bulk_commit();
                TR(62);
                bulk_wait_all();
                TR(111);
                mbar_arrive(bar_se); mbar_arrive_remote(bar_se, r ^ 1);
                red_release(&g_flag_o[mt * 32], 1);
                TR(17); TRG(102);
                if (!late) {
                    prefetch_tmap(&tm.outA); prefetch_tmap(&tm.outB);
                    #pragma unroll
                    for (int c = 0; c < 2; c++) {
                        mbar_wait(bar_qkv + 8 * c, 1);
                        fence_async_smem();
                        tma_store3(c ? &tm.outB : &tm.outA, sb + OUT_ST + c * 8192, mt * 64, sub & 3);
                    }
                    bulk_commit();
                    asm volatile("cp.async.bulk.wait_group.read 0;" ::: "memory");
                    TR(19);
                }
            }
            __syncwarp();
        } else {
            asm volatile("st.shared.u32 [%0], %1;" :: "r"(bars + 168), "r"(epoch) : "memory");
            if (OPOLL2_ON) asm volatile("st.shared.u32 [%0], %1;" :: "r"(bars + 144), "r"(0) : "memory");
            __syncwarp();
            if (lane == 0) mbar_arrive(bar_ab + 8);
            mbar_wait_limit(bar_ab, 0);
            const uint32_t ta = clk32();
            if (tid == 96) TRG(98);
            const bool rest = warp == 3 && __all_sync(0xffffffffu, (int)(ld_acquire(lane >= 22 ? fl2 : fl3) - epoch) >= 0);
            forward(&g_flag_ab[((warp - 2) * 8 + frow) * 32 + st0 + 4 * ((warp - 2) ^ FLIP) + (lane & 2)], epoch, Int<1>(), 0, ta + (warp == 2 ? TP(POLL_AT) : TP(POLL_AT1)));
            if (warp == 2) {
                const uint4* const hp = pin(g_halo + (max(mt - 1, 0) * 8 + sub) * 320 + lane);
                const uint32_t ha = pin(stg + KV_OFF + (lane & 7) * KV_PITCH + (lane >> 3) * 16);
                mbar_wait(mt > 0 ? bar_go + 24 : bar_qkv, 0);
                uint4 v[10];
                if (mt > 0) {
                    const uint32_t tq = clk32();
                    while ((int)(clk32() - tq) < TP(HALO_WAIT)) { }
                    #pragma unroll 1
                    for (;;) {
                        uint32_t bad = 0;
                        #pragma unroll
                        for (int j = 0; j < 10; j++) v[j] = ld_b128_relaxed(hp + j * 32);
                        #pragma unroll
                        for (int j = 0; j < 10; j++) bad |= v[j].w ^ epoch;
                        if (__all_sync(0xffffffffu, bad == 0) || (ABL & 1)) break;
                        __nanosleep(200);
                    }
                } else {
                    const uint32_t r0 = stg + KV_OFF + 8 * KV_PITCH + 112 + (lane & 3) * 4;
                    v[0].x = v[0].y = v[0].z = v[1].x = v[1].y = v[1].z = v[2].x = 0;
                    v[2].y = lds32(r0); v[2].z = lds32(r0 + 16); v[3].x = lds32(r0 + 32); v[3].y = lds32(r0 + 48); v[3].z = lds32(r0 + 64); v[4].x = lds32(r0 + 80); v[4].y = lds32(r0 + 96);
                    #pragma unroll
                    for (int j = 0; j < 5; j++) v[5 + j] = v[j];
                }
                mbar_wait(bar_free, 0);
                #pragma unroll
                for (int p = 0; p < 2; p++) {
                    const uint4* u = v + 5 * p;
                    stsm_x4(ha + p * KV_PAR, u[0].x, u[0].y, u[0].z, u[1].x);
                    stsm_x4(ha + p * KV_PAR + 64, u[1].y, u[1].z, u[2].x, u[2].y);
                    stsm_x4(ha + p * KV_PAR + 128, u[2].z, u[3].x, u[3].y, u[3].z);
                    stsm_x2(ha + p * KV_PAR + 192, u[4].x, u[4].y);
                }
                __syncwarp();
                if (lane == 0) { mbar_arrive(bar_halo); TR(10); TRG(100); }
                if (OPOLL2_ON && !late) {
                    mbar_wait(bar_ab + 8, 0);
                    const uint32_t at = ta + TP(OPOLL_AT) + TP(OPOLL2);
                    while ((int)(clk32() - at) < 0) { }
                    forward(&g_flag_o[mt * 32], epoch * 8, Int<2>(), bar_fl + 32, at);
                }
            } else {
                #pragma unroll 1
                for (int j = 2; j < (late ? 4 : 5); j++) {
                    const unsigned* const fl = j == 2 ? fl2 : j == 4 ? &g_flag_o[mt * 32] : lane < 24 ? fl3 : &g_flag_ab[(16 + 8 * r + (lane & 7)) * 32 + mt];
                    const uint32_t at = ta + (j == 2 ? TP(POLL_AT2) : j == 3 ? TP(POLL_AT3) : TP(OPOLL_AT));
                    if (!rest) { while ((int)(clk32() - at) < 0) { } }
                    if (OPOLL2_ON && j == 4) { mbar_wait(bar_ab + 8, 0); forward(fl, epoch * 8, Int<2>(), bar_fl + 32, at); } else
                    forward(fl, j == 4 ? epoch * 8 : epoch, Int<0>(), bar_fl + 8 * j, at);
                    if (lane == 0) TR(j == 3 ? 39 : j == 4 ? 13 : 35 + j);
                }
                mbar_wait_limit(bar_end, 0);
            }
            __syncwarp();
        }
      }
      TR_END();
    } else {
        if (tid == 128) {
            mbar_init(bar_ab, 4); mbar_init(bar_ab + 8, 6); mbar_init(bar_free, 1); mbar_init(bar_free + 8, 1); mbar_init(bar_qkv, 4); mbar_init(bar_qkv + 8, 4); mbar_init(bar_o, 8);
            mbar_init(bar_halo, 1); mbar_init(bar_end, 3);
            #pragma unroll
            for (int j = 0; j < 7; j++) mbar_init(bar_go + 8 * j, 1);
            mbar_init(bar_sf, 1); mbar_init(bar_se, 2); mbar_init(bar_af, 4);
            asm volatile("fence.mbarrier_init.release.cluster;" ::: "memory");
        }
        __syncwarp();
        cluster_arrive();
        if (warp >= 8) {
            float d[4];
            #pragma unroll 1
            for (int i = 0; i < TP(WARM_N); i++) {
                const uint32_t t1 = clk32();
                wgmma_fence();
                wgmma_n8<1, 0>(d, desc_k(sb + 7 * AB_BYTES), desc_k(sb + 7 * AB_BYTES), 0);
                wgmma_commit();
                wgmma_wait<0>();
                while ((int)(clk32() - t1) < TP(WARM_GAP)) { }
                __syncwarp();
            }
        }
        cluster_wait();
        const int wg = warp >> 3, w = warp & 3, cw = warp - 4;

        const bool sig_local = (tid & 127) == 0;
        const int i8 = lane & 7, m = lane >> 3;
        const bool sig = (tid & 95) == 0;
        uint32_t rel;
        asm("mapa.shared::cluster.u32 %0, %1, %2;" : "=r"(rel) : "r"(bar_empty), "r"(r ^ (w & 1)));
        auto done = [&](int it) { (void)it; if ((tid & 127) == 64) TRL(160 + it); };
        auto release = [&](int s) { if (sig) asm volatile("mbarrier.arrive.shared::cluster.b64 _, [%0];" :: "r"(rel + 8 * s) : "memory"); };
        const uint32_t dA = desc_k(sb + wg * 8192), dB = desc_k(sb + SLOT_A), dBt = desc_mn(sb + SLOT_A);
        const uint32_t a_frag = sb + wg * 8192 + (w * 16 + (lane & 15)) * 128 + (((lane >> 4) ^ i8) << 4);
        auto wait_full = [&](int it) { mbar_wait(bar_full + 8 * (it & 3), (it >> 2) & 1); if (sig_local) TR(128 + wg * 64 + it); };
        uint32_t kq[4][4], vq[14], qb[2][8];
        {
            float aq[28], ak[28], av[28];
            uint32_t mh0 = 0;
            uint32_t af[2][4][4];
            auto load_af = [&](int it) {
                wait_full(it);
                #pragma unroll
                for (int k = 0; k < 4; k++) ldsm_x4((a_frag ^ (k << 5)) + (it & 3) * SLOT_BYTES, af[it & 1][k][0], af[it & 1][k][1], af[it & 1][k][2], af[it & 1][k][3]);
            };
            uint32_t abw[28], base;
            auto stage_ab = [&](int j0, int j1) {
                #pragma unroll
                for (int j = j0; j < j1; j++) {
                    if (j < 7) stsm_x4_t(base + j * 2048, abw[4 * j], abw[4 * j + 1], abw[4 * j + 2], abw[4 * j + 3]);
                    else { __syncwarp(); if (lane == 0) mbar_arrive(bar_ab + 8 * wg); }
                }
            };
            {
                float bacc[56];
                base = pin((wg ? stg : sb + 7 * AB_BYTES) + (((2 * w + (m & 1)) ^ i8) << 4) + ((m >> 1) * 8 + i8) * 128);
                auto ab_loop = [&](auto sign) {
                auto ab_issue = [&](int kb) {
                    mbar_wait_p(bar_abf + 8 * kb, 0);
                    if (kb == 0 && wg == 1) asm volatile("bar.sync 3, 256;" ::: "memory");
                    if (sig_local) TR(112 + wg * 8 + kb);
                    wgmma_fence();
                    #pragma unroll
                    for (int k = 0; k < 4; k++) wgmma_n112<decltype(sign)::value, 0>(bacc, dA + kb * (AB_BYTES >> 4) + 2 * k, dB + kb * (AB_BYTES >> 4) + 2 * k, (kb | k) != 0);
                    wgmma_commit();
                    if (kb == 0 && wg == 0) asm volatile("bar.arrive 3, 256;" ::: "memory");
                };
                #pragma unroll
                for (int kb = 0; kb < 5; kb++) {
                    ab_issue(kb);
                    if (kb > 0) wgmma_wait<1>();
                    if (kb == 2 || kb == 3) release(kb - 2);
                }
                if (wg == 0) {
                    ab_issue(5);
                    ab_issue(6);
                    asm volatile("bar.arrive 4, 256;" ::: "memory");
                    wgmma_wait<2>();
                    release(2);
                } else {
                    uint32_t xf[8][4];
                    #pragma unroll
                    for (int j = 0; j < 8; j++) {
                        if ((j & 3) == 0) mbar_wait(bar_abf + 8 * (5 + (j >> 2)), 0);
                        ldsm_x4((a_frag ^ ((j & 3) << 5)) + (5 + (j >> 2)) * AB_BYTES, xf[j][0], xf[j][1], xf[j][2], xf[j][3]);
                    }
                    wgmma_wait<0>();
                    release(2);
                    asm volatile("bar.sync 4, 256;" ::: "memory");
                    wgmma_fence();
                    #pragma unroll
                    for (int j = 0; j < 8; j++) {
                        wgmma_rs_n112<0, decltype(sign)::value>(bacc, xf[j], dB + (5 + (j >> 2)) * (AB_BYTES >> 4) + 2 * (j & 3), 1);
                        if ((j & 3) == 3) wgmma_commit();
                    }
                }
                };
                if (sub >> 2) ab_loop(Int<-1>()); else ab_loop(Int<1>());
                wgmma_wait<1>();
                release(3);
                reg_set<REG_CONS>();
                if (wg == 1) load_af(0);
                wgmma_wait<0>();
                if (sig_local) TRX(21 + wg);
                if (AB_ST) { if (wg == 0) asm volatile("bar.arrive 3, 256;" ::: "memory"); else asm volatile("bar.sync 3, 256;" ::: "memory"); }
                #pragma unroll
                for (int j = 0; j < 28; j++) abw[j] = pack_bf16(bacc[2 * j], bacc[2 * j + 1]);
                stage_ab(0, AB_ST);
                if (wg == 0 || AB_ST == 7) stage_ab(AB_ST, 8);
            }
            const uint32_t dQ = dBt + (sub & 1);
            #pragma unroll
            for (int it = 0; it < 7; it++) {
                const uint32_t o = (it & 3) * (SLOT_BYTES >> 4);
                if (it > 0 || wg == 0) load_af(it);
                if (it == 5) mh0 = pin((lane & 3) < 2 ? 0xffffffffu : 0u);
                if (AB_ST < 7 && wg == 1) { if (it == 1) stage_ab(AB_ST, AB_ST2); if (it == 2) stage_ab(AB_ST2, 8); }
                wgmma_wait<0>();
                if (it > 0) { release((it - 1) & 3); done(it - 1); }
                if (it == 0 && sig_local) TRL(60 + wg);
                if (wg == 0) { if (it > 0) asm volatile("bar.sync 6, 256;" ::: "memory"); } else asm volatile("bar.sync 8, 256;" ::: "memory");
                wgmma_fence();
                #pragma unroll
                for (int j = 0; j < 12; j++) {
                    const int k = it < 6 || !KV_FIRST ? j / 3 : j < 8 ? j >> 1 : j - 8, x = it < 6 || !KV_FIRST ? j % 3 : j < 8 ? j & 1 : 2;
                    const uint32_t d = dQ + o + (k >> 1) * 768 + (k & 1) * 128;
                    if (j == Q_ARR) { if (wg == 0) asm volatile("bar.arrive 8, 256;" ::: "memory"); else asm volatile("bar.arrive 6, 256;" ::: "memory"); }
                    if (x == 0) wgmma_rs_n56<1>(ak, af[it & 1][k], d + 256, (it | k) != 0);
                    if (x == 1) wgmma_rs_n56<1>(av, af[it & 1][k], d + 512, (it | k) != 0);
                    if (x == 2) wgmma_rs_n56<1>(aq, af[it & 1][k], d, (it | k) != 0);
                    if (KV_FIRST && it == 6 && j == 7) wgmma_commit();
                }
                wgmma_commit();
            }
            uint4* const hp = pin(g_halo + (mt * 8 + sub) * 320 + wg * 160 + lane);
            mbar_wait(bar_ab + 8, 0);
            const uint32_t epoch = lds32(bars + 168);
            wgmma_wait<KV_FIRST>();
            #pragma unroll
            for (int j = 0; j < 16; j++) kq[j >> 2][j & 3] = pin(pack_bf16(ak[2 * (j - 2 * (j > 7))], ak[1 + 2 * (j - 2 * (j > 7))]));
            #pragma unroll
            for (int j = 0; j < 14; j++) vq[j] = pin(pack_bf16(av[2 * j], av[2 * j + 1]));
            if (w == 3 && !(ABL & 1)) {
                st_b128_relaxed(hp, kq[0][1], kq[0][3], kq[1][1], epoch);
                st_b128_relaxed(hp + 32, kq[1][3], kq[2][3], kq[3][1], epoch);
                st_b128_relaxed(hp + 64, kq[3][3], vq[1], vq[3], epoch);
                st_b128_relaxed(hp + 96, vq[5], vq[7], vq[9], epoch);
                st_b128_relaxed(hp + 128, vq[11], vq[13], 0u, epoch);
                if (lane == 0) TR(8);
            }
            wgmma_wait<0>();
            release(6 & 3);
            if (sig_local) TRX(23 + wg);
            #pragma unroll
            for (int j = 0; j < 14; j++) qb[j & 1][(j >> 1) + (j > 7)] = pin(pack_bf16(aq[2 * j], aq[2 * j + 1]));
            #pragma unroll
            for (int j = 0; j < 2; j++) { qb[j][4] = qb[j][3] & ~mh0; qb[j][3] &= mh0; }
        }
        float acc[112];
        const int it1 = 7 + nj;
        auto big_issue = [&](int slot, bool first) {
            wgmma_fence();
            #pragma unroll
            for (int k = 0; k < 4; k++) wgmma_n224<1, 0>(acc, dA + slot * (SLOT_BYTES >> 4) + 2 * k, dB + slot * (SLOT_BYTES >> 4) + 2 * k, !first || k != 0);
            wgmma_commit();
        };
        if (wg == 1) {
            asm volatile("bar.sync 7, 256;" ::: "memory");
            big_issue(3, true);
        } else {
            wait_full(7);
            asm volatile("bar.sync 6, 256;" ::: "memory");
            big_issue(3, true);
            asm volatile("bar.arrive 7, 256;" ::: "memory");
            if (sig_local) TR(20);
        }
        {
            auto plain = [&](int it) {
                wait_full(it); wgmma_wait<0>(); release((it - 1) & 3); done(it - 1); big_issue(it & 3, false);
                mbar_wait(bar_free, 0);
            };
            auto before_mma = [&](int it, int last) {
                if (wg == last) {
                    mbar_wait_limit(bar_full + 8 * (it & 3), (it >> 2) & 1);
                    if (sig_local) TR(128 + last * 64 + it);
                    asm volatile("bar.sync 2, 256;" ::: "memory");
                    wgmma_wait<0>();
                    release((it - 1) & 3);
                    done(it - 1);
                } else {
                    if (GAP_FLIP) { wgmma_wait<0>(); release((it - 1) & 3); }
                    asm volatile("bar.arrive 2, 256;" ::: "memory");
                }
            };
            auto after_mma = [&](int it, int last) {
                if (wg == (last ^ 1)) {
                    if (!GAP_FLIP) { wgmma_wait<0>(); release((it - 1) & 3); }
                    asm volatile("bar.sync 7, 256;" ::: "memory");
                    big_issue(it & 3, false);
                } else {
                    big_issue(it & 3, false);
                    asm volatile("bar.arrive 7, 256;" ::: "memory");
                }
            };
            const uint32_t kvw = stg + KV_OFF + wg * KV_PAR + (w * 16 + i8) * KV_PITCH;
            const uint32_t a_k = kvw + (m & 1) * 8 * KV_PITCH + (m >> 1) * 16, a_v = kvw + (m >> 1) * 8 * KV_PITCH + 112 + (m & 1) * 16;
            mbar_wait(bar_free, 0);
            #pragma unroll
            for (int u = 0; u < (ABL & 64 ? 0 : 3); u++) stsm_x4(a_k + 8 * KV_PITCH + 112 + u * 32, vq[4 * u], vq[4 * u + 1], vq[4 * u + 2], vq[4 * u + 3]);
            if (!(ABL & 64)) stsm_x2(a_k + 8 * KV_PITCH + 112 + 96, vq[12], vq[13]);
            plain(8);
            #pragma unroll
            for (int u = 0; u < (ABL & 64 ? 1 : 4); u++) stsm_x4(a_k + 8 * KV_PITCH + (2 * u - (u > 1)) * 16, kq[u][0], kq[u][1], kq[u][2], kq[u][3]);
            __syncwarp();
            if (lane == 0) mbar_arrive(bar_qkv + 8 * wg);
            if (sig_local) TR(25 + wg);
            uint32_t kp[4][4], vt[8][4], pb[4][2];
            auto load_v = [&](int n) {
                #pragma unroll
                for (int u = 0; u < 4; u++) {
                    if ((ABL & 64) && u > 0) { vt[2 * u + n][0] = vq[u]; vt[2 * u + n][1] = vq[u + 4]; vt[2 * u + n][2] = vq[u + 8]; vt[2 * u + n][3] = vq[u + n]; } else
                    ldsm_x4_t(a_v + n * 8 * KV_PITCH + (2 * u - (u > 1)) * 16, vt[2 * u + n][0], vt[2 * u + n][1], vt[2 * u + n][2], vt[2 * u + n][3]);
                }
            };
            load_v(1);
            plain(9);
            if (QK_AT > 10) plain(10);
            mbar_wait(w == 0 && !(ABL & 2) ? bar_halo : bar_qkv + 8 * wg, 0);
            #pragma unroll
            for (int u = 0; u < 4; u++) {
                if ((ABL & 64) && u > 0) { kp[u][0] = kq[u][1]; kp[u][1] = kq[u][0]; kp[u][2] = kq[u][3]; kp[u][3] = kq[u][2]; } else
                ldsm_x4(a_k + (2 * u - (u > 1)) * 16, kp[u][0], kp[u][1], kp[u][2], kp[u][3]);
            }
            if (sig_local) TR(54 + wg);
            before_mma(QK_AT, GAP_FLIP);
            float s[4][4];
            #pragma unroll
            for (int i = 0; i < 16; i++) s[i >> 2][i & 3] = 0.f;
            #pragma unroll
            for (int i = 0; i < (ABL & 4 ? 0 : 8); i++) {
                const int n = i & 1, h = (i >> 1) & 1, ks = 2 * h + (i >> 2);
                if (n) mma16816(s[i & 3], kq[ks][0], kq[ks][1], kq[ks][2], kq[ks][3], qb[1][2 * ks], qb[1][2 * ks + 1]);
                else mma16816(s[i & 3], kp[ks][0], kp[ks][1], kp[ks][2], kp[ks][3], qb[0][2 * ks], qb[0][2 * ks + 1]);
            }
            #pragma unroll
            for (int i = 0; i < 16; i++) asm volatile("" : "+f"(s[i >> 2][i & 3]) :: "memory");
            after_mma(QK_AT, GAP_FLIP);
            if (sig_local) TR(48 + wg);
            const int g = lane >> 2, t2 = 2 * (lane & 3);
            const uint32_t mlo = (t2 > g ? 0xffffu : 0u) | (t2 + 1 > g ? 0xffff0000u : 0u), before = (mt | w) == 0 ? mlo : 0u;
            uint32_t y[4], mx[2];
            #pragma unroll
            for (int i = 0; i < 4; i++) {
                const uint32_t x = pack_bf16(g > t2 ? s[i][0] : s[i][2], g > t2 + 1 ? s[i][1] : s[i][3]);
                y[i] = movm_t(pack_bf16(bf_lo(x) * ATT_SCALE, bf_hi(x) * ATT_SCALE));
                if (!(i & 1)) y[i] = (y[i] & ~before) | (MASKED & before);
            }
            #pragma unroll
            for (int h = 0; h < 2; h++) {
                mx[h] = max_bf16x2(__byte_perm(y[2 * h], y[2 * h + 1], 0x5410), __byte_perm(y[2 * h], y[2 * h + 1], 0x7632));
                mx[h] = pin(max_bf16x2(mx[h], __shfl_xor_sync(0xffffffffu, mx[h], 1)));
            }
            load_v(0);
            if (sig_local) TR(50 + wg);
            const bool second = wg == (GAP_FLIP ^ 1);
            if (SM_CUT == 0 || !second) plain(QK_AT + 1);
            #pragma unroll
            for (int h = 0; h < 2; h++) mx[h] = max_bf16x2(mx[h], __shfl_xor_sync(0xffffffffu, mx[h], 2));
            float e0[4], e1[4], sum[4];
            #pragma unroll
            for (int i = 0; i < 4; i++) {
                const float mi = i & 1 ? bf_hi(mx[i >> 1]) : bf_lo(mx[i >> 1]);
                e0[i] = ex2_approx((bf_lo(y[i]) - mi) * LOG2E); e1[i] = ex2_approx((bf_hi(y[i]) - mi) * LOG2E);
                sum[i] = e0[i] + e1[i];
                if (SM_CUT == 1) { e0[i] = pin(e0[i]); e1[i] = pin(e1[i]); sum[i] = pin(sum[i]); }
            }
            if (SM_CUT == 1 && second) plain(QK_AT + 1);
            #pragma unroll
            for (int i = 0; i < 4; i++) {
                sum[i] += __shfl_xor_sync(0xffffffffu, sum[i], 1);
                if (SM_CUT == 2) { e0[i] = pin(e0[i]); e1[i] = pin(e1[i]); sum[i] = pin(sum[i]); }
            }
            if (SM_CUT == 2 && second) plain(QK_AT + 1);
            #pragma unroll
            for (int i = 0; i < 4; i++) {
                sum[i] += __shfl_xor_sync(0xffffffffu, sum[i], 2);
                const float inv = rcp_approx(sum[i]);
                const uint32_t p = pack_bf16(e0[i] * inv, e1[i] * inv);
                pb[i][0] = pin(p & mlo); pb[i][1] = pin(p & ~mlo);
            }
            if (sig_local) TR(52 + wg);
            before_mma(QK_AT + 2, 0);
            float ao[8][4];
            #pragma unroll
            for (int i = 0; i < 8; i++) {
                ao[i][0] = ao[i][1] = ao[i][2] = ao[i][3] = 0.f;
                if (!(ABL & 4)) mma16816(ao[i], vt[i][0], vt[i][1], vt[i][2], vt[i][3], pb[(i >> 2) * 2 + (i & 1)][0], pb[(i >> 2) * 2 + (i & 1)][1]);
            }
            #pragma unroll
            for (int i = 0; i < 32; i++) asm volatile("" : "+f"(ao[i >> 2][i & 3]) :: "memory");
            after_mma(QK_AT + 2, 0);
            if (sig_local) TRX(11 + wg);
            if (g >= 4) { ao[2][2] = ao[4][0]; ao[2][3] = ao[4][1]; ao[3][2] = ao[5][0]; ao[3][3] = ao[5][1]; }
            mbar_wait(bar_free + 8, 0);
            const uint32_t orow = stg + wg * 7168 + (m >> 1) * 1024 + (w * 16 + (lane & 15)) * 16;
            stsm_x4_t(orow, pack_bf16(ao[0][0], ao[0][1]), pack_bf16(ao[1][0], ao[1][1]), pack_bf16(ao[0][2], ao[0][3]), pack_bf16(ao[1][2], ao[1][3]));
            stsm_x4_t(orow + 2048, pack_bf16(ao[2][0], ao[2][1]), pack_bf16(ao[3][0], ao[3][1]), pack_bf16(ao[2][2], ao[2][3]), pack_bf16(ao[3][2], ao[3][3]));
            stsm_x4_t(orow + 4096, pack_bf16(ao[4][2], ao[4][3]), pack_bf16(ao[5][2], ao[5][3]), pack_bf16(ao[6][0], ao[6][1]), pack_bf16(ao[7][0], ao[7][1]));
            stsm_x2_t(orow + 6144, pack_bf16(ao[6][2], ao[6][3]), pack_bf16(ao[7][2], ao[7][3]));
            __syncwarp();
            if (lane == 0) mbar_arrive(bar_o);
        }
        uint32_t af[4 * L_NB][4];
        #pragma unroll 1
        for (int it = QK_AT + 3; it < it1 - (late ? L_NB : 3); it++) {
            wait_full(it);
            wgmma_wait<0>();
            if (it != 7 + 32 - KB_EARLY - 4) release((it - 1) & 3);
            done(it - 1);
            big_issue(it & 3, false);
            if (L_PRE && it == 7 + 32 - KB_EARLY - L_NB - 2) {
                mbar_wait(bar_sf, 0);
                #pragma unroll
                for (int k = 0; k < 4; k++) ldsm_x4((a_frag ^ (k << 5)) + NSLOT * SLOT_BYTES, af[k][0], af[k][1], af[k][2], af[k][3]);
            }
        }
        mbar_wait(bar_fl + 24, 0);
        if (tid == 128) atomicAdd(&g_epoch[cta * 8], 1);
        __nv_bfloat16* const yp = pin(out + (size_t)(mt * 128 + cw * 16 + (lane >> 2)) * NOUT + DM + nh * 256 + (lane & 3) * 8);
        const int y6 = 192 - nh * 224;
        #define Y_WORD(A, i, jj) pack_bf16(A[16 * ((i) >> 1) + 4 * (jj) + 2 * ((i) & 1)], A[16 * ((i) >> 1) + 4 * (jj) + 2 * ((i) & 1) + 1])
        #define Y_ADDR(i) (yp + ((i) & 1) * 8 * NOUT + ((i) < 12 ? ((i) >> 1) * 32 : y6))
        const bool odd = lane & 4;
        __nv_bfloat16* const yq = pin(odd ? yp - NOUT + 32 : yp);
        #define Y_PAIR(A, i, B, j, rh, C, PAUSE) do { \
            uint32_t x_[4], y_[4]; \
            _Pragma("unroll") \
            for (int jj = 0; jj < 4; jj++) { \
                const uint32_t u_ = Y_WORD(A, 2 * (i) + (rh), jj), v_ = Y_WORD(B, 2 * (j) + (rh), jj), o_ = __shfl_xor_sync(0xffffffffu, odd ? u_ : v_, 4); \
                x_[jj] = odd ? o_ : u_; y_[jj] = odd ? v_ : o_; \
            } \
            red_add_bf16x8(yq + (rh) * 8 * NOUT + (C), x_[0], x_[1], x_[2], x_[3]); \
            PAUSE; \
            red_add_bf16x8(yq + ((rh) * 8 + 1) * NOUT + (C), y_[0], y_[1], y_[2], y_[3]); \
        } while (0)
        if (late) {
            constexpr int IT = 7 + 32 - KB_EARLY - L_NB;
            #define L_SLOT(j) ((j) == 0 ? NSLOT : (IT + (j) - 1) & 3)
            auto load_af = [&](int j) {
                if (j == 0) mbar_wait(bar_sf, 0); else wait_full(IT + j - 1);
                #pragma unroll
                for (int k = 0; k < 4; k++) ldsm_x4((a_frag ^ (k << 5)) + L_SLOT(j) * SLOT_BYTES, af[4 * j + k][0], af[4 * j + k][1], af[4 * j + k][2], af[4 * j + k][3]);
            };
            if (!L_PRE) load_af(0);
            load_af(1);
            if (L_UP) load_af(2);
            wgmma_wait<0>();
            done(IT - 1);
            if (!L_UP && wg == 1) load_af(2);
            if (L_NB == 4 && wg == 1) load_af(L_NB - 1);
            auto issue = [&](auto& p, auto c0, int j0, int j1, bool first, bool last) {
                constexpr int W = sizeof(p) / 2, C0 = decltype(c0)::value;
                if (wg == 0) { if (!first) asm volatile("bar.sync 9, 256;" ::: "memory"); } else asm volatile("bar.sync 5, 256;" ::: "memory");
                wgmma_fence();
                #pragma unroll
                for (int j = j0; j < j1; j++) {
                    if (!L_UP && first && j == 8) { if (wg == 0) load_af(2); wgmma_fence(); }
                    if (L_NB == 4 && first && j == 12) { if (wg == 0) load_af(L_NB - 1); wgmma_fence(); }
                    if (j == j1 - 12 + L_ARR) { if (wg == 0) asm volatile("bar.arrive 5, 256;" ::: "memory"); else if (!last) asm volatile("bar.arrive 9, 256;" ::: "memory"); }
                    const uint32_t d = dB + L_SLOT(j >> 2) * (SLOT_BYTES >> 4) + C0 * 8 + 2 * (j & 3);
                    if constexpr (W == 96) wgmma_rs_n96<0>(p, af[j], d, 1); else if constexpr (W == 64) wgmma_rs_n64<0>(p, af[j], d, 1); else wgmma_rs_n32<0>(p, af[j], d, 1);
                }
                wgmma_commit();
            };
            float pa[48], p0[32], p1[32];
            #pragma unroll
            for (int i = 0; i < 48; i++) asm volatile("mov.b32 %0, %1;" : "=f"(pa[i]) : "f"(acc[64 + i]));
            #pragma unroll
            for (int i = 0; i < 32; i++) asm volatile("mov.b32 %0, %1;" : "=f"(p1[i]) : "f"(acc[32 + i]));
            #pragma unroll
            for (int i = 0; i < 32; i++) asm volatile("mov.b32 %0, %1;" : "=f"(p0[i]) : "f"(acc[i]));
            issue(pa, Int<128>(), 0, 4 * L_NB, true, false);
            wgmma_wait<0>();
            if (sig_local) TRL(14 + wg);
            Y_PAIR(pa, 0, pa, 1, 0, 128, ); Y_PAIR(pa, 0, pa, 1, 1, 128, );
            #pragma unroll
            for (int i = 0; i < 2; i++) red_add_bf16x8(Y_ADDR(12 + i), Y_WORD(pa, 4 + i, 0), Y_WORD(pa, 4 + i, 1), Y_WORD(pa, 4 + i, 2), Y_WORD(pa, 4 + i, 3));
            issue(p0, Int<0>(), 0, 4 * L_NB, false, false);
            wgmma_wait<0>();
            Y_PAIR(p0, 0, p0, 1, 0, 0, ); Y_PAIR(p0, 0, p0, 1, 1, 0, );
            issue(p1, Int<64>(), 0, 4 * L_NB, false, true);
            if (sig_local) mbar_arrive(bar_end);
            wgmma_wait<0>();
            if (sig_local) TRX(27 + wg);
            Y_PAIR(p1, 0, p1, 1, 0, 64, ); Y_PAIR(p1, 0, p1, 1, 1, 64, );
            if (sig_local) TR(29 + wg);
        } else {
        constexpr int IT0 = 7 + KB_EARLY;
        auto load_af = [&](int j) {
            wait_full(IT0 - 3 + j);
            #pragma unroll
            for (int k = 0; k < 4; k++) ldsm_x4((a_frag ^ (k << 5)) + ((IT0 - 3 + j) & 3) * SLOT_BYTES, af[4 * j + k][0], af[4 * j + k][1], af[4 * j + k][2], af[4 * j + k][3]);
        };
        wait_full(IT0 - 3);
        wgmma_wait<0>();
        release((IT0 - 4) & 3);
        done(IT0 - 4);
        if (wg == 1) {
            load_af(0); load_af(1); load_af(2);
            asm volatile("bar.sync 5, 256;" ::: "memory");
            release((bar_af - bar_empty) / 8);
            #pragma unroll
            for (int it = IT0 - 3; it < IT0; it++) {
                if (it == IT0 - 1) { wgmma_wait<1>(); release((it - 2) & 3); }
                wgmma_fence();
                #pragma unroll
                for (int k = 0; k < 4; k++) wgmma_rs_n224<0>(acc, af[4 * (it - IT0 + 3) + k], dB + (it & 3) * (SLOT_BYTES >> 4) + 2 * k, 1);
                wgmma_commit();
            }
            asm volatile("bar.arrive 9, 256;" ::: "memory");
            wgmma_wait<1>();
            release((IT0 - 2) & 3);
            wgmma_wait<0>();
            release((IT0 - 1) & 3);
            if (sig_local) { mbar_arrive(bar_end); TRL(28); }
            const uint32_t t1 = clk32() + TP(RED_AT1);
            auto pause = [&](int i) {
                if (i == RW3) mbar_wait(bar_abf + 24, 1);
                if (i == RW4) mbar_wait(bar_abf + 32, 1);
                while ((int)(clk32() - t1) < i * TP(RED_GAP1)) { }
            };
            #pragma unroll
            for (int i = 0; i < 2; i++) { pause(i); red_add_bf16x8(Y_ADDR(12 + i), Y_WORD(acc, 12 + i, 0), Y_WORD(acc, 12 + i, 1), Y_WORD(acc, 12 + i, 2), Y_WORD(acc, 12 + i, 3)); }
            #pragma unroll
            for (int i = 0; i < 6; i++) { pause(2 + 2 * i); Y_PAIR(acc, i & 6, acc, (i & 6) + 1, i & 1, 32 * (i & 6), pause(3 + 2 * i)); }
            if (sig_local) TRX(30);
        } else {
            float lo[64], hi[48];
            #pragma unroll
            for (int i = 0; i < 48; i++) asm volatile("mov.b32 %0, %1;" : "=f"(hi[i]) : "f"(acc[64 + i]));
            #pragma unroll
            for (int i = 0; i < 64; i++) asm volatile("mov.b32 %0, %1;" : "=f"(lo[i]) : "f"(acc[i]));
            #pragma unroll
            for (int it = IT0 - 3; it < IT0; it++) {
                if (it == IT0 - 1) {
                    #pragma unroll
                    for (int k = 0; k < E_FILL; k++) wgmma_n96<1, 0>(hi, dA + ((IT0 - 3 + (k >> 2)) & 3) * (SLOT_BYTES >> 4) + 2 * (k & 3), dB + ((IT0 - 3 + (k >> 2)) & 3) * (SLOT_BYTES >> 4) + 1024 + 2 * (k & 3), 1);
                }
                if (it > IT0 - 3) wait_full(it);
                wgmma_fence();
                #pragma unroll
                for (int k = 0; k < 4; k++) wgmma_n128<1, 0>(lo, dA + (it & 3) * (SLOT_BYTES >> 4) + 2 * k, dB + (it & 3) * (SLOT_BYTES >> 4) + 2 * k, 1);
            }
            wgmma_commit();
            #define E_RED(i) do { if ((i) < 8) red_add_bf16x8(Y_ADDR(i), Y_WORD(lo, (i) & 7, 0), Y_WORD(lo, (i) & 7, 1), Y_WORD(lo, (i) & 7, 2), Y_WORD(lo, (i) & 7, 3)); \
                                  else red_add_bf16x8(Y_ADDR(i), Y_WORD(hi, (i) & 7, 0), Y_WORD(hi, (i) & 7, 1), Y_WORD(hi, (i) & 7, 2), Y_WORD(hi, (i) & 7, 3)); } while (0)
            #pragma unroll
            for (int j = E_FILL; j < 12; j++) {
                const int it = IT0 - 3 + (j >> 2), k = j & 3;
                if (j == E_FILL + E_SPLIT) {
                    wgmma_commit();
                    wgmma_wait<1>();
                    if (sig_local) TR(14);
                    #pragma unroll
                    for (int i = 0; i < RED_A; i++) E_RED(i);
                    wgmma_fence();
                }
                wgmma_n96<1, 0>(hi, dA + (it & 3) * (SLOT_BYTES >> 4) + 2 * k, dB + (it & 3) * (SLOT_BYTES >> 4) + 1024 + 2 * k, 1);
            }
            wgmma_commit();
            asm volatile("bar.arrive 5, 256;" ::: "memory");
            #pragma unroll
            for (int i = RED_A; i < RED_FAST; i++) E_RED(i);
            wgmma_wait<0>();
            release((bar_af - bar_empty) / 8); release((IT0 - 3) & 3); release((IT0 - 2) & 3); release((IT0 - 1) & 3);
            if (sig_local) TRL(27);
            const uint32_t t1 = clk32();
            #pragma unroll
            for (int i = RED_FAST; i < 14 - E_LATE; i++) {
                while ((int)(clk32() - t1) < (i - RED_FAST) * TP(RED_GAP)) { }
                E_RED(i);
            }
            if (sig_local) TR(29);
            float o0[56], o1[56];
            auto out_issue = [&](float (&oa)[56], int p, int j) {
                wgmma_fence();
                #pragma unroll
                for (int k = 0; k < (ABL & 32 ? 0 : 4); k++) wgmma_n112<1, 1, 8>(oa, dB + (63 << 16) + ((OUT_O(p, j) - SLOT_A) >> 4) + 128 * k, dB + ((((OUT_B(j) - OUT_A(j)) >> 4) - 1) << 16) + ((OUT_A(j) - SLOT_A) >> 4) + 128 * k, (j | k) != 0);
                wgmma_commit();
            };
            const uint32_t wa = pin(sb + w * 2048 + ((m & 1) * 8 + i8) * 128 + (((m >> 1) ^ i8) << 4)), ra = pin(sb + w * 2048 + m * 128 + ((i8 ^ m) << 4));
            auto stage = [&](float (&oa)[56], int buf, int u) {
                stsm_x4((wa ^ ((u & 3) << 5)) + buf + (u >> 2) * 8192, pack_bf16(oa[8 * u], oa[8 * u + 1]), pack_bf16(oa[8 * u + 2], oa[8 * u + 3]),
                        pack_bf16(oa[8 * u + 4], oa[8 * u + 5]), pack_bf16(oa[8 * u + 6], oa[8 * u + 7]));
            };
            __nv_bfloat16* const op = pin(out + (size_t)(mt * 128 + 1 + w * 32 + 2 * m) * NOUT + (sub & 3) * 64 + i8 * 8);
            const int c1 = 256 - (sub & 3) * 16;
            asm volatile("bar.sync 9, 256;" ::: "memory");
            #pragma unroll
            for (int j = 0; j < 7; j++) {
                if (!(j & 1)) { mbar_wait(bar_abf + 4 * j, 1); if (sig_local) TR(128 + IT0 + j); }
                out_issue(o0, 0, j);
                if (j < E_LATE) E_RED(14 - E_LATE + j);
            }
            #undef E_RED
            #pragma unroll
            for (int j = 0; j < 7; j++) {
                if (j == 3) { mbar_wait(bar_abf + 32, 1); if (sig_local) TR(192 + IT0 + j); }
                out_issue(o1, 1, j);
                if (j == 1) { wgmma_wait<2>(); if (sig_local) TR(31); }
                if (j >= 1 && j < 5) {
                    stage(o0, OUT_ST, 2 * j - 2);
                    if (j < 4) stage(o0, OUT_ST, 2 * j - 1);
                    if (j == 2 || j == 4) { __syncwarp(); if (lane == 0) mbar_arrive(bar_qkv + 4 * j - 8); }
                }
            }
            if (sig_local) mbar_arrive(bar_end);
            wgmma_wait<0>();
            if (sig_local) TRL(32);
            #pragma unroll
            for (int c = 0; c < 2; c++) {
                #pragma unroll
                for (int u = 4 * c; u < (c ? 7 : 4); u++) stage(o1, 0, u);
                __syncwarp();
                #pragma unroll
                for (int q = 0; q < 4; q++) {
                    uint4 v;
                    asm volatile("ld.shared.v4.u32 {%0, %1, %2, %3}, [%4];" : "=r"(v.x), "=r"(v.y), "=r"(v.z), "=r"(v.w) : "r"((ra ^ ((q & 1) << 6)) + c * 8192 + q * 512) : "memory");
                    if (c == 0 || i8 < 6) *reinterpret_cast<uint4*>(op + q * 8 * NOUT + (c ? c1 : 0)) = v;
                }
            }
        }
        }
        #undef Y_PAIR
        #undef Y_WORD
        #undef Y_ADDR
        if (sig_local) { TRX(33 + wg); if (wg == (late ? 1 : 0)) TRG(104); }
        TR_END();
    }
}

typedef CUresult (*EncodeFn)(CUtensorMap*, CUtensorMapDataType, cuuint32_t, void*, const cuuint64_t*, const cuuint64_t*,
                             const cuuint32_t*, const cuuint32_t*, CUtensorMapInterleave, CUtensorMapSwizzle,
                             CUtensorMapL2promotion, CUtensorMapFloatOOBfill);

void make_map(EncodeFn fn, CUtensorMap* tm, const void* ptr, uint64_t inner, uint64_t outer, uint32_t box_inner, uint32_t box_outer,
              CUtensorMapSwizzle sw = CU_TENSOR_MAP_SWIZZLE_128B, uint64_t clip = 0) {
    cuuint64_t gd[2] = {clip ? clip : inner, outer};
    cuuint64_t gs[1] = {inner * 2};
    cuuint32_t bd[2] = {box_inner, box_outer};
    cuuint32_t es[2] = {1, 1};
    fn(tm, CU_TENSOR_MAP_DATA_TYPE_BFLOAT16, 2, const_cast<void*>(ptr), gd, gs, bd, es, CU_TENSOR_MAP_INTERLEAVE_NONE,
       sw, CU_TENSOR_MAP_L2_PROMOTION_L2_128B, CU_TENSOR_MAP_FLOAT_OOB_FILL_NONE);
}
void make_map3(EncodeFn fn, CUtensorMap* tm, const void* ptr, uint64_t n0, uint64_t n1, uint64_t s1, uint64_t n2, uint64_t s2, uint32_t b1, uint32_t b2) {
    cuuint64_t gd[3] = {n0, n1, n2};
    cuuint64_t gs[2] = {s1 * 2, s2 * 2};
    cuuint32_t bd[3] = {64, b1, b2};
    cuuint32_t es[3] = {1, 1, 1};
    fn(tm, CU_TENSOR_MAP_DATA_TYPE_BFLOAT16, 3, const_cast<void*>(ptr), gd, gs, bd, es, CU_TENSOR_MAP_INTERLEAVE_NONE,
       CU_TENSOR_MAP_SWIZZLE_128B, CU_TENSOR_MAP_L2_PROMOTION_L2_128B, CU_TENSOR_MAP_FLOAT_OOB_FILL_NONE);
}
void make_map_perm(EncodeFn fn, CUtensorMap* tm, void* ptr, uint32_t n) {
    cuuint64_t gd[5] = {SEQ, 2, 4, 4, 28};
    cuuint64_t gs[4] = {SEQ * 2, 8 * SEQ * 2, 2 * SEQ * 2, 32 * SEQ * 2};
    cuuint32_t bd[5] = {64, 2, 4, 4, n};
    cuuint32_t es[5] = {1, 1, 1, 1, 1};
    fn(tm, CU_TENSOR_MAP_DATA_TYPE_BFLOAT16, 5, ptr, gd, gs, bd, es, CU_TENSOR_MAP_INTERLEAVE_NONE,
       CU_TENSOR_MAP_SWIZZLE_128B, CU_TENSOR_MAP_L2_PROMOTION_L2_128B, CU_TENSOR_MAP_FLOAT_OOB_FILL_NONE);
}

}

extern "C" void kernel_launch(void* const* d_in, const int* in_sizes, int n_in, void* d_out, int out_size) {
    (void)in_sizes; (void)n_in; (void)out_size;
    static EncodeFn fn = nullptr;
    static void* p_abT = nullptr;
    if (!fn) {
        void* p = nullptr; cudaDriverEntryPointQueryResult qr;
        cudaGetDriverEntryPoint("cuTensorMapEncodeTiled", &p, cudaEnableDefault, &qr);
        fn = (EncodeFn)p;
        cudaGetSymbolAddress(&p_abT, g_abT);
        cudaFuncSetAttribute(fused_kernel, cudaFuncAttributeMaxDynamicSharedMemorySize, SMEM_BYTES);
    }
    TMaps tm;
    make_map3(fn, &tm.xA3, d_in[0], DM, SEQ / 2, 2 * DM, 2, DM, 64, 2);
    make_map3(fn, &tm.wqkv3, d_in[1], DM, DM, 3 * DM, 3, DM, 32, 3);
    make_map(fn, &tm.wo64, d_in[2], DM, DM, 64, 64);
    make_map3(fn, &tm.outA, d_out, 64, SEQ / 2, 2 * NOUT, 4, 64, 64, 1);
    make_map3(fn, &tm.outB, (const __nv_bfloat16*)d_out + 256, 48, SEQ / 2, 2 * NOUT, 4, 48, 64, 1);
    make_map(fn, &tm.xB, d_in[3], DM, SEQ, 64, 128);
    make_map(fn, &tm.wre, d_in[4], SEQ, SEQ, 64, 128);
    make_map(fn, &tm.wim, d_in[5], SEQ, SEQ, 64, 128);
    make_map(fn, &tm.wreH, d_in[4], SEQ, SEQ, 64, 64);
    make_map(fn, &tm.wimH, d_in[5], SEQ, SEQ, 64, 64);
    make_map(fn, &tm.wdre, d_in[6], DM, DM, 64, 112);
    make_map(fn, &tm.wdim, d_in[7], DM, DM, 64, 112);
    make_map_perm(fn, &tm.abP4, p_abT, 4);
    make_map_perm(fn, &tm.abP3, p_abT, 3);
    make_map(fn, &tm.abH, p_abT, SEQ, 896, 64, 16);
    make_map(fn, &tm.ab32, p_abT, SEQ, 896, 64, 32);
    make_map(fn, &tm.ab80, p_abT, SEQ, 896, 64, 80);
    fused_kernel<<<NCTA, 384, SMEM_BYTES, cudaStreamPerThread>>>((__nv_bfloat16*)d_out,
        tm);
}
```
